```python
import torch

def _softmax(x, axis=-1):
    return torch.softmax(x, dim=axis)
def _gelu(x):
    return torch.nn.functional.gelu(x, approximate="tanh")
def _silu(x):
    return torch.nn.functional.silu(x)
def _sigmoid(x):
    return torch.sigmoid(x)
def _layernorm(x, axis=-1, eps=1e-5):
    m = x.mean(dim=axis, keepdim=True)
    v = x.var(dim=axis, keepdim=True, unbiased=False)
    return (x - m) / torch.sqrt(v + eps)
def _scatter_add(tgt, idx, src, axis=0):
    return tgt.clone().index_add_(axis, idx, src)
def _segment_sum(src, seg, n):
    out = torch.zeros((n,) + src.shape[1:], dtype=src.dtype)
    return out.index_add_(0, seg, src)
def _pad(x, pw):
    flat = tuple(v for pair in reversed(pw) for v in pair)
    return torch.nn.functional.pad(x, flat)

kernel_name = 'concat_heads__mha_block_cached__compressed_kv_cla__decode'

def setup_inputs():

    _w = (lambda a: (lambda t: t.to(torch.bfloat16) if t.is_floating_point() else t)(torch.as_tensor(a)))
    def _A_setup():
        B, Sq, D = 4, 1, 576
        H, Sk, Dh = 32, 4096, 128
        return {
            "x": _w((lambda *s: torch.randn(*s, dtype=torch.bfloat16) * 1.6)(B, Sq, D)),
            "k_cache": _w((lambda *s: torch.randn(*s, dtype=torch.bfloat16) * 1.6)(B, H, Sk, Dh)),
            "v_cache": _w((lambda *s: torch.randn(*s, dtype=torch.bfloat16) * 0.05)(B, H, Sk, Dh)),
            "wq": _w((lambda *s: torch.randn(*s, dtype=torch.bfloat16) * 1.6)(D, H * Dh) * (D ** -0.5)),
            "wo": _w((lambda *s: torch.randn(*s, dtype=torch.bfloat16) * 0.05)(H * Dh, D) * ((H * Dh) ** -0.5)),
        }
    _A_in = _A_setup()

    def _B_setup():
        B, H, Sq, Sk, D, M = 4, 32, 1, 4096, 128, 576
        Dc = 4 * D
        return {
            "x": _w((lambda *s: torch.randn(*s, dtype=torch.bfloat16) * 3.2)(B, Sq, M)),
            "c_kv": _w((lambda *s: torch.randn(*s, dtype=torch.bfloat16) * 0.1)(B, Sk, Dc)),
            "w_q": _w((lambda *s: torch.randn(*s, dtype=torch.bfloat16) * 6.4)(M, H, D) * (M ** -0.5)),
            "w_uk": _w((lambda *s: torch.randn(*s, dtype=torch.bfloat16) * 6.4)(Dc, H, D) * (Dc ** -0.5)),
            "w_uv": _w((lambda *s: torch.randn(*s, dtype=torch.bfloat16) * 0.1)(Dc, H, D) * (Dc ** -0.5)),
            "w_o": _w((lambda *s: torch.randn(*s, dtype=torch.bfloat16) * 0.1)(H, D, M) * ((H * D) ** -0.5)),
        }
    _B_in = _B_setup()

    return {
        "A_x": _A_in["x"],
        "A_k_cache": _A_in["k_cache"],
        "A_v_cache": _A_in["v_cache"],
        "A_wq": _A_in["wq"],
        "A_wo": _A_in["wo"],
        "B_x": _B_in["x"],
        "B_c_kv": _B_in["c_kv"],
        "B_w_q": _B_in["w_q"],
        "B_w_uk": _B_in["w_uk"],
        "B_w_uv": _B_in["w_uv"],
        "B_w_o": _B_in["w_o"],
    }

def reference(A_x, A_k_cache, A_v_cache, A_wq, A_wo, B_x, B_c_kv, B_w_q, B_w_uk, B_w_uv, B_w_o):
    def _A_ref(x, k_cache, v_cache, wq, wo):
        B, Sq, D = x.shape
        H, Dh = 32, 128
        q = (lambda x, *d: x.permute(*d))((x @ wq).reshape(B, Sq, H, Dh), 0, 2, 1, 3)
        scores = torch.einsum("bhqd,bhkd->bhqk", q, k_cache) * (Dh ** -0.5)
        p = _softmax(scores, axis=-1)
        o = torch.einsum("bhqk,bhkd->bhqd", p, v_cache)
        return (lambda x, *d: x.permute(*d))(o, 0, 2, 1, 3).reshape(B, Sq, H * Dh) @ wo

    def _B_ref(x, c_kv, w_q, w_uk, w_uv, w_o):
        B, Sq, M = x.shape[0], x.shape[1], x.shape[2]
        Sk = c_kv.shape[1]
        H, D = w_q.shape[1], w_q.shape[2]
        q = torch.einsum("bqm,mhd->bhqd", x, w_q)
        k = torch.einsum("bkc,chd->bhkd", c_kv, w_uk)
        v = torch.einsum("bkc,chd->bhkd", c_kv, w_uv)
        scores = torch.einsum("bhqd,bhkd->bhqk", q, k) * (D ** -0.5)
        off = Sk - Sq
        qi = torch.arange(Sq)[:, None]
        kj = torch.arange(Sk)[None, :]
        cmask = kj <= (qi + off)
        scores = torch.where(cmask[None, None], scores, -1e9)
        p = _softmax(scores, axis=-1)
        ctx = torch.einsum("bhqk,bhkd->bhqd", p, v)
        return torch.einsum("bhqd,hdm->bqm", ctx, w_o)

    a = _A_ref(A_x, A_k_cache, A_v_cache, A_wq, A_wo)
    b = _B_ref(B_x, B_c_kv, B_w_q, B_w_uk, B_w_uv, B_w_o)
    return torch.concatenate([a, b], axis=-1)
```

```cpp
#include <cuda_runtime.h>
#include <cuda.h>
#include <cuda_bf16.h>
#include <stdint.h>

namespace {

constexpr int NH = 32, SK = 4096, DM = 576;
constexpr int KEYS = 128;
constexpr int UPP = SK / KEYS;
constexpr int NUK = 4 * NH * UPP;
constexpr int TILE_BYTES = KEYS * 256;
#define NWORK 2
constexpr int NW = NWORK;
constexpr int NBCTA = 32;
constexpr int MINCL = 15;
constexpr int NFIN = 72;
constexpr int SLOT = 32768;
constexpr int NSLOT = 6;
constexpr int BRING = 5;
constexpr int J0W = 5 * SLOT;
constexpr int MISC = NSLOT * SLOT + 4096;
constexpr int XP = 1168, CP = 1040, QP = 272;
constexpr int M_XA = MISC;
constexpr int M_XB = M_XA + 4 * XP;
constexpr int M_CH = M_XB + 4 * XP;
constexpr int M_CL = M_CH + 4 * CP;
constexpr int M_QB = M_CL + 4 * CP;
constexpr int M_QA = M_CH;
constexpr int M_J0 = M_QB + 4 * QP;
constexpr int M_P = M_J0 + 2048;
constexpr int M_ALPHA = M_P + 2560;
constexpr int M_OMEGA = M_ALPHA + 128;
constexpr int M_BAR = M_OMEGA + 128;
constexpr int M_HELP = M_BAR + 128;
#define PH 1
constexpr int NPC = 4 * PH, PKS = 8 / PH;
constexpr int F_W = 4 * SLOT;
constexpr int F_BF = M_HELP + 128;
constexpr int F_RX = F_BF + 4096;
constexpr int F_BAR = F_RX + 2048;
constexpr int SMEM_BYTES = F_BAR + 8 * (4 + 2 * NPC) + 1024;
static_assert(SMEM_BYTES <= 232448 && M_BAR % 8 == 0 && M_QA % 16 == 0 && M_P % 16 == 0, "smem layout");
#define XW 2
#define X3 1
#define X3C 2
#define NEARLY 2
#define BD 4
#define FPF 3
#define FSLEEP 800
#define VS0 24
#define GO0 (29 * 128 + 64)
#define GD0 0
#define GD1 2000
#define AD0 1000
#define AD1 2000
#define ERANK 8
#define GDC 0
#define NPOLL 2
#define PGAP 200
static_assert(NW + XW <= 4 && NEARLY <= NW + XW && BD <= BRING, "slots 4 and 5 hold the finisher weights");
constexpr int KMIN = 2, KMAX = 4, VMIN = 0, VMAX = 4;
constexpr float SCALE = 0.08838834764831845f;
constexpr float LOG2E = 1.4426950408889634f;
constexpr unsigned SPIN_LIMIT = 1u << 24;

#define NREP 2
#define NREPC 1
constexpr int C_QUEUE = 0, C_KDONE = 1, C_BBAR = 3, C_LINES = 5;

struct Params {
    const __nv_bfloat16 *kc, *xa, *vc, *wo, *xb;
    __nv_bfloat16* out;
    CUtensorMap tm_j0;
    CUtensorMap tm_wq, tm_wuk, tm_ckv, tm_wuv, tm_wo;
    CUtensorMap tm_fa, tm_fb;
};

__device__ unsigned g_epoch;
__device__ unsigned g_ctl[2][C_LINES][32];
__device__ uint2 g_qll[4 * 2048];
__device__ uint2 g_scores[128 * SK / 4];
__device__ float2 g_stats[128 * UPP];
__device__ float4 g_oacc[128 * 32];
__device__ unsigned g_vdone[NREP * NH][32];
__device__ float4 g_octx[128 * 32];
__device__ unsigned g_cdone[NH][32];
__device__ uint4 g_qabs[4 * 8 * 4 * 4 * 32];
__device__ float2 g_bpart[NBCTA * NH * 256];
__device__ float2 g_bml[NBCTA * NH];
__device__ uint4 g_outb[NBCTA * NH * 36];

#define TS(i)
#define TSV(i, v)
#define LAND(i)
#define CLK(x)
#define ACC(a, x, y)

__device__ __forceinline__ uint32_t smem_u32(const void* p) { return (uint32_t)__cvta_generic_to_shared(p); }
__device__ __forceinline__ void mbar_init(uint32_t bar, uint32_t cnt) {
    asm volatile("mbarrier.init.shared::cta.b64 [%0], %1;" ::"r"(bar), "r"(cnt) : "memory");
}
__device__ __forceinline__ void mbar_expect_tx(uint32_t bar, uint32_t bytes) {
    asm volatile("mbarrier.arrive.expect_tx.shared::cta.b64 _, [%0], %1;" ::"r"(bar), "r"(bytes) : "memory");
}
__device__ __forceinline__ bool mbar_try(uint32_t bar, uint32_t parity) {
    uint32_t ok;
    asm volatile("{\n.reg .pred p;\nmbarrier.try_wait.parity.shared::cta.b64 p, [%1], %2;\nselp.u32 %0, 1, 0, p;\n}\n"
                 : "=r"(ok) : "r"(bar), "r"(parity) : "memory");
    return ok;
}
__device__ __forceinline__ void mbar_wait(uint32_t bar, uint32_t parity) {
    unsigned n = 0;
    while (!mbar_try(bar, parity)) { if (++n > SPIN_LIMIT) __trap(); }
}
__device__ __forceinline__ void bulk_load(uint32_t dst, const void* src, uint32_t bytes, uint32_t bar, uint64_t pol) {
    asm volatile("cp.async.bulk.shared::cluster.global.mbarrier::complete_tx::bytes.L2::cache_hint [%0], [%1], %2, [%3], %4;"
                 ::"r"(dst), "l"(src), "r"(bytes), "r"(bar), "l"(pol) : "memory");
}
__device__ __forceinline__ void tma3d(uint32_t dst, const CUtensorMap* tm, int c0, int c1, int c2, uint32_t bar, uint64_t pol) {
    asm volatile("cp.async.bulk.tensor.3d.shared::cluster.global.mbarrier::complete_tx::bytes.L2::cache_hint [%0], [%1, {%3,%4,%5}], [%2], %6;"
                 ::"r"(dst), "l"(tm), "r"(bar), "r"(c0), "r"(c1), "r"(c2), "l"(pol) : "memory");
}
__device__ __forceinline__ void l2_prefetch(const void* src, uint32_t bytes) {
    asm volatile("cp.async.bulk.prefetch.L2.global [%0], %1;" ::"l"(src), "r"(bytes) : "memory");
}
__device__ __forceinline__ void ldsm4(uint32_t (&r)[4], uint32_t addr) {
    asm volatile("ldmatrix.sync.aligned.m8n8.x4.shared.b16 {%0,%1,%2,%3}, [%4];"
                 : "=r"(r[0]), "=r"(r[1]), "=r"(r[2]), "=r"(r[3]) : "r"(addr));
}
__device__ __forceinline__ void ldsm4t(uint32_t (&r)[4], uint32_t addr) {
    asm volatile("ldmatrix.sync.aligned.m8n8.x4.trans.shared.b16 {%0,%1,%2,%3}, [%4];"
                 : "=r"(r[0]), "=r"(r[1]), "=r"(r[2]), "=r"(r[3]) : "r"(addr));
}
__device__ __forceinline__ void mma16816(float (&d)[4], const uint32_t (&a)[4], uint32_t b0, uint32_t b1) {
    asm("mma.sync.aligned.m16n8k16.row.col.f32.bf16.bf16.f32 {%0,%1,%2,%3}, {%4,%5,%6,%7}, {%8,%9}, {%0,%1,%2,%3};"
        : "+f"(d[0]), "+f"(d[1]), "+f"(d[2]), "+f"(d[3])
        : "r"(a[0]), "r"(a[1]), "r"(a[2]), "r"(a[3]), "r"(b0), "r"(b1));
}
__device__ __forceinline__ uint32_t lds32(uint32_t a) {
    uint32_t v;
    asm volatile("ld.shared.u32 %0, [%1];" : "=r"(v) : "r"(a));
    return v;
}
__device__ __forceinline__ unsigned ld_acquire(const unsigned* p) {
    unsigned v;
    asm volatile("ld.acquire.gpu.global.u32 %0, [%1];" : "=r"(v) : "l"(p) : "memory");
    return v;
}
__device__ __forceinline__ uint2 ld_relaxed8(const void* p) {
    uint2 v;
    asm volatile("ld.relaxed.gpu.global.v2.u32 {%0,%1}, [%2];" : "=r"(v.x), "=r"(v.y) : "l"(p) : "memory");
    return v;
}
__device__ __forceinline__ unsigned ld_relaxed4(const void* p) {
    unsigned v;
    asm volatile("ld.relaxed.gpu.global.u32 %0, [%1];" : "=r"(v) : "l"(p) : "memory");
    return v;
}
__device__ __forceinline__ unsigned atom_inc(unsigned* p) {
    unsigned v;
    asm volatile("atom.relaxed.gpu.global.inc.u32 %0, [%1], 0x7fffffff;" : "=r"(v) : "l"(p) : "memory");
    return v;
}
__device__ __forceinline__ unsigned long long ld_relaxed64(const void* p) {
    unsigned long long v;
    asm volatile("ld.relaxed.gpu.global.u64 %0, [%1];" : "=l"(v) : "l"(p) : "memory");
    return v;
}
__device__ __forceinline__ void st_relaxed64(void* p, unsigned long long v) {
    asm volatile("st.relaxed.gpu.global.u64 [%0], %1;" ::"l"(p), "l"(v) : "memory");
}
__device__ __forceinline__ float4 ld_relaxed16(const void* p) {
    float4 v;
    asm volatile("ld.relaxed.gpu.global.v4.f32 {%0,%1,%2,%3}, [%4];" : "=f"(v.x), "=f"(v.y), "=f"(v.z), "=f"(v.w) : "l"(p) : "memory");
    return v;
}
__device__ __forceinline__ uint32_t mapa(uint32_t a, uint32_t rank) {
    uint32_t r;
    asm("mapa.shared::cluster.u32 %0, %1, %2;" : "=r"(r) : "r"(a), "r"(rank));
    return r;
}
__device__ __forceinline__ void fence_gpu() { asm volatile("fence.acq_rel.gpu;" ::: "memory"); }
__device__ __forceinline__ void red_add_u32(unsigned* p, unsigned v) {
    asm volatile("red.relaxed.gpu.global.add.u32 [%0], %1;" ::"l"(p), "r"(v) : "memory");
}
__device__ __forceinline__ void st_tagged2(void* p, float a, float b, unsigned tag) {
    const unsigned long long hi = (unsigned long long)tag << 32;
    asm volatile("st.relaxed.gpu.global.v2.b64 [%0], {%1,%2};" ::"l"(p), "l"(hi | __float_as_uint(a)), "l"(hi | __float_as_uint(b)) : "memory");
}
__device__ __forceinline__ ulonglong2 ld_tagged2(const void* p) {
    ulonglong2 v;
    asm volatile("ld.relaxed.gpu.global.v2.b64 {%0,%1}, [%2];" : "=l"(v.x), "=l"(v.y) : "l"(p) : "memory");
    return v;
}
__device__ __forceinline__ float4 atom_add_f4(void* p, float a, float b, float c, float d) {
    float4 r;
    asm volatile("atom.relaxed.gpu.global.add.v4.f32 {%0,%1,%2,%3}, [%4], {%5,%6,%7,%8};"
                 : "=f"(r.x), "=f"(r.y), "=f"(r.z), "=f"(r.w) : "l"(p), "f"(a), "f"(b), "f"(c), "f"(d) : "memory");
    return r;
}
__device__ __forceinline__ void red_release_cta_shared(uint32_t a, unsigned v) {
    asm volatile("red.release.cta.shared::cta.add.u32 [%0], %1;" ::"r"(a), "r"(v) : "memory");
}
__device__ __forceinline__ unsigned ld_acquire_cta_shared(uint32_t a) {
    unsigned v;
    asm volatile("ld.acquire.cta.shared::cta.u32 %0, [%1];" : "=r"(v) : "r"(a) : "memory");
    return v;
}
__device__ __forceinline__ void st_release_cta_shared(uint32_t a, unsigned v) {
    asm volatile("st.release.cta.shared::cta.u32 [%0], %1;" ::"r"(a), "r"(v) : "memory");
}
__device__ __forceinline__ void wait_count(const unsigned* p, unsigned target) {
    unsigned n = 0;
    while (ld_acquire(p) < target) { if (++n > SPIN_LIMIT) __trap(); }
}
__device__ __forceinline__ uint32_t pack_bf16(float lo, float hi) {
    uint32_t r;
    asm("cvt.rn.bf16x2.f32 %0, %1, %2;" : "=r"(r) : "f"(hi), "f"(lo));
    return r;
}
__device__ __forceinline__ float bf_lo(uint32_t v) { return __uint_as_float(v << 16); }
__device__ __forceinline__ float bf_hi(uint32_t v) { return __uint_as_float(v & 0xffff0000u); }
__device__ __forceinline__ float ex2(float x) { float y; asm("ex2.approx.ftz.f32 %0, %1;" : "=f"(y) : "f"(x)); return y; }
__device__ __forceinline__ float expsub(float a, float b) { return ex2((a - b) * LOG2E); }
__device__ __forceinline__ float warp_max(float v) {
#pragma unroll
    for (int m = 16; m; m >>= 1) v = fmaxf(v, __shfl_xor_sync(~0u, v, m));
    return v;
}
__device__ __forceinline__ float warp_sum(float v) {
#pragma unroll
    for (int m = 16; m; m >>= 1) v += __shfl_xor_sync(~0u, v, m);
    return v;
}
template <bool CLU>
__device__ __forceinline__ unsigned unit_block(int u) {
    const unsigned x = ((unsigned)u & (NUK - 1)) / UPP;
    const int lg = u < NUK ? min(KMAX, max(KMIN, 29 - __clz(x | 1))) : (CLU && (int)x >= 4 * VS0 ? 0 : min(VMAX, max(VMIN, 29 - __clz((127 - x) | 1))));
    const unsigned r = x & ((4u << lg) - 1);
    return ((x - r + (r & ((1u << lg) - 1)) * 4 + (r >> lg)) * UPP) | ((unsigned)u & (UPP - 1));
}
__device__ __forceinline__ const char* block_src(const void* base, unsigned blk) {
    const unsigned po = blk / UPP;
    return reinterpret_cast<const char*>(base) + (size_t)(((po & 3) * NH + (po >> 2)) * UPP + blk % UPP) * TILE_BYTES;
}

template <bool CLU>
__device__ __forceinline__ void a_worker(const Params& p, int un, bool once, bool pre, bool hold, int nstatic, uint32_t slot, uint32_t bar,
                                         uint32_t help, uint32_t go, unsigned epoch, uint64_t pol) {
    constexpr int NU = 2 * NUK, NR = CLU ? NREPC : NREP;
    const int lane = threadIdx.x & 31, g = lane >> 2, t = lane & 3;
    const int li = lane & 7;
    uint32_t kaddr[4], vaddr[8];
    {
        const int e = (lane >> 3) & 1, kk = lane >> 4;
#pragma unroll
        for (int s = 0; s < 4; s++) kaddr[s] = slot + (16 * li + e) * 256 + ((2 * s + kk + li) & 7) * 16;
        const int vrow = 4 * (li >> 1) + (li & 1) + 2 * kk;
#pragma unroll
        for (int c = 0; c < 8; c++) vaddr[c] = slot + vrow * 256 + e * 128 + ((c + li) & 7) * 16;
#pragma unroll
        for (int c = 0; c < 8; c++) asm volatile("" : "+r"(vaddr[c]));
    }
    const uint32_t vmask = (g >> 1) != t ? 0u : ((g & 1) ? 0xffff0000u : 0xffffu);
    int kseen = -1;
    unsigned long long H0 = 0, H1 = 0;
    auto header = [&](int v, unsigned vb) {
        if (v >= NU) return;
        const void *a0, *a1;
        if (v < NUK) {
            const unsigned po = vb / UPP;
            a0 = g_qll + (po & 3) * 2048 + (po >> 2) * 64 + lane;
            a1 = reinterpret_cast<const uint2*>(a0) + 32;
        } else {
            const int half = vb / (NUK / 2);
            if (half > kseen) {
                unsigned n = 0;
                while (ld_acquire_cta_shared(help + 12 + 4 * half) == 0) { if (++n > (SPIN_LIMIT << 4)) __trap(); }
                kseen = half;
            }
            a0 = &g_scores[vb * (KEYS / 4) + lane];
            a1 = &g_stats[(vb / UPP) * UPP + lane];
        }
        H0 = ld_relaxed64(a0);
        H1 = ld_relaxed64(a1);
    };
    asm volatile("bar.sync 2, %0;" ::"n"(32 * (NW + XW + 1)) : "memory");
    epoch = __shfl_sync(~0u, epoch, 0);
    if (hold) { unsigned n = 0; while (ld_acquire_cta_shared(help + 24) < 2) { if (++n > (SPIN_LIMIT << 4)) __trap(); } }
    unsigned (*ctl)[32] = g_ctl[epoch & 1];
    const unsigned tag = epoch + 1;
    unsigned nxt = once ? NU : 0;
    int u = -1;
    unsigned bu = 0, bn = unit_block<CLU>(un);
    bool have = false;
    uint32_t phase = 0;
    unsigned kpend = 0;
    const unsigned zero = gridDim.x >> 24;
    uint32_t Q[16];
    float4 oret = make_float4(0.f, 0.f, 0.f, 0.f);
    while (true) {
        const char* nsrc = block_src(un < NUK ? p.kc : p.vc, bn);
        float4* odst = &g_oacc[(bu / UPP) * 32 + lane];
        unsigned* vdst = &g_vdone[(lane & (NR - 1)) * NH + bu / (4 * UPP)][0];
        float d[8][4];
        CLK(c1);
        asm volatile("" : "+l"(odst));
        if (u >= NUK) {
#pragma unroll
            for (int j = 0; j < 8; j++) { d[j][0] = d[j][1] = d[j][2] = d[j][3] = 0.f; }
            mbar_wait(bar, phase);
            LAND(NUK + bu);
            uint32_t a[2][8][4];
#pragma unroll
            for (int c = 0; c < 8; c++) ldsm4t(a[0][c], vaddr[c]);
#pragma unroll
            for (int j = 0; j < 8; j++) {
                if (j < 7) {
#pragma unroll
                    for (int c = 0; c < 8; c++) ldsm4t(a[(j + 1) & 1][c], vaddr[c] + (j + 1) * 4096);
                }
#pragma unroll
                for (int c = 0; c < 8; c++) mma16816(d[c], a[j & 1][c], Q[2 * j], Q[2 * j + 1]);
            }
            float o[4];
#pragma unroll
            for (int r = 0; r < 2; r++) {
                o[2 * r] = d[0][2 * r] + d[7][2 * r + 1];
                o[2 * r + 1] = d[0][2 * r + 1] + d[1][2 * r];
#pragma unroll
                for (int k = 1; k < 4; k++) {
                    const int src = (lane & 28) | ((t - k) & 3);
                    o[2 * r] += __shfl_sync(~0u, d[2 * k][2 * r] + d[2 * k - 1][2 * r + 1], src);
                    o[2 * r + 1] += __shfl_sync(~0u, d[2 * k][2 * r + 1] + d[2 * k + 1][2 * r], src);
                }
            }
            oret = atom_add_f4(odst, o[0], o[1], o[2], o[3]);
        } else if (u >= 0) {
#pragma unroll
            for (int j = 0; j < 8; j++) { d[j][0] = d[j][1] = d[j][2] = d[j][3] = 0.f; }
            mbar_wait(bar, phase);
            LAND(bu);
            uint32_t a[2][8][4];
#pragma unroll
            for (int j = 0; j < 8; j++) ldsm4(a[0][j], kaddr[0] + (4 * (j & 3) + 2 * (j >> 2)) * 256);
#pragma unroll
            for (int s = 0; s < 8; s++) {
                if (s < 7) {
#pragma unroll
                    for (int j = 0; j < 8; j++)
                        ldsm4(a[(s + 1) & 1][j], kaddr[(s + 1) & 3] + (4 * (j & 3) + 2 * (j >> 2)) * 256 + ((s + 1) >> 2) * 128);
                }
#pragma unroll
                for (int j = 0; j < 8; j++)
                    mma16816(d[j], a[s & 1][j], Q[(s & 4) * 2 + ((2 * s - 2 * j) & 7)], Q[(s & 4) * 2 + ((2 * s + 1 - 2 * j) & 7)]);
            }
        }
        if (u >= 0) phase ^= 1;
        CLK(c2b);
        if (un < NU && lane == 0) {
            if (!once) nxt = atom_inc(&ctl[C_QUEUE][0]);
            if (u >= 0 || !pre) {
                mbar_expect_tx(bar, TILE_BYTES);
                bulk_load(slot, nsrc, TILE_BYTES, bar, pol);
            }
        }
        if (CLU && un >= NU && go && lane == 0) asm volatile("mbarrier.arrive.relaxed.cta.shared::cta.b64 _, [%0];" ::"r"(go) : "memory");
        CLK(c3);
        if ((unsigned)u < (unsigned)NUK) {
            const int j0 = (t - (g >> 1)) & 3;
            float v[4];
#pragma unroll
            for (int q = 0; q < 4; q++) {
                const int jq = (q >> 1) * 4, e = (q & 1) * 2;
                const float x0 = (g & 1) ? d[jq + 0][e + 1] : d[jq + 0][e];
                const float x1 = (g & 1) ? d[jq + 1][e + 1] : d[jq + 1][e];
                const float x2 = (g & 1) ? d[jq + 2][e + 1] : d[jq + 2][e];
                const float x3 = (g & 1) ? d[jq + 3][e + 1] : d[jq + 3][e];
                const float y0 = (j0 & 1) ? x1 : x0, y1 = (j0 & 1) ? x3 : x2;
                v[q] = (j0 & 2) ? y1 : y0;
            }
            const uint32_t r0 = pack_bf16(v[0], v[1]), r1 = pack_bf16(v[2], v[3]);
            const uint32_t s0 = pack_bf16(bf_lo(r0) * SCALE, bf_hi(r0) * SCALE);
            const uint32_t s1 = pack_bf16(bf_lo(r1) * SCALE, bf_hi(r1) * SCALE);
            g_scores[bu * (KEYS / 4) + 4 * g + j0] = make_uint2(s0, s1);
            const float f0 = bf_lo(s0), f1 = bf_hi(s0), f2 = bf_lo(s1), f3 = bf_hi(s1);
            const float m = warp_max(fmaxf(fmaxf(f0, f1), fmaxf(f2, f3)));
            const float l = warp_sum((expsub(f0, m) + expsub(f1, m)) + (expsub(f2, m) + expsub(f3, m)));
            if (lane == 0) g_stats[bu] = make_float2(m, l);
            kpend++;
            if (un / (NUK / 2) != u / (NUK / 2)) {
                __syncwarp();
                if (lane == 0) {
                    red_release_cta_shared(help + 4 * (u / (NUK / 2)), kpend);
                    if (un >= NUK) red_release_cta_shared(help + 8, 1u);
                }
                kpend = 0;
            }
        }
        CLK(c4);
        int unn = NU;
        if (un < NU) {
            unsigned n = 0;
            while (true) {
                if (!have) header(un, bn);
                if (un >= NUK || __all_sync(~0u, (uint32_t)(H0 >> 32) == tag && (uint32_t)(H1 >> 32) == tag)) break;
                if (++n > SPIN_LIMIT) __trap();
                have = false;
            }
            if (un >= NUK) {
                const uint32_t s0 = (uint32_t)H0, s1 = (uint32_t)(H0 >> 32);
                const float mu = __uint_as_float((uint32_t)H1);
                const float m = warp_max(mu);
                const float l = warp_sum(__uint_as_float((uint32_t)(H1 >> 32)) * expsub(mu, m));
                const float inv = 1.0f / l;
                const uint32_t w0 = pack_bf16(expsub(bf_lo(s0), m) * inv, expsub(bf_hi(s0), m) * inv);
                const uint32_t w1 = pack_bf16(expsub(bf_lo(s1), m) * inv, expsub(bf_hi(s1), m) * inv);
#pragma unroll
                for (int j = 0; j < 8; j++) {
                    Q[2 * j] = __shfl_sync(~0u, w0, 4 * j + t) & vmask;
                    Q[2 * j + 1] = __shfl_sync(~0u, w1, 4 * j + t) & vmask;
                }
            } else {
#pragma unroll
                for (int j = 0; j < 8; j++) {
                    const int src = (((j + g) & 7) << 2) + t;
                    Q[j] = __shfl_sync(~0u, (uint32_t)H0, src);
                    Q[8 + j] = __shfl_sync(~0u, (uint32_t)H1, src);
                }
            }
            unn = nstatic + (int)__shfl_sync(~0u, nxt, 0);
        }
        if (u >= NUK && lane < NR)
            red_add_u32(vdst,
                        1u + ((__float_as_uint(oret.x) | __float_as_uint(oret.y) | __float_as_uint(oret.z) | __float_as_uint(oret.w)) & zero));
        if (un >= NU) break;
        bu = bn;
        have = !(un < NUK && unn >= NUK && !(un >= NUK / 2 && unn < NUK + NUK / 2));
        bn = unit_block<CLU>(unn);
        if (have) header(unn, bn);
        u = un;
        un = unn;
    }
}

__device__ __forceinline__ void k_helper(uint32_t help, unsigned epoch) {
    if ((threadIdx.x & 31) != 0) return;
    unsigned (*ctl)[32] = g_ctl[epoch & 1];
    unsigned sent0 = 0, sent1 = 0, n = 0;
    int seen = 0;
    bool fin = false;
    while (!fin || seen < 2) {
        if (!fin) {
            fin = ld_acquire_cta_shared(help + 8) == NW + XW;
            const unsigned c0 = ld_acquire_cta_shared(help), c1 = ld_acquire_cta_shared(help + 4);
            if (c0 != sent0 || c1 != sent1) {
                fence_gpu();
                if (c0 != sent0) red_add_u32(&ctl[C_KDONE][0], c0 - sent0);
                if (c1 != sent1) red_add_u32(&ctl[C_KDONE + 1][0], c1 - sent1);
                sent0 = c0; sent1 = c1;
            }
        }
        if (seen < 2 && ld_acquire(&ctl[C_KDONE + seen][0]) >= NUK / 2) {
            st_release_cta_shared(help + 12 + 4 * seen, 1u);
            seen++;
        } else {
            __nanosleep(300);
        }
        if (++n > SPIN_LIMIT) __trap();
    }
}

__device__ __forceinline__ void v_poller(uint32_t sbase, int f, int w) {
    constexpr int HL = NH;
    const int lane = threadIdx.x & 31;
    const unsigned (*cp)[32] = &g_vdone[((f * NPOLL + w) % NREP) * NH];
    unsigned n = 0;
    while (ld_acquire_cta_shared(sbase + M_HELP + 12) == 0) { __nanosleep(1000); if (++n > SPIN_LIMIT) __trap(); }
    int h = 0;
    bool fast = false;
    while (h < HL) {
        const unsigned r = __ballot_sync(~0u, ld_acquire(&cp[min(h + (lane & 3), HL - 1)][0]) >= 4 * UPP) & 15u;
        if (r & 1) {
            h = min(HL, h + __ffs(~r) - 1);
            __syncwarp();
            if (lane == 0) asm volatile("red.release.cta.shared::cta.max.u32 [%0], %1;" ::"r"(sbase + M_HELP + 20), "r"(h) : "memory");
        }
        if (h < HL - 4) {
            __nanosleep(h ? 300 : 1000);
        } else if (!fast) {
            fast = true;
            const long long t0 = clock64();
            while (clock64() - t0 < w * PGAP) {}
        }
        if (++n > SPIN_LIMIT) __trap();
    }
}
__device__ __forceinline__ void finisher(const Params& p, uint32_t sbase, int f) {
    constexpr int HL = NH;
    const int lane = threadIdx.x & 31;
    {
        const char* wg = reinterpret_cast<const char*>(p.wo);
        const uint32_t dst = sbase + 4 * SLOT + (16 * (lane & 7) + (lane >> 3)) * 16;
#pragma unroll 1
        for (int h = -FPF - 4; h < HL; h++) {
            if (lane == 0 && (unsigned)(h + FPF) < (unsigned)HL) l2_prefetch(wg + (size_t)(h + FPF) * 147456 + f * 2048, 2048);
            if (h >= 0) {
#pragma unroll
                for (int r = 0; r < 4; r++)
                    asm volatile("cp.async.cg.shared.global [%0], [%1], 16;" ::"r"(dst + h * 2048 + ((r & 1) * 4 + (r >> 1) * 8) * 16),
                                 "l"(wg + (size_t)(h * 128 + r * 32 + lane) * (DM * 2) + f * 16) : "memory");
            }
            __nanosleep(FSLEEP);
        }
        asm volatile("cp.async.wait_all;" ::: "memory");
        __syncwarp();
    }
    TS(11);
    const float4* vec = g_oacc + ((lane >> 2) & 3) * 32 + (lane >> 4) * 16 + (lane & 3);
    float acc[2][2][4];
#pragma unroll
    for (int i = 0; i < 16; i++) acc[i >> 3][(i >> 2) & 1][i & 3] = 0.f;
    uint32_t* outp = reinterpret_cast<uint32_t*>(p.out + (lane >> 2) * (2 * DM) + f * 8 + (lane & 3) * 2);
    uint32_t wa = sbase + 4 * SLOT + lane * 16;
    auto project = [&](const float4 (&x)[4], const uint32_t (&w)[4][4]) {
#pragma unroll
        for (int s = 0; s < 4; s++) {
            const uint32_t a[4] = {pack_bf16(x[s].x, x[s].y), 0u, pack_bf16(x[s].z, x[s].w), 0u};
            mma16816(acc[0][s & 1], a, w[s >> 1][(s & 1) * 2], w[s >> 1][(s & 1) * 2 + 1]);
            mma16816(acc[1][s & 1], a, w[2 + (s >> 1)][(s & 1) * 2], w[2 + (s >> 1)][(s & 1) * 2 + 1]);
        }
    };
    int h = 0;
    unsigned n = 0;
    while (h < HL) {
        uint32_t w[4][4];
#pragma unroll
        for (int q = 0; q < 4; q++) ldsm4t(w[q], wa + q * 512);
        int ready;
        while ((ready = ld_acquire_cta_shared(sbase + M_HELP + 20)) <= h) {
            if (h < HL - 3) __nanosleep(100);
            if (++n > (SPIN_LIMIT << 4)) __trap();
        }
        float4 x[4], y[4];
#pragma unroll
        for (int s = 0; s < 4; s++) x[s] = ld_relaxed16(vec + s * 4);
        const bool two = ready > h + 1;
        if (two) {
#pragma unroll
            for (int s = 0; s < 4; s++) y[s] = ld_relaxed16(vec + 128 + s * 4);
        }
        project(x, w);
        if (two) {
#pragma unroll
            for (int q = 0; q < 4; q++) ldsm4t(w[q], wa + 2048 + q * 512);
            project(y, w);
        }
        const int nr = two ? 2 : 1;
        h += nr;
        vec += nr * 128;
        wa += nr * 2048;
        const float o0 = acc[0][0][0] + acc[0][1][0] + __shfl_down_sync(~0u, acc[1][0][0] + acc[1][1][0], 16);
        const float o1 = acc[0][0][1] + acc[0][1][1] + __shfl_down_sync(~0u, acc[1][0][1] + acc[1][1][1], 16);
        asm volatile("{\n.reg .pred p;\nsetp.ne.u32 p, %2, 0;\n@p st.global.u32 [%0], %1;\n}" ::"l"(outp), "r"(pack_bf16(o0, o1)),
                     "r"((uint32_t)(lane < 16 && h == NH)) : "memory");
    }
}

__device__ __noinline__ void f_collect(const unsigned (*flag)[32], unsigned full, const float4* src, bool last, uint32_t sbase) {
    const int lane = threadIdx.x & 31, g = lane >> 2, t = lane & 3;
    unsigned n = 0, todo = 15;
    while (todo) {
        const unsigned v = ld_acquire(&flag[t][0]);
        unsigned m = __ballot_sync(~0u, v == full) & todo;
        if (m == 0) {
            if (!last || (todo == 15 && __shfl_sync(~0u, v, 0) == 0)) __nanosleep(200);
            if (++n > SPIN_LIMIT) __trap();
            continue;
        }
        __syncwarp();
        todo ^= m;
        if (last && todo == 0) TS(16);
        do {
            const int h0 = __ffs(m) - 1, h1 = 31 - __clz(m);
            m &= ~((1u << h0) | (1u << h1));
            float4 x[2][4];
#pragma unroll
            for (int b = 0; b < 8; b++) x[b >> 2][b & 3] = ld_relaxed16(src + ((b & 4) ? h1 : h0) * 128 + (b & 3) * 32 + lane);
#pragma unroll
            for (int b = 0; b < 8; b++)
                asm volatile("st.shared.v2.u32 [%0], {%1,%2};" ::"r"(sbase + F_BF + ((b & 4) ? h1 : h0) * 1024 + g * 128 + ((b ^ g) & 3) * 32 + t * 8),
                             "r"(pack_bf16(x[b >> 2][b & 3].x, x[b >> 2][b & 3].y)), "r"(pack_bf16(x[b >> 2][b & 3].z, x[b >> 2][b & 3].w)) : "memory");
            __syncwarp();
            if (lane < (h0 == h1 ? 2 : 4) * PH)
                asm volatile("mbarrier.arrive.shared::cta.b64 _, [%0];"
                             ::"r"(sbase + F_BAR + 32 + (((lane / PH) & 1) * NPC + (lane < 2 * PH ? h0 : h1) * PH + lane % PH) * 8) : "memory");
            if (last && (h0 == 2 || h1 == 2)) TS(21);
        } while (m);
    }
    if (last) TS(17);
}

__device__ __noinline__ void f_project(const CUtensorMap* tm, int col0, int rank, int sl, int j, uint32_t go, int delay, uint32_t sbase, uint64_t pol) {
    const int lane = threadIdx.x & 31, g = lane >> 2, t = lane & 3;
    const uint32_t wb = sbase + F_W - sl * 2 * SLOT, bars = sbase + F_BAR + 32 + sl * NPC * 8;
    const uint32_t wa = wb + ((lane & 7) + (lane >> 4) * 8) * 128 + (((2 * j + ((lane >> 3) & 1)) ^ (lane & 7)) * 16);
    const uint32_t ba = sbase + F_BF + t * 8;
    const uint32_t rdst = mapa(sbase + F_RX + sl * 1024 + rank * 128 + g * 16 + (t & 1) * 8, 2 * j + (t >> 1));
    const uint32_t rbar = mapa(sbase + F_BAR + 16 + sl * 8, 2 * j + (t >> 1));
    if (delay >= 0) {
        mbar_wait(go, 0);
        const long long t0 = clock64();
        while (clock64() - t0 < delay) {}
        TS(18);
    } else {
        unsigned n = 0;
        while (ld_acquire_cta_shared(sbase + M_HELP + 12) == 0) { __nanosleep(1000); if (++n > SPIN_LIMIT) __trap(); }
    }
    if (lane == 0) {
#pragma unroll 1
        for (int q = 0; q < PH; q++) {
            const uint32_t bar = bars + (j * PH + q) * 8;
            mbar_expect_tx(bar, 16384 / PH);
            tma3d(wb + (j * PH + q) * (16384 / PH), tm, col0, (4 * rank + j) * 16, q * PKS, bar, pol);
        }
    }
    __syncwarp();
    if (delay < 0) mbar_wait(bars, 0);
    float acc[2][4];
#pragma unroll
    for (int i = 0; i < 8; i++) acc[i >> 2][i & 3] = 0.f;
    uint32_t todo = (1u << NPC) - 1;
    unsigned n = 0;
    while (todo) {
        uint32_t ok;
        asm volatile("{\n.reg .pred p;\nmbarrier.test_wait.parity.shared::cta.b64 p, [%1], 0;\nselp.u32 %0, 1, 0, p;\n}\n"
                     : "=r"(ok) : "r"(bars + (lane & (NPC - 1)) * 8) : "memory");
        uint32_t m = __ballot_sync(~0u, ok) & todo;
        if (m == 0) {
            if (++n > (SPIN_LIMIT << 2)) __trap();
            continue;
        }
        __syncwarp();
        todo ^= m;
        if (todo == 0) TS(19);
        do {
            const int pc = __ffs(m) - 1;
            m &= m - 1;
            uint32_t a[PKS][4], bf[PKS][2];
#pragma unroll
            for (int s = 0; s < PKS; s++) {
                ldsm4t(a[s], wa + (pc * PKS + s) * 2048);
                asm volatile("ld.shared.v2.u32 {%0,%1}, [%2];" : "=r"(bf[s][0]), "=r"(bf[s][1])
                             : "r"(ba + (pc * PKS + s) * 128 + ((g ^ s) & 3) * 32) : "memory");
            }
#pragma unroll
            for (int s = 0; s < PKS; s++) mma16816(acc[s & 1], a[s], bf[s][0], bf[s][1]);
        } while (m);
        const float v0 = (t & 2) ? acc[0][2] + acc[1][2] : acc[0][0] + acc[1][0], v1 = (t & 2) ? acc[0][3] + acc[1][3] : acc[0][1] + acc[1][1];
        asm volatile("{\n.reg .pred p;\nsetp.eq.u32 p, %4, 0;\n"
                     "@p st.async.weak.shared::cluster.mbarrier::complete_tx::bytes.v2.b32 [%0], {%1,%2}, [%3];\n}"
                     ::"r"(rdst), "r"(__float_as_uint(v0)), "r"(__float_as_uint(v1)), "r"(rbar), "r"(todo) : "memory");
    }
    TS(20);
}

__device__ __noinline__ void f_receive(__nv_bfloat16* out, int sl, uint32_t sbase) {
    const int lane = threadIdx.x & 31;
    out += (lane & 3) * (2 * DM) + (lane >> 2);
    unsigned n = 0;
    uint32_t ok;
    do {
        do {
            asm volatile("{\n.reg .pred p;\nmbarrier.test_wait.parity.acquire.cluster.shared::cta.b64 p, [%1], 0;\nselp.u32 %0, 1, 0, p;\n}\n"
                         : "=r"(ok) : "r"(sbase + F_BAR + 16 + sl * 8) : "memory");
            if (n > (SPIN_LIMIT << 2)) __trap();
        } while (n++ && !ok);
        float v[8];
#pragma unroll
        for (int r = 0; r < 8; r++)
            asm volatile("ld.shared.f32 %0, [%1];" : "=f"(v[r]) : "r"(sbase + F_RX + sl * 1024 + r * 128 + lane * 4) : "memory");
        const float o = ((v[0] + v[1]) + (v[2] + v[3])) + ((v[4] + v[5]) + (v[6] + v[7]));
        asm volatile("{\n.reg .pred p;\nsetp.ne.u32 p, %2, 0;\n@p st.global.u16 [%0], %1;\n}"
                     ::"l"(out), "h"((unsigned short)pack_bf16(o, 0.f)), "r"(ok) : "memory");
    } while (!ok);
    TS(15);
}

__device__ __forceinline__ void b_final(const Params& p, uint32_t sbase, int blk, unsigned epoch, uint64_t pol) {
    const int warp = threadIdx.x >> 5, lane = threadIdx.x & 31;
    const int rank = blk & 7, sl = warp >> 2, col0 = ((blk >> 3) * 2 + sl) * 64;
    asm volatile("barrier.cluster.wait.acquire.aligned;" ::: "memory");
    if (warp == 0) f_collect(&g_cdone[4 * rank], epoch + 1, &g_octx[4 * rank * 128], false, sbase);
    if (warp == 7 && rank == 0) {
        unsigned (*ctl)[32] = g_ctl[epoch & 1];
        unsigned n = 0;
        while (ld_acquire(&ctl[C_KDONE][0]) < NUK / 2) { __nanosleep(500); if (++n > SPIN_LIMIT) __trap(); }
        while (ld_relaxed4(&g_vdone[GO0 / 128 - 2][0]) < 4 * UPP) { __nanosleep(200); if (++n > SPIN_LIMIT) __trap(); }
        while (ld_relaxed4(&g_vdone[GO0 / 128][0]) <= GO0 % 128) { if (++n > SPIN_LIMIT) __trap(); }
        const long long t0 = clock64();
#pragma unroll 1
        for (int i = 0; i < 2; i++) {
            while (clock64() - t0 < (i ? GD1 : GD0) + (blk >> 3) * GDC) {}
            if (lane < 8) asm volatile("mbarrier.arrive.relaxed.cluster.shared::cluster.b64 _, [%0];" ::"r"(mapa(sbase + F_BAR + i * 8, lane)) : "memory");
        }
    }
    f_project(&p.tm_fb, col0, rank, sl, warp & 3, sbase + F_BAR + sl * 8, 0, sbase, pol);
    if ((warp & 3) == 0) f_receive(p.out + DM + col0 + rank * 8, sl, sbase);
}

constexpr int BS_WUK = 5, BS_Q = 9, BS_CKV = 11, BS_PART = 27, BS_WUV = 29, BS_END = 33;

__device__ __noinline__ void b_issue(const Params& p, int n, int bi, uint32_t sbase, uint64_t pol) {
    if (n >= BS_END || (n >= BS_Q && n < BS_CKV) || (n >= BS_PART && n < BS_WUV)) return;
    const uint32_t bar = sbase + M_BAR + (NSLOT + n % BRING) * 8;
    const CUtensorMap* tm;
    int row, panel = 2 * bi;
    if (n < BS_WUK) { tm = &p.tm_wq; row = n * 128; }
    else if (n < BS_Q) { tm = &p.tm_wuk; row = (n - BS_WUK) * 128; }
    else if (n < BS_PART) {
        tm = &p.tm_ckv; panel = 0;
        row = (bi >> 3) * SK + ((n - BS_CKV) * 8 + (bi & 7)) * 32;
    }
    else { tm = &p.tm_wuv; row = (n - BS_WUV) * 128; }
    mbar_expect_tx(bar, n == 0 ? 32768 + 4 * 1152 : 32768);
    tma3d(sbase + (n % BRING) * SLOT, tm, 0, row, panel, bar, pol);
}
__device__ __forceinline__ void b_issue_xchg(int n, const void* src, uint32_t sbase, uint64_t pol) {
    asm volatile("fence.proxy.async;" ::: "memory");
#pragma unroll
    for (int i = 0; i < 2; i++) {
        const uint32_t bar = sbase + M_BAR + (NSLOT + (n + i) % BRING) * 8;
        mbar_expect_tx(bar, 32768);
        bulk_load(sbase + ((n + i) % BRING) * SLOT, reinterpret_cast<const char*>(src) + i * 32768, 32768, bar, pol);
    }
}
__device__ __forceinline__ void b_wait(int n, uint32_t sbase) {
    mbar_wait(sbase + M_BAR + (NSLOT + n % BRING) * 8, (n / BRING) & 1);
}

__device__ __noinline__ void b_gemm(const Params& p, uint32_t sbase, int n0, int n1, int ktot, uint32_t xh, uint32_t xl, int pitch,
                                    int bi, uint64_t pol) {
    const int tid = threadIdx.x, warp = tid >> 5, lane = tid & 31, g = lane >> 2, t = lane & 3;
    const uint32_t woff = (warp >> 2) * 16384 + (lane & 15) * 128 + ((((warp & 3) * 2 + (lane >> 4)) ^ (lane & 7)) * 16);
    const uint32_t xoff = (g & 3) * pitch + t * 4;
    float acc[2][4];
#pragma unroll
    for (int i = 0; i < 8; i++) acc[i >> 2][i & 3] = 0.f;
#pragma unroll 1
    for (int n = n0; n < n1; n++) {
        b_wait(n, sbase);
        const uint32_t slot = sbase + (n % BRING) * SLOT + woff;
        const int k0 = (n - n0) * 128;
        const int ns = min(8, (ktot - k0) >> 4);
#pragma unroll 2
        for (int s = 0; s < ns; s++) {
            uint32_t a[4], w[4];
            const uint32_t xo = xoff + (k0 + 16 * s) * 2;
            a[0] = lds32(xh + xo); a[2] = lds32(xh + xo + 16);
            a[1] = xl ? lds32(xl + xo) : 0u; a[3] = xl ? lds32(xl + xo + 16) : 0u;
            ldsm4t(w, slot + s * 2048);
            mma16816(acc[0], a, w[0], w[1]);
            mma16816(acc[1], a, w[2], w[3]);
        }
        __syncthreads();
        if (tid == 0) b_issue(p, n + BD, bi, sbase, pol);
    }
    if (g < 4) {
#pragma unroll
        for (int j = 0; j < 2; j++)
            asm volatile("st.shared.u32 [%0], %1;" ::"r"(sbase + M_QB + g * QP + (warp * 16 + j * 8 + t * 2) * 2),
                         "r"(pack_bf16(acc[j][0] + acc[j][2], acc[j][1] + acc[j][3])) : "memory");
    }
    __syncthreads();
}

__device__ __forceinline__ void b_exchange(unsigned* c, int n, const void* src, uint32_t sbase, uint64_t pol) {
    TS(n == BS_Q ? 24 : 28);
    __syncthreads();
    if (threadIdx.x == 0) {
        TS(n == BS_Q ? 25 : 29);
        fence_gpu();
        TS(n == BS_Q ? 26 : 30);
        red_add_u32(c, 1u);
        wait_count(c, NBCTA);
        TS(n == BS_Q ? 27 : 31);
        b_issue_xchg(n, src, sbase, pol);
    }
}

template <bool CLU>
__device__ __noinline__ void b_chain(const Params& p, char* smem, uint32_t sbase, int bi, unsigned epoch, uint64_t pol) {
    const int tid = threadIdx.x, warp = tid >> 5, lane = tid & 31, g = lane >> 2, t = lane & 3;
    unsigned (*ctl)[32] = g_ctl[epoch & 1];
    float* red = reinterpret_cast<float*>(smem + 5 * SLOT);
    __syncthreads();
    b_gemm(p, sbase, 0, BS_WUK, DM, sbase + M_XB, 0, XP, bi, pol);
    TS(6);
    {
        uint32_t Q[16];
#pragma unroll
        for (int c = 0; c < 16; c++) Q[c] = lds32(sbase + M_QB + (g & 3) * QP + c * 16 + t * 4);
        float* qa = reinterpret_cast<float*>(smem + M_QA);
#pragma unroll 1
        for (int n = BS_WUK; n < BS_Q; n++) {
            b_wait(n, sbase);
            const uint32_t base = sbase + (n % BRING) * SLOT + (warp * 16 + (lane & 15)) * 128;
            float d[2][4];
#pragma unroll
            for (int i = 0; i < 8; i++) d[i >> 2][i & 3] = 0.f;
#pragma unroll
            for (int s = 0; s < 8; s++) {
                uint32_t a[4];
                ldsm4(a, base + (s >> 2) * 16384 + (((2 * (s & 3) + (lane >> 4)) ^ (lane & 7)) * 16));
                mma16816(d[s & 1], a, Q[2 * s], Q[2 * s + 1]);
            }
            const int c = (n - BS_WUK) * 128 + warp * 16 + g + 8 * (t >> 1);
            qa[(2 * (t & 1)) * 512 + c] = (t & 2) ? d[0][2] + d[1][2] : d[0][0] + d[1][0];
            qa[(2 * (t & 1) + 1) * 512 + c] = (t & 2) ? d[0][3] + d[1][3] : d[0][1] + d[1][1];
            __syncthreads();
            if (tid == 0) b_issue(p, n + BD, bi, sbase, pol);
        }
#pragma unroll 1
        for (int r = 0; r < 2; r++) {
            const int id = tid + r * 256;
            const int b = id >> 7, c0 = ((id >> 2) & 31) * 16 + (id & 3) * 2;
            const float2 u0 = *reinterpret_cast<const float2*>(qa + b * 512 + c0);
            const float2 u1 = *reinterpret_cast<const float2*>(qa + b * 512 + c0 + 8);
            const uint32_t h0 = pack_bf16(u0.x, u0.y), h1 = pack_bf16(u1.x, u1.y);
            const uint32_t l0 = pack_bf16(u0.x - bf_lo(h0), u0.y - bf_hi(h0)), l1 = pack_bf16(u1.x - bf_lo(h1), u1.y - bf_hi(h1));
            g_qabs[((id >> 2) * 4 + (bi >> 3)) * 32 + (bi & 7) * 4 + (id & 3)] = make_uint4(h0, l0, h1, l1);
        }
    }
    b_exchange(&ctl[C_BBAR][0], BS_Q, &g_qabs[(bi >> 3) * 4096], sbase, pol);
    {
        uint32_t qf[4][4][4];
        b_wait(BS_Q + (warp >> 2), sbase);
        TS(7);
        {
            const uint4* qs = reinterpret_cast<const uint4*>(smem + ((BS_Q + (warp >> 2)) % BRING) * SLOT) + (warp & 3) * 512 + lane;
#pragma unroll
            for (int s = 0; s < 4; s++)
#pragma unroll
                for (int i = 0; i < 4; i++) {
                    const uint4 v = qs[(s * 4 + i) * 32];
                    qf[i][s][0] = v.x; qf[i][s][1] = v.y; qf[i][s][2] = v.z; qf[i][s][3] = v.w;
                }
        }
        __syncthreads();
        if (tid == 0) { b_issue(p, BS_Q + BD, bi, sbase, pol); b_issue(p, BS_Q + 1 + BD, bi, sbase, pol); }
        float acc[2][8][4];
#pragma unroll
        for (int i = 0; i < 2; i++)
#pragma unroll
            for (int j = 0; j < 8; j++) { acc[i][j][0] = acc[i][j][1] = acc[i][j][2] = acc[i][j][3] = 0.f; }
        float mrun = -INFINITY, lrun = 0.f;
        const int head = tid >> 3, kq = tid & 7;
        float* alpha = reinterpret_cast<float*>(smem + M_ALPHA);
        for (int n = BS_CKV; n < BS_PART; n++) {
            b_wait(n, sbase);
            const uint32_t slot = sbase + (n % BRING) * SLOT;
            float sc[4][4][4];
#pragma unroll
            for (int i = 0; i < 4; i++)
#pragma unroll
                for (int j = 0; j < 4; j++) { sc[i][j][0] = sc[i][j][1] = sc[i][j][2] = sc[i][j][3] = 0.f; }
#pragma unroll
            for (int j = 0; j < 4; j++)
#pragma unroll
                for (int sp = 0; sp < 2; sp++) {
                    uint32_t bf[4];
                    ldsm4(bf, slot + warp * 4096 + (8 * j + (lane & 7)) * 128 + (((4 * sp + (lane >> 3)) ^ (lane & 7)) * 16));
#pragma unroll
                    for (int i = 0; i < 4; i++) {
                        mma16816(sc[i][j], qf[i][2 * sp], bf[0], bf[1]);
                        mma16816(sc[i][j], qf[i][2 * sp + 1], bf[2], bf[3]);
                    }
                }
#pragma unroll
            for (int i = 0; i < 4; i++)
#pragma unroll
                for (int j = 0; j < 4; j++)
                    *reinterpret_cast<float2*>(red + warp * 1024 + (8 * i + g) * 32 + ((8 * j) ^ (8 * (g & 3))) + 2 * t) =
                        make_float2(sc[i][j][0] + sc[i][j][2], sc[i][j][1] + sc[i][j][3]);
            __syncthreads();
            if (tid == 0 && n > BS_CKV) b_issue(p, n - 1 + BD, bi, sbase, pol);
            {
                float4 s = make_float4(0.f, 0.f, 0.f, 0.f);
#pragma unroll
                for (int w = 0; w < 8; w++) {
                    const float4 v = *reinterpret_cast<const float4*>(red + w * 1024 + head * 32 + ((4 * kq) ^ (8 * (head & 3))));
                    s.x += v.x; s.y += v.y; s.z += v.z; s.w += v.w;
                }
                const uint32_t r0 = pack_bf16(s.x, s.y), r1 = pack_bf16(s.z, s.w);
                const uint32_t s0 = pack_bf16(bf_lo(r0) * SCALE, bf_hi(r0) * SCALE);
                const uint32_t s1 = pack_bf16(bf_lo(r1) * SCALE, bf_hi(r1) * SCALE);
                const float f0 = bf_lo(s0), f1 = bf_hi(s0), f2 = bf_lo(s1), f3 = bf_hi(s1);
                float mx = fmaxf(fmaxf(f0, f1), fmaxf(f2, f3));
                mx = fmaxf(mx, __shfl_xor_sync(~0u, mx, 1));
                mx = fmaxf(mx, __shfl_xor_sync(~0u, mx, 2));
                mx = fmaxf(mx, __shfl_xor_sync(~0u, mx, 4));
                const float mnew = fmaxf(mrun, mx);
                const float al = expsub(mrun, mnew);
                const float p0 = expsub(f0, mnew), p1 = expsub(f1, mnew), p2 = expsub(f2, mnew), p3 = expsub(f3, mnew);
                lrun = lrun * al + ((p0 + p1) + (p2 + p3));
                mrun = mnew;
                *reinterpret_cast<uint2*>(smem + M_P + head * 80 + kq * 8) = make_uint2(pack_bf16(p0, p1), pack_bf16(p2, p3));
                if (kq == 0) alpha[head] = al;
            }
            __syncthreads();
            {
                uint32_t pf[2][2][4];
#pragma unroll
                for (int i = 0; i < 2; i++)
#pragma unroll
                    for (int ks = 0; ks < 2; ks++)
                        ldsm4(pf[i][ks], sbase + M_P + (16 * i + (lane & 15)) * 80 + (16 * ks + 8 * (lane >> 4)) * 2);
#pragma unroll
                for (int i = 0; i < 2; i++) {
                    const float a0 = alpha[16 * i + g], a1 = alpha[16 * i + 8 + g];
#pragma unroll
                    for (int j = 0; j < 8; j++) { acc[i][j][0] *= a0; acc[i][j][1] *= a0; acc[i][j][2] *= a1; acc[i][j][3] *= a1; }
                }
#pragma unroll
                for (int j = 0; j < 8; j++) {
                    uint32_t bf[4];
                    ldsm4t(bf, slot + warp * 4096 + lane * 128 + ((j ^ (lane & 7)) * 16));
#pragma unroll
                    for (int i = 0; i < 2; i++) {
                        mma16816(acc[i][j], pf[i][0], bf[0], bf[1]);
                        mma16816(acc[i][j], pf[i][1], bf[2], bf[3]);
                    }
                }
            }
        }
        __syncthreads();
        if (tid == 0) b_issue(p, BS_PART - 1 + BD, bi, sbase, pol);
        lrun += __shfl_xor_sync(~0u, lrun, 1);
        lrun += __shfl_xor_sync(~0u, lrun, 2);
        lrun += __shfl_xor_sync(~0u, lrun, 4);
        if (kq == 0) g_bml[head * NBCTA + bi] = make_float2(mrun, lrun);
#pragma unroll
        for (int i = 0; i < 2; i++)
#pragma unroll
            for (int j = 0; j < 8; j++) {
                g_bpart[((16 * i + g) * NBCTA + bi) * 256 + warp * 32 + j * 4 + t] = make_float2(acc[i][j][0], acc[i][j][1]);
                g_bpart[((16 * i + 8 + g) * NBCTA + bi) * 256 + warp * 32 + j * 4 + t] = make_float2(acc[i][j][2], acc[i][j][3]);
            }
    }
    if (!CLU) {
#pragma unroll 1
        for (int i = tid; i < NH * 36; i += 256) g_outb[bi * NH * 36 + i] = make_uint4(0u, epoch, 0u, epoch);
    }
    b_exchange(&ctl[C_BBAR + 1][0], BS_PART, &g_bpart[bi * NBCTA * 256], sbase, pol);
    {
        float* omega = reinterpret_cast<float*>(smem + M_OMEGA);
        if (warp == 0) {
            __syncwarp();
            const uint2 ml = ld_relaxed8(&g_bml[bi * NBCTA + lane]);
            const float ms = __uint_as_float(ml.x);
            float m = ms;
            m = fmaxf(m, __shfl_xor_sync(~0u, m, 1));
            m = fmaxf(m, __shfl_xor_sync(~0u, m, 2));
            m = fmaxf(m, __shfl_xor_sync(~0u, m, 4));
            const float w = expsub(ms, m);
            float l = w * __uint_as_float(ml.y);
            l += __shfl_xor_sync(~0u, l, 1);
            l += __shfl_xor_sync(~0u, l, 2);
            l += __shfl_xor_sync(~0u, l, 4);
            omega[lane] = w / l;
        }
        __syncthreads();
        b_wait(BS_PART, sbase);
        b_wait(BS_PART + 1, sbase);
#pragma unroll 1
        for (int b = 0; b < 4; b++) {
            const float2* ps = reinterpret_cast<const float2*>(smem + ((BS_PART + (b >> 1)) % BRING) * SLOT) + (b & 1) * 2048 + tid;
            float c0 = 0.f, c1 = 0.f;
#pragma unroll
            for (int s = 0; s < 8; s++) {
                const float w = omega[b * 8 + s];
                const float2 v = ps[s * 256];
                c0 = fmaf(w, v.x, c0);
                c1 = fmaf(w, v.y, c1);
            }
            const uint32_t hi = pack_bf16(c0, c1);
            *reinterpret_cast<uint32_t*>(smem + M_CH + b * CP + tid * 4) = hi;
            *reinterpret_cast<uint32_t*>(smem + M_CL + b * CP + tid * 4) = pack_bf16(c0 - bf_lo(hi), c1 - bf_hi(hi));
        }
        __syncthreads();
        if (tid == 0) { b_issue(p, BS_PART + BD, bi, sbase, pol); b_issue(p, BS_PART + 1 + BD, bi, sbase, pol); }
    }
    b_gemm(p, sbase, BS_WUV, BS_END, 512, sbase + M_CH, sbase + M_CL, CP, bi, pol);
    TS(12);
    if (CLU) {
        if (warp < 4) {
            const unsigned short* c = reinterpret_cast<const unsigned short*>(smem + M_QB + warp * QP) + 16 * t + g;
            g_octx[(bi * 4 + warp) * 32 + lane] = make_float4(bf_lo(c[0]), bf_lo(c[8]), bf_lo(c[64]), bf_lo(c[72]));
        }
        __syncthreads();
        if (tid == 0) asm volatile("st.release.gpu.global.u32 [%0], %1;" ::"l"(&g_cdone[bi][0]), "r"(epoch + 1) : "memory");
        return;
    }
    if (tid == 0) {
#pragma unroll 1
        for (int i = 0; i < 4; i++) {
            mbar_expect_tx(sbase + M_BAR + i * 8, 36864);
            tma3d(sbase + i * 36864, &p.tm_wo, 0, bi * 128 + i * 32, 0, sbase + M_BAR + i * 8, pol);
        }
    }
    TS(8);
    {
        float acc[9][4];
#pragma unroll
        for (int j = 0; j < 9; j++) { acc[j][0] = acc[j][1] = acc[j][2] = acc[j][3] = 0.f; }
#pragma unroll 1
        for (int i = 0; i < 4; i++) {
            const uint32_t xo = sbase + M_QB + (g & 3) * QP + i * 64 + t * 4;
            const uint32_t a0[4] = {lds32(xo), 0u, lds32(xo + 16), 0u}, a1[4] = {lds32(xo + 32), 0u, lds32(xo + 48), 0u};
            mbar_wait(sbase + M_BAR + i * 8, 0);
#pragma unroll
            for (int j = 0; j < 9; j++) {
                const int nt = warp * 9 + j;
                uint32_t w[4];
                ldsm4t(w, sbase + i * 36864 + (nt >> 3) * 4096 + lane * 128 + (((nt & 7) ^ (lane & 7)) * 16));
                mma16816(acc[j], a0, w[0], w[1]);
                mma16816(acc[j], a1, w[2], w[3]);
            }
        }
        if (g < 4) {
#pragma unroll
            for (int j = 0; j < 9; j++) {
                const int c2 = (warp * 9 + j) * 4 + t;
                st_tagged2(&g_outb[((c2 / 9) * NH + bi) * 36 + g * 9 + c2 % 9], acc[j][0], acc[j][1], epoch + 1);
            }
        }
    }
    TS(9);
    {
        const uint4* src = g_outb + (bi * NH + (tid >> 3)) * 36 + (tid & 7);
        float2* part = reinterpret_cast<float2*>(red);
        unsigned n = 0;
        while (true) {
            ulonglong2 v[5];
            bool ok = true;
#pragma unroll
            for (int i = 0; i < 5; i++)
                if (i < 4 || (tid & 7) < 4) v[i] = ld_tagged2(src + i * 8);
#pragma unroll
            for (int i = 0; i < 5; i++)
                if (i < 4 || (tid & 7) < 4) {
                    ok = ok && (unsigned)(v[i].x >> 32) == epoch + 1 && (unsigned)(v[i].y >> 32) == epoch + 1;
                    part[(tid >> 3) * 36 + (tid & 7) + i * 8] = make_float2(__uint_as_float((unsigned)v[i].x), __uint_as_float((unsigned)v[i].y));
                }
            if (ok) break;
            __nanosleep(400);
            if (++n > SPIN_LIMIT) __trap();
        }
        __syncthreads();
        if (tid < 36) {
            float s0 = 0.f, s1 = 0.f;
#pragma unroll 8
            for (int h = 0; h < NH; h++) { const float2 v = part[h * 36 + tid]; s0 += v.x; s1 += v.y; }
            *reinterpret_cast<uint32_t*>(p.out + (tid / 9) * 2 * DM + DM + bi * 18 + (tid % 9) * 2) = pack_bf16(s0, s1);
        }
    }
    TS(10);
}

template <bool CLU>
__global__ void __launch_bounds__(256, 1) fused_decode_kernel(const __grid_constant__ Params p) {
    extern __shared__ __align__(1024) char smem_raw[];
    const uint32_t sbase = (smem_u32(smem_raw) + 1023u) & ~1023u;
    char* smem = smem_raw + (sbase - smem_u32(smem_raw));
    const int tid = threadIdx.x, warp = tid >> 5, lane = tid & 31;
    const int blk = blockIdx.x;
    const bool isB = CLU ? blk < NBCTA : (blk & 3) == 0 && (blk >> 2) < NBCTA;
    const int bi = CLU ? blk : blk >> 2;
    const int nb = CLU ? blk - NBCTA : blk - min(NBCTA, (blk + 3) >> 2);
    const int nnb = gridDim.x - NBCTA;
    const int nstatic = nnb * (NW + XW);
    uint64_t pol;
    asm volatile("createpolicy.fractional.L2::evict_first.b64 %0, 1.0;" : "=l"(pol));
    const uint32_t wbar = sbase + M_BAR + warp * 8, wslot = sbase + warp * SLOT;
    const int u0 = warp * nnb + nb;
    const bool hold = ((blk >> 2) >> KMIN << KMIN) * 4 * UPP < nstatic;
    const uint32_t jbar = sbase + M_BAR + (NSLOT + BRING) * 8;
    if (warp == 7) {
        if (lane == 0 && blk < 128) {
            mbar_init(jbar, 1);
            asm volatile("fence.mbarrier_init.release.cluster;" ::: "memory");
            uint64_t poln;
            asm volatile("createpolicy.fractional.L2::evict_normal.b64 %0, 1.0;" : "=l"(poln));
            mbar_expect_tx(jbar, 36864 + 4 * 1152);
            tma3d(sbase + J0W, &p.tm_j0, blk * 32, 0, 0, jbar, poln);
            bulk_load(sbase + M_XA, p.xa, 4608, jbar, poln);
        }
        if (lane < 8) reinterpret_cast<unsigned*>(smem + M_HELP)[lane] = 0;
        __syncwarp();
        if (!isB) asm volatile("bar.arrive 2, %0;" ::"n"(32 * (NW + XW + 1)) : "memory");
    }
    if (warp < 4 && lane == 0) {
        mbar_init(wbar, 1);

        asm volatile("fence.mbarrier_init.release.cluster;" ::: "memory");
        if (warp < NEARLY && !isB && !hold) {
            mbar_expect_tx(wbar, TILE_BYTES);
            bulk_load(wslot, block_src(p.kc, unit_block<CLU>(u0)), TILE_BYTES, wbar, pol);
        }
    }
    unsigned epoch = 0;
    if (lane == 0) epoch = ld_relaxed4(&g_epoch);
    TS(0);
    if (CLU) {
        if (warp == 6) {
            if (lane < 4 + 2 * NPC) mbar_init(sbase + F_BAR + lane * 8, lane < 4 ? 1 : 2);
            if ((lane >> 1) == 1) mbar_expect_tx(sbase + F_BAR + lane * 8, 1024);
            asm volatile("fence.mbarrier_init.release.cluster;" ::: "memory");
        }
        asm volatile("barrier.cluster.arrive.relaxed.aligned;" ::: "memory");
    }
    if ((warp >> 1) == 2 && blk < 128) st_relaxed64(&g_qll[((tid - 128) >> 4) * 2048 + blk * 16 + (tid & 15)], 0ull);
    if (isB || warp >= NW + XW) epoch = __shfl_sync(~0u, epoch, 0);
    if (isB && warp == 3) asm volatile("bar.sync 1, 160;" ::: "memory");
    if (isB && tid == 96) {
#pragma unroll 1
        for (int i = 0; i < BRING; i++) mbar_init(sbase + M_BAR + (NSLOT + i) * 8, 1);
        asm volatile("fence.mbarrier_init.release.cluster;" ::: "memory");
        if (hold) { unsigned n = 0; while (ld_acquire_cta_shared(sbase + M_HELP + 24) < 2) { if (++n > (SPIN_LIMIT << 4)) __trap(); } }
#pragma unroll 1
        for (int b = 0; b < 4; b++) bulk_load(sbase + M_XB + b * XP, p.xb + b * DM, 1152, sbase + M_BAR + NSLOT * 8, pol);
#pragma unroll 1
        for (int n = 0; n < BD; n++) b_issue(p, n, bi, sbase, pol);
    }
    if (warp >= 4 && blk < 128) {
        const int g = lane >> 2, t = lane & 3, j = tid - 128;
        asm volatile("bar.sync 1, %0;" ::"r"(isB ? 160 : 128) : "memory");
#pragma unroll 1
        for (int sl = blk, ph = 0;; sl += 128 - gridDim.x, ph = 1) {
        mbar_wait(jbar, ph);
        TS(13);
        float acc[4][4];
#pragma unroll
        for (int i = 0; i < 16; i++) acc[i >> 2][i & 3] = 0.f;
        const uint32_t wa = sbase + J0W + ((warp - 4) * 144 + (lane & 15)) * 64;
        const uint32_t sw = (lane >> 1) & 3, xa = sbase + M_XA + (g & 3) * 1152 + (warp - 4) * 288 + t * 4;
#pragma unroll 3
        for (int s = 0; s < 9; s++) {
            const uint32_t a[4] = {lds32(xa + s * 32), 0u, lds32(xa + s * 32 + 16), 0u};
            uint32_t w0[4], w1[4];
            ldsm4t(w0, wa + s * 1024 + (((lane >> 4) ^ sw) * 16));
            ldsm4t(w1, wa + s * 1024 + (((2 + (lane >> 4)) ^ sw) * 16));
            mma16816(acc[0], a, w0[0], w0[1]);
            mma16816(acc[1], a, w0[2], w0[3]);
            mma16816(acc[2], a, w1[0], w1[1]);
            mma16816(acc[3], a, w1[2], w1[3]);
        }
        float2* j0 = reinterpret_cast<float2*>(smem + M_J0);
        if (g < 4) {
#pragma unroll
            for (int i = 0; i < 4; i++) j0[(warp - 4) * 64 + g * 16 + i * 4 + t] = make_float2(acc[i][0], acc[i][1]);
        }
        asm volatile("bar.sync 1, 128;" ::: "memory");
        const bool again = sl == blk && blk + 128 - (int)gridDim.x >= (int)gridDim.x;
        if (again && tid == 224) {
            mbar_expect_tx(jbar, 36864);
            tma3d(sbase + J0W, &p.tm_j0, (blk + 128 - gridDim.x) * 32, 0, 0, jbar, pol);
        }
        if (warp < 6) {
            const float2 v0 = j0[j], v1 = j0[64 + j], v2 = j0[128 + j], v3 = j0[192 + j];
            st_relaxed64(&g_qll[(j >> 4) * 2048 + sl * 16 + (j & 15)],
                         (unsigned long long)pack_bf16((v0.x + v1.x) + (v2.x + v3.x), (v0.y + v1.y) + (v2.y + v3.y)) |
                             ((unsigned long long)(epoch + 1) << 32));
            __syncwarp();
            if (lane == 0) asm volatile("red.relaxed.cta.shared::cta.add.u32 [%0], 1;" ::"r"(sbase + M_HELP + 24) : "memory");
        } else if (warp == 7) {
            if (blk < C_LINES) g_ctl[(epoch & 1) ^ 1][blk][lane] = 0;
        }
        TS(1);
        if (!again) break;
        asm volatile("bar.sync 1, 128;" ::: "memory");
        }
    }
    if (isB) {
        b_chain<CLU>(p, smem, sbase, bi, epoch, pol);
        if (CLU) b_final(p, sbase, blk, epoch, pol);
        return;
    }
    const int sl = nb >> 3, rank = blk & 7;
    if (warp < NW + XW) {
        a_worker<CLU>(p, u0, warp >= NW + ((nb & 3) < (CLU ? X3C : X3) ? 1 : 0), warp < NEARLY && !hold, hold, nstatic, wslot, wbar, sbase + M_HELP,
                      warp < 2 ? sbase + F_BAR + warp * 8 : 0, epoch, pol);
        if (CLU && warp == 3 && sl < 10) {
            epoch = __shfl_sync(~0u, epoch, 0);
            unsigned n = 0;
            while (ld_acquire_cta_shared(sbase + M_HELP + 12) == 0) { __nanosleep(1000); if (++n > SPIN_LIMIT) __trap(); }
            asm volatile("barrier.cluster.wait.acquire.aligned;" ::: "memory");
            f_collect((sl < 9 ? g_vdone : g_cdone) + 4 * rank, sl < 9 ? 4 * UPP : epoch + 1, (sl < 9 ? g_oacc : g_octx) + 4 * rank * 128,
                      sl < 9 && rank == 7, sbase);
            mbar_wait(sbase + F_BAR, 0);
            f_receive(p.out + (sl < 9 ? sl * 64 : DM + 512) + rank * 8, 0, sbase);
        }
        return;
    }
    if (warp == 7) {
#pragma unroll 1
        for (int i = nb; i < 4 * NH; i += nnb) g_oacc[i * 32 + lane] = make_float4(0.f, 0.f, 0.f, 0.f);
        if (nb < NREP * NH) g_vdone[nb][lane] = 0;
        __syncwarp();
        k_helper(sbase + M_HELP, epoch);
        if (nb == 0 && lane == 0) g_epoch = epoch + 1;
        __syncwarp();
    }
    if (CLU) {
        if (sl < 10) {
            const CUtensorMap* tm = sl < 9 ? &p.tm_fa : &p.tm_fb;
            asm volatile("barrier.cluster.wait.acquire.aligned;" ::: "memory");
            if (warp == 7 && lane == 0) asm volatile("prefetch.tensormap [%0];" ::"l"(tm) : "memory");
            f_project(tm, min(sl, 8) * 64, rank, 0, warp & 3, sbase + F_BAR + ((warp >> 1) & 1) * 8, sl < 9 && rank >= ERANK ? -1 : (warp & 1) ? AD1 : AD0, sbase, pol);
        }
    } else if (warp == 6 && nb < NFIN) {
        finisher(p, sbase, nb);
        TS(4);
    } else if (warp != 7 && warp >= 6 - NPOLL && nb < NFIN) {
        v_poller(sbase, nb, warp - (6 - NPOLL));
    }
}

}

typedef CUresult (*EncodeFn)(CUtensorMap*, CUtensorMapDataType, cuuint32_t, void*, const cuuint64_t*, const cuuint64_t*,
                             const cuuint32_t*, const cuuint32_t*, CUtensorMapInterleave, CUtensorMapSwizzle,
                             CUtensorMapL2promotion, CUtensorMapFloatOOBfill);

extern "C" void kernel_launch(void* const* d_in, const int* in_sizes, int n_in, void* d_out, int out_size) {
    (void)in_sizes; (void)n_in; (void)out_size;
    static int nsm = 0, ncl = 0;
    static EncodeFn encode = nullptr;
    cudaLaunchConfig_t cfg = {};
    cudaLaunchAttribute at[1];
    at[0].id = cudaLaunchAttributeClusterDimension;
    at[0].val.clusterDim.x = 8; at[0].val.clusterDim.y = 1; at[0].val.clusterDim.z = 1;
    cfg.blockDim = dim3(256); cfg.dynamicSmemBytes = SMEM_BYTES; cfg.stream = cudaStreamPerThread; cfg.attrs = at; cfg.numAttrs = 1;
    if (nsm == 0) {
        int dev = 0;
        cudaGetDevice(&dev);
        cudaDeviceGetAttribute(&nsm, cudaDevAttrMultiProcessorCount, dev);
        cudaFuncSetAttribute(fused_decode_kernel<false>, cudaFuncAttributeMaxDynamicSharedMemorySize, SMEM_BYTES);
        cudaFuncSetAttribute(fused_decode_kernel<true>, cudaFuncAttributeMaxDynamicSharedMemorySize, SMEM_BYTES);
        cfg.gridDim = dim3(128);
        if (cudaOccupancyMaxActiveClusters(&ncl, fused_decode_kernel<true>, &cfg) != cudaSuccess) { ncl = 0; (void)cudaGetLastError(); }
        if (ncl > MINCL) ncl = MINCL;
        void* fn = nullptr;
        cudaDriverEntryPointQueryResult qr;
        cudaGetDriverEntryPoint("cuTensorMapEncodeTiled", &fn, cudaEnableDefault, &qr);
        encode = (EncodeFn)fn;
    }
    Params p;
    auto panels = [&](CUtensorMap* tm, void* ptr, int rows, int cols, int box_rows, int box_panels) {
        const cuuint64_t gd[3] = {64, (cuuint64_t)rows, (cuuint64_t)(cols / 64)}, gs[2] = {(cuuint64_t)cols * 2, 128};
        const cuuint32_t box[3] = {64, (cuuint32_t)box_rows, (cuuint32_t)box_panels}, es[3] = {1, 1, 1};
        encode(tm, CU_TENSOR_MAP_DATA_TYPE_BFLOAT16, 3, ptr, gd, gs, box, es, CU_TENSOR_MAP_INTERLEAVE_NONE,
               CU_TENSOR_MAP_SWIZZLE_128B, CU_TENSOR_MAP_L2_PROMOTION_L2_256B, CU_TENSOR_MAP_FLOAT_OOB_FILL_NONE);
    };
    panels(&p.tm_wq, d_in[7], DM, 4096, 128, 2);
    panels(&p.tm_wuk, d_in[8], 512, 4096, 128, 2);
    panels(&p.tm_wuv, d_in[9], 512, 4096, 128, 2);
    panels(&p.tm_wo, d_in[10], 4096, DM, 32, 9);
    panels(&p.tm_ckv, d_in[6], 4 * SK, 512, 32, 8);
    {
        const cuuint64_t gd[3] = {4096, 192, 3}, gs[2] = {8192, 192 * 8192};
        const cuuint32_t box[3] = {32, 192, 3}, es[3] = {1, 1, 1};
        encode(&p.tm_j0, CU_TENSOR_MAP_DATA_TYPE_BFLOAT16, 3, d_in[3], gd, gs, box, es, CU_TENSOR_MAP_INTERLEAVE_NONE,
               CU_TENSOR_MAP_SWIZZLE_64B, CU_TENSOR_MAP_L2_PROMOTION_L2_128B, CU_TENSOR_MAP_FLOAT_OOB_FILL_NONE);
    }
    for (int i = 0; i < 2; i++) {
        const cuuint64_t gd[3] = {DM, 512, 8}, gs[2] = {8 * DM * 2, DM * 2};
        const cuuint32_t box[3] = {64, 16, PKS}, es[3] = {1, 1, 1};
        encode(i ? &p.tm_fb : &p.tm_fa, CU_TENSOR_MAP_DATA_TYPE_BFLOAT16, 3, d_in[i ? 10 : 4], gd, gs, box, es, CU_TENSOR_MAP_INTERLEAVE_NONE,
               CU_TENSOR_MAP_SWIZZLE_128B, CU_TENSOR_MAP_L2_PROMOTION_L2_128B, CU_TENSOR_MAP_FLOAT_OOB_FILL_NONE);
    }
    p.xa = (const __nv_bfloat16*)d_in[0];
    p.kc = (const __nv_bfloat16*)d_in[1];
    p.vc = (const __nv_bfloat16*)d_in[2];
    p.wo = (const __nv_bfloat16*)d_in[4];
    p.xb = (const __nv_bfloat16*)d_in[5];
    p.out = (__nv_bfloat16*)d_out;
    if (ncl >= MINCL) {
        cfg.gridDim = dim3(8 * ncl);
        cudaLaunchKernelEx(&cfg, fused_decode_kernel<true>, p);
    } else {
        fused_decode_kernel<false><<<nsm, 256, SMEM_BYTES, cudaStreamPerThread>>>(p);
    }
}
```

```cpp
#include <cuda_runtime.h>
#include <cuda.h>
#include <cuda_bf16.h>
#include <stdint.h>

namespace {

constexpr int NH = 32, SK = 4096, DM = 576;
constexpr int KEYS = 128;
constexpr int UPP = SK / KEYS;
constexpr int NUK = 4 * NH * UPP;
constexpr int TILE_BYTES = KEYS * 256;
#define NWORK 2
constexpr int NW = NWORK;
constexpr int NBCTA = 32;
constexpr int MINCL = 15;
constexpr int NFIN = 72;
constexpr int SLOT = 32768;
constexpr int NSLOT = 6;
constexpr int BRING = 5;
constexpr int J0W = 5 * SLOT;
constexpr int MISC = NSLOT * SLOT + 4096;
constexpr int XP = 1168, CP = 1040, QP = 272;
constexpr int M_XA = MISC;
constexpr int M_XB = M_XA + 4 * XP;
constexpr int M_CH = M_XB + 4 * XP;
constexpr int M_CL = M_CH + 4 * CP;
constexpr int M_QB = M_CL + 4 * CP;
constexpr int M_QA = M_CH;
constexpr int M_J0 = M_QB + 4 * QP;
constexpr int M_P = M_J0 + 2048;
constexpr int M_ALPHA = M_P + 2560;
constexpr int M_OMEGA = M_ALPHA + 128;
constexpr int M_BAR = M_OMEGA + 128;
constexpr int M_HELP = M_BAR + 128;
#define PH 1
constexpr int F_W = 4 * SLOT;
constexpr int F_BF = (M_HELP + 128 + 255) / 256 * 256;
constexpr int F_RX = F_BF + 4096;
constexpr int F_BAR = F_RX + 2048;
constexpr int SMEM_BYTES = F_BAR + 64 + 64 * PH + 1024;
static_assert(SMEM_BYTES <= 232448 && M_BAR % 8 == 0 && M_QA % 16 == 0 && M_P % 16 == 0, "smem layout");
#define XW 2
#define X3 1
#define X3C 2
#define NEARLY 3
#define BD 5
#define FPF 3
#define FSLEEP 800
#define VS0 24
#define EARLY 100
#define ELOG 5
#define TPU 159
#define A0 2600
#define AJ 700
#define AR (AJ / 8 / PH)
#define AK 24
#define AC 0
#define BK 24
#define BC 0
#define B0 2100
#define BJ 700
#define BS (300 / PH)
#define BR (BJ / 8 / PH)
#define NPOLL 2
#define PGAP 200
static_assert(NW + XW <= 4 && NEARLY <= NW + XW && BD <= BRING, "slots 4 and 5 hold the finisher weights");
#define KMAX 4
#define VMAX 4
constexpr int KMIN = 2, VMIN = 0;
constexpr float SCALE = 0.08838834764831845f;
constexpr float LOG2E = 1.4426950408889634f;
constexpr unsigned SPIN_LIMIT = 1u << 24;

#define NREP 2
#define NREPC 1
constexpr int C_QUEUE = 0, C_KDONE = 1, C_BBAR = 3, C_LINES = 5;

struct Params {
    const __nv_bfloat16 *kc, *xa, *vc, *wo, *xb;
    __nv_bfloat16* out;
    CUtensorMap tm_j0;
    CUtensorMap tm_wq, tm_wuk, tm_ckv, tm_wuv, tm_wo;
    CUtensorMap tm_fa, tm_fb;
};

__device__ unsigned g_epoch;
__device__ unsigned g_ctl[2][C_LINES][32];
__device__ uint2 g_qll[4 * 2048];
__device__ uint2 g_scores[128 * SK / 4];
__device__ float2 g_stats[128 * UPP];
__device__ float4 g_oacc[128 * 32];
__device__ unsigned g_vdone[NREP * NH][32];
__device__ float4 g_octx[128 * 32];
__device__ unsigned g_cdone[NH][32];
__device__ unsigned long long g_dry[16][16];
__device__ uint4 g_qabs[4 * 8 * 4 * 4 * 32];
__device__ float2 g_bpart[NBCTA * NH * 256];
__device__ float2 g_bml[NBCTA * NH];
__device__ uint4 g_outb[NBCTA * NH * 36];

#define TS(i)
#define TSV(i, v)
#define LAND(i)
#define CLK(x)
#define ACC(a, x, y)

__device__ __forceinline__ uint32_t smem_u32(const void* p) { return (uint32_t)__cvta_generic_to_shared(p); }
__device__ __forceinline__ void mbar_init(uint32_t bar, uint32_t cnt) {
    asm volatile("mbarrier.init.shared::cta.b64 [%0], %1;" ::"r"(bar), "r"(cnt) : "memory");
}
__device__ __forceinline__ void mbar_expect_tx(uint32_t bar, uint32_t bytes) {
    asm volatile("mbarrier.arrive.expect_tx.shared::cta.b64 _, [%0], %1;" ::"r"(bar), "r"(bytes) : "memory");
}
__device__ __forceinline__ bool mbar_try(uint32_t bar, uint32_t parity) {
    uint32_t ok;
    asm volatile("{\n.reg .pred p;\nmbarrier.try_wait.parity.shared::cta.b64 p, [%1], %2;\nselp.u32 %0, 1, 0, p;\n}\n"
                 : "=r"(ok) : "r"(bar), "r"(parity) : "memory");
    return ok;
}
__device__ __forceinline__ void mbar_wait(uint32_t bar, uint32_t parity) {
    unsigned n = 0;
    while (!mbar_try(bar, parity)) { if (++n > SPIN_LIMIT) __trap(); }
}
__device__ __forceinline__ void mbar_spin(uint32_t bar) {
    asm volatile("{\n.reg .pred p;\n.reg .u32 n;\nmov.u32 n, 0;\nSPIN:\nmbarrier.test_wait.parity.shared::cta.b64 p, [%0], 0;\n@p bra.uni DONE;\n"
                 "add.u32 n, n, 1;\nsetp.lt.u32 p, n, 0x4000000;\n@p bra.uni SPIN;\ntrap;\nDONE:\n}" ::"r"(bar) : "memory");
}
__device__ __forceinline__ void bulk_load(uint32_t dst, const void* src, uint32_t bytes, uint32_t bar, uint64_t pol) {
    asm volatile("cp.async.bulk.shared::cluster.global.mbarrier::complete_tx::bytes.L2::cache_hint [%0], [%1], %2, [%3], %4;"
                 ::"r"(dst), "l"(src), "r"(bytes), "r"(bar), "l"(pol) : "memory");
}
__device__ __forceinline__ void tma3d(uint32_t dst, const CUtensorMap* tm, int c0, int c1, int c2, uint32_t bar, uint64_t pol) {
    asm volatile("cp.async.bulk.tensor.3d.shared::cluster.global.mbarrier::complete_tx::bytes.L2::cache_hint [%0], [%1, {%3,%4,%5}], [%2], %6;"
                 ::"r"(dst), "l"(tm), "r"(bar), "r"(c0), "r"(c1), "r"(c2), "l"(pol) : "memory");
}
__device__ __forceinline__ void l2_prefetch(const void* src, uint32_t bytes) {
    asm volatile("cp.async.bulk.prefetch.L2.global [%0], %1;" ::"l"(src), "r"(bytes) : "memory");
}
__device__ __forceinline__ void ldsm4(uint32_t (&r)[4], uint32_t addr) {
    asm volatile("ldmatrix.sync.aligned.m8n8.x4.shared.b16 {%0,%1,%2,%3}, [%4];"
                 : "=r"(r[0]), "=r"(r[1]), "=r"(r[2]), "=r"(r[3]) : "r"(addr));
}
__device__ __forceinline__ void ldsm4t(uint32_t (&r)[4], uint32_t addr) {
    asm volatile("ldmatrix.sync.aligned.m8n8.x4.trans.shared.b16 {%0,%1,%2,%3}, [%4];"
                 : "=r"(r[0]), "=r"(r[1]), "=r"(r[2]), "=r"(r[3]) : "r"(addr));
}
__device__ __forceinline__ void mma16816(float (&d)[4], const uint32_t (&a)[4], uint32_t b0, uint32_t b1) {
    asm("mma.sync.aligned.m16n8k16.row.col.f32.bf16.bf16.f32 {%0,%1,%2,%3}, {%4,%5,%6,%7}, {%8,%9}, {%0,%1,%2,%3};"
        : "+f"(d[0]), "+f"(d[1]), "+f"(d[2]), "+f"(d[3])
        : "r"(a[0]), "r"(a[1]), "r"(a[2]), "r"(a[3]), "r"(b0), "r"(b1));
}
__device__ __forceinline__ uint32_t lds32(uint32_t a) {
    uint32_t v;
    asm volatile("ld.shared.u32 %0, [%1];" : "=r"(v) : "r"(a));
    return v;
}
__device__ __forceinline__ unsigned ld_acquire(const unsigned* p) {
    unsigned v;
    asm volatile("ld.acquire.gpu.global.u32 %0, [%1];" : "=r"(v) : "l"(p) : "memory");
    return v;
}
__device__ __forceinline__ uint2 ld_relaxed8(const void* p) {
    uint2 v;
    asm volatile("ld.relaxed.gpu.global.v2.u32 {%0,%1}, [%2];" : "=r"(v.x), "=r"(v.y) : "l"(p) : "memory");
    return v;
}
__device__ __forceinline__ unsigned ld_relaxed4(const void* p) {
    unsigned v;
    asm volatile("ld.relaxed.gpu.global.u32 %0, [%1];" : "=r"(v) : "l"(p) : "memory");
    return v;
}
__device__ __forceinline__ unsigned atom_inc(unsigned* p) {
    unsigned v;
    asm volatile("atom.relaxed.gpu.global.inc.u32 %0, [%1], 0x7fffffff;" : "=r"(v) : "l"(p) : "memory");
    return v;
}
__device__ __forceinline__ unsigned long long ld_relaxed64(const void* p) {
    unsigned long long v;
    asm volatile("ld.relaxed.gpu.global.u64 %0, [%1];" : "=l"(v) : "l"(p) : "memory");
    return v;
}
__device__ __forceinline__ void st_relaxed64(void* p, unsigned long long v) {
    asm volatile("st.relaxed.gpu.global.u64 [%0], %1;" ::"l"(p), "l"(v) : "memory");
}
__device__ __forceinline__ float4 ld_relaxed16(const void* p) {
    float4 v;
    asm volatile("ld.relaxed.gpu.global.v4.f32 {%0,%1,%2,%3}, [%4];" : "=f"(v.x), "=f"(v.y), "=f"(v.z), "=f"(v.w) : "l"(p) : "memory");
    return v;
}
__device__ __forceinline__ uint32_t mapa(uint32_t a, uint32_t rank) {
    uint32_t r;
    asm("mapa.shared::cluster.u32 %0, %1, %2;" : "=r"(r) : "r"(a), "r"(rank));
    return r;
}
__device__ __forceinline__ uint32_t time_ns() { uint32_t t; asm volatile("mov.u32 %0, %globaltimer_lo;" : "=r"(t)); return t; }
__device__ __forceinline__ void fence_gpu() { asm volatile("fence.acq_rel.gpu;" ::: "memory"); }
__device__ __forceinline__ void red_add_u32(unsigned* p, unsigned v) {
    asm volatile("red.relaxed.gpu.global.add.u32 [%0], %1;" ::"l"(p), "r"(v) : "memory");
}
__device__ __forceinline__ void st_tagged2(void* p, float a, float b, unsigned tag) {
    const unsigned long long hi = (unsigned long long)tag << 32;
    asm volatile("st.relaxed.gpu.global.v2.b64 [%0], {%1,%2};" ::"l"(p), "l"(hi | __float_as_uint(a)), "l"(hi | __float_as_uint(b)) : "memory");
}
__device__ __forceinline__ ulonglong2 ld_tagged2(const void* p) {
    ulonglong2 v;
    asm volatile("ld.relaxed.gpu.global.v2.b64 {%0,%1}, [%2];" : "=l"(v.x), "=l"(v.y) : "l"(p) : "memory");
    return v;
}
__device__ __forceinline__ float4 atom_add_f4(void* p, float a, float b, float c, float d) {
    float4 r;
    asm volatile("atom.relaxed.gpu.global.add.v4.f32 {%0,%1,%2,%3}, [%4], {%5,%6,%7,%8};"
                 : "=f"(r.x), "=f"(r.y), "=f"(r.z), "=f"(r.w) : "l"(p), "f"(a), "f"(b), "f"(c), "f"(d) : "memory");
    return r;
}
__device__ __forceinline__ void red_release_cta_shared(uint32_t a, unsigned v) {
    asm volatile("red.release.cta.shared::cta.add.u32 [%0], %1;" ::"r"(a), "r"(v) : "memory");
}
__device__ __forceinline__ unsigned ld_acquire_cta_shared(uint32_t a) {
    unsigned v;
    asm volatile("ld.acquire.cta.shared::cta.u32 %0, [%1];" : "=r"(v) : "r"(a) : "memory");
    return v;
}
__device__ __forceinline__ void st_release_cta_shared(uint32_t a, unsigned v) {
    asm volatile("st.release.cta.shared::cta.u32 [%0], %1;" ::"r"(a), "r"(v) : "memory");
}
__device__ __forceinline__ void wait_count(const unsigned* p, unsigned target) {
    unsigned n = 0;
    while (ld_acquire(p) < target) { if (++n > SPIN_LIMIT) __trap(); }
}
__device__ __forceinline__ uint32_t pack_bf16(float lo, float hi) {
    uint32_t r;
    asm("cvt.rn.bf16x2.f32 %0, %1, %2;" : "=r"(r) : "f"(hi), "f"(lo));
    return r;
}
__device__ __forceinline__ float bf_lo(uint32_t v) { return __uint_as_float(v << 16); }
__device__ __forceinline__ float bf_hi(uint32_t v) { return __uint_as_float(v & 0xffff0000u); }
__device__ __forceinline__ float ex2(float x) { float y; asm("ex2.approx.ftz.f32 %0, %1;" : "=f"(y) : "f"(x)); return y; }
__device__ __forceinline__ float expsub(float a, float b) { return ex2((a - b) * LOG2E); }
__device__ __forceinline__ float warp_max(float v) {
#pragma unroll
    for (int m = 16; m; m >>= 1) v = fmaxf(v, __shfl_xor_sync(~0u, v, m));
    return v;
}
__device__ __forceinline__ float warp_sum(float v) {
#pragma unroll
    for (int m = 16; m; m >>= 1) v += __shfl_xor_sync(~0u, v, m);
    return v;
}
template <bool CLU>
__device__ __forceinline__ unsigned unit_block(int u) {
    const unsigned x = ((unsigned)u & (NUK - 1)) / UPP;
    const int lg = u < NUK ? min(KMAX, max(KMIN, 29 - __clz(x | 1))) : (CLU && (int)x >= 4 * VS0 ? 0 : min(VMAX, max(VMIN, 29 - __clz((127 - x) | 1))));
    const unsigned r = x & ((4u << lg) - 1);
    return ((x - r + (r & ((1u << lg) - 1)) * 4 + (r >> lg)) * UPP) | ((unsigned)u & (UPP - 1));
}
__device__ __forceinline__ const char* block_src(const void* base, unsigned blk) {
    const unsigned po = blk / UPP;
    return reinterpret_cast<const char*>(base) + (size_t)(((po & 3) * NH + (po >> 2)) * UPP + blk % UPP) * TILE_BYTES;
}

template <bool CLU>
__device__ __forceinline__ void a_worker(const Params& p, int un, bool once, bool pre, bool hold, int nstatic, uint32_t slot, uint32_t bar,
                                         uint32_t help, unsigned epoch, uint64_t pol) {
    constexpr int NU = 2 * NUK, NR = CLU ? NREPC : NREP;
    const int lane = threadIdx.x & 31, g = lane >> 2, t = lane & 3;
    const int li = lane & 7;
    uint32_t kaddr[4], vaddr[8];
    {
        const int e = (lane >> 3) & 1, kk = lane >> 4;
#pragma unroll
        for (int s = 0; s < 4; s++) kaddr[s] = slot + (16 * li + e) * 256 + ((2 * s + kk + li) & 7) * 16;
        const int vrow = 4 * (li >> 1) + (li & 1) + 2 * kk;
#pragma unroll
        for (int c = 0; c < 8; c++) vaddr[c] = slot + vrow * 256 + e * 128 + ((c + li) & 7) * 16;
#pragma unroll
        for (int c = 0; c < 8; c++) asm volatile("" : "+r"(vaddr[c]));
    }
    const uint32_t vmask = (g >> 1) != t ? 0u : ((g & 1) ? 0xffff0000u : 0xffffu);
    int kseen = -1;
    unsigned long long H0 = 0, H1 = 0;
    auto header = [&](int v, unsigned vb) {
        if (v >= NU) return;
        const void *a0, *a1;
        if (v < NUK) {
            const unsigned po = vb / UPP;
            a0 = g_qll + (po & 3) * 2048 + (po >> 2) * 64 + lane;
            a1 = reinterpret_cast<const uint2*>(a0) + 32;
        } else {
            const int half = vb / (NUK / 2);
            if (half > kseen) {
                unsigned n = 0;
                while (ld_acquire_cta_shared(help + 12 + 4 * half) == 0) { if (++n > (SPIN_LIMIT << 4)) __trap(); }
                kseen = half;
            }
            a0 = &g_scores[vb * (KEYS / 4) + lane];
            a1 = &g_stats[(vb / UPP) * UPP + lane];
        }
        H0 = ld_relaxed64(a0);
        H1 = ld_relaxed64(a1);
    };
    asm volatile("bar.sync 2, %0;" ::"n"(32 * (NW + XW + 1)) : "memory");
    epoch = __shfl_sync(~0u, epoch, 0);
    if (hold) { unsigned n = 0; while (ld_acquire_cta_shared(help + 24) < 2) { if (++n > (SPIN_LIMIT << 4)) __trap(); } }
    unsigned (*ctl)[32] = g_ctl[epoch & 1];
    const unsigned tag = epoch + 1;
    unsigned nxt = once ? NU : 0;
    int u = -1;
    unsigned bu = 0, bn = unit_block<CLU>(un);
    bool have = false;
    uint32_t phase = 0;
    unsigned kpend = 0;
    const unsigned zero = gridDim.x >> 24;
    uint32_t Q[16];
    float4 oret = make_float4(0.f, 0.f, 0.f, 0.f);
    while (true) {
        const char* nsrc = block_src(un < NUK ? p.kc : p.vc, bn);
        float4* odst = &g_oacc[(bu / UPP) * 32 + lane];
        unsigned* vdst = &g_vdone[(lane & (NR - 1)) * NH + bu / (4 * UPP)][0];
        float d[8][4];
        CLK(c1);
        asm volatile("" : "+l"(odst));
        if (u >= NUK) {
#pragma unroll
            for (int j = 0; j < 8; j++) { d[j][0] = d[j][1] = d[j][2] = d[j][3] = 0.f; }
            mbar_wait(bar, phase);
            LAND(NUK + bu);
            uint32_t a[2][8][4];
#pragma unroll
            for (int c = 0; c < 8; c++) ldsm4t(a[0][c], vaddr[c]);
#pragma unroll
            for (int j = 0; j < 8; j++) {
                if (j < 7) {
#pragma unroll
                    for (int c = 0; c < 8; c++) ldsm4t(a[(j + 1) & 1][c], vaddr[c] + (j + 1) * 4096);
                }
#pragma unroll
                for (int c = 0; c < 8; c++) mma16816(d[c], a[j & 1][c], Q[2 * j], Q[2 * j + 1]);
            }
            float o[4];
#pragma unroll
            for (int r = 0; r < 2; r++) {
                o[2 * r] = d[0][2 * r] + d[7][2 * r + 1];
                o[2 * r + 1] = d[0][2 * r + 1] + d[1][2 * r];
#pragma unroll
                for (int k = 1; k < 4; k++) {
                    const int src = (lane & 28) | ((t - k) & 3);
                    o[2 * r] += __shfl_sync(~0u, d[2 * k][2 * r] + d[2 * k - 1][2 * r + 1], src);
                    o[2 * r + 1] += __shfl_sync(~0u, d[2 * k][2 * r + 1] + d[2 * k + 1][2 * r], src);
                }
            }
            oret = atom_add_f4(odst, o[0], o[1], o[2], o[3]);
        } else if (u >= 0) {
#pragma unroll
            for (int j = 0; j < 8; j++) { d[j][0] = d[j][1] = d[j][2] = d[j][3] = 0.f; }
            mbar_wait(bar, phase);
            LAND(bu);
            uint32_t a[2][8][4];
#pragma unroll
            for (int j = 0; j < 8; j++) ldsm4(a[0][j], kaddr[0] + (4 * (j & 3) + 2 * (j >> 2)) * 256);
#pragma unroll
            for (int s = 0; s < 8; s++) {
                if (s < 7) {
#pragma unroll
                    for (int j = 0; j < 8; j++)
                        ldsm4(a[(s + 1) & 1][j], kaddr[(s + 1) & 3] + (4 * (j & 3) + 2 * (j >> 2)) * 256 + ((s + 1) >> 2) * 128);
                }
#pragma unroll
                for (int j = 0; j < 8; j++)
                    mma16816(d[j], a[s & 1][j], Q[(s & 4) * 2 + ((2 * s - 2 * j) & 7)], Q[(s & 4) * 2 + ((2 * s + 1 - 2 * j) & 7)]);
            }
        }
        if (u >= 0) phase ^= 1;
        CLK(c2b);
        if (un < NU && lane == 0) {
            if (!once) nxt = atom_inc(&ctl[C_QUEUE][0]);
            if (u >= 0 || !pre) {
                mbar_expect_tx(bar, TILE_BYTES);
                bulk_load(slot, nsrc, TILE_BYTES, bar, pol);
            }
        }
        const uint32_t tk = clock();
        CLK(c3);
        if ((unsigned)u < (unsigned)NUK) {
            const int j0 = (t - (g >> 1)) & 3;
            float v[4];
#pragma unroll
            for (int q = 0; q < 4; q++) {
                const int jq = (q >> 1) * 4, e = (q & 1) * 2;
                const float x0 = (g & 1) ? d[jq + 0][e + 1] : d[jq + 0][e];
                const float x1 = (g & 1) ? d[jq + 1][e + 1] : d[jq + 1][e];
                const float x2 = (g & 1) ? d[jq + 2][e + 1] : d[jq + 2][e];
                const float x3 = (g & 1) ? d[jq + 3][e + 1] : d[jq + 3][e];
                const float y0 = (j0 & 1) ? x1 : x0, y1 = (j0 & 1) ? x3 : x2;
                v[q] = (j0 & 2) ? y1 : y0;
            }
            const uint32_t r0 = pack_bf16(v[0], v[1]), r1 = pack_bf16(v[2], v[3]);
            const uint32_t s0 = pack_bf16(bf_lo(r0) * SCALE, bf_hi(r0) * SCALE);
            const uint32_t s1 = pack_bf16(bf_lo(r1) * SCALE, bf_hi(r1) * SCALE);
            g_scores[bu * (KEYS / 4) + 4 * g + j0] = make_uint2(s0, s1);
            const float f0 = bf_lo(s0), f1 = bf_hi(s0), f2 = bf_lo(s1), f3 = bf_hi(s1);
            const float m = warp_max(fmaxf(fmaxf(f0, f1), fmaxf(f2, f3)));
            const float l = warp_sum((expsub(f0, m) + expsub(f1, m)) + (expsub(f2, m) + expsub(f3, m)));
            if (lane == 0) g_stats[bu] = make_float2(m, l);
            kpend++;
            if (un / (NUK / 2) != u / (NUK / 2)) {
                __syncwarp();
                if (lane == 0) {
                    red_release_cta_shared(help + 4 * (u / (NUK / 2)), kpend);
                    if (un >= NUK) red_release_cta_shared(help + 8, 1u);
                }
                kpend = 0;
            }
        }
        CLK(c4);
        int unn = NU;
        if (un < NU) {
            unsigned n = 0;
            while (true) {
                if (!have) header(un, bn);
                if (un >= NUK || __all_sync(~0u, (uint32_t)(H0 >> 32) == tag && (uint32_t)(H1 >> 32) == tag)) break;
                if (++n > SPIN_LIMIT) __trap();
                have = false;
            }
            if (un >= NUK) {
                const uint32_t s0 = (uint32_t)H0, s1 = (uint32_t)(H0 >> 32);
                const float mu = __uint_as_float((uint32_t)H1);
                const float m = warp_max(mu);
                const float l = warp_sum(__uint_as_float((uint32_t)(H1 >> 32)) * expsub(mu, m));
                const float inv = 1.0f / l;
                const uint32_t w0 = pack_bf16(expsub(bf_lo(s0), m) * inv, expsub(bf_hi(s0), m) * inv);
                const uint32_t w1 = pack_bf16(expsub(bf_lo(s1), m) * inv, expsub(bf_hi(s1), m) * inv);
#pragma unroll
                for (int j = 0; j < 8; j++) {
                    Q[2 * j] = __shfl_sync(~0u, w0, 4 * j + t) & vmask;
                    Q[2 * j + 1] = __shfl_sync(~0u, w1, 4 * j + t) & vmask;
                }
            } else {
#pragma unroll
                for (int j = 0; j < 8; j++) {
                    const int src = (((j + g) & 7) << 2) + t;
                    Q[j] = __shfl_sync(~0u, (uint32_t)H0, src);
                    Q[8 + j] = __shfl_sync(~0u, (uint32_t)H1, src);
                }
            }
            unn = nstatic + (int)__shfl_sync(~0u, nxt, 0);
            if (CLU && ((NU - EARLY - unn) & ~(7 << ELOG)) == 0 && lane < MINCL)
                st_relaxed64(&g_dry[lane][(NU - EARLY - unn) >> ELOG],
                             (time_ns() - (((uint32_t)clock() - tk) >> 1) + (NU - unn) * TPU / 16) | (unsigned long long)tag << 32);
        }
        if (u >= NUK && lane < NR)
            red_add_u32(vdst,
                        1u + ((__float_as_uint(oret.x) | __float_as_uint(oret.y) | __float_as_uint(oret.z) | __float_as_uint(oret.w)) & zero));
        if (un >= NU) break;
        bu = bn;
        have = !(un < NUK && unn >= NUK && !(un >= NUK / 2 && unn < NUK + NUK / 2));
        bn = unit_block<CLU>(unn);
        if (have) header(unn, bn);
        u = un;
        un = unn;
    }
}

__device__ __forceinline__ void k_helper(uint32_t help, unsigned epoch) {
    if ((threadIdx.x & 31) != 0) return;
    unsigned (*ctl)[32] = g_ctl[epoch & 1];
    unsigned sent0 = 0, sent1 = 0, n = 0;
    int seen = 0;
    bool fin = false;
    while (!fin || seen < 2) {
        if (!fin) {
            fin = ld_acquire_cta_shared(help + 8) == NW + XW;
            const unsigned c0 = ld_acquire_cta_shared(help), c1 = ld_acquire_cta_shared(help + 4);
            if (c0 != sent0 || c1 != sent1) {
                fence_gpu();
                if (c0 != sent0) red_add_u32(&ctl[C_KDONE][0], c0 - sent0);
                if (c1 != sent1) red_add_u32(&ctl[C_KDONE + 1][0], c1 - sent1);
                sent0 = c0; sent1 = c1;
            }
        }
        if (seen < 2 && ld_acquire(&ctl[C_KDONE + seen][0]) >= NUK / 2) {
            st_release_cta_shared(help + 12 + 4 * seen, 1u);
            seen++;
        } else {
            __nanosleep(300);
        }
        if (++n > SPIN_LIMIT) __trap();
    }
}

__device__ __forceinline__ void v_poller(uint32_t sbase, int f, int w) {
    constexpr int HL = NH;
    const int lane = threadIdx.x & 31;
    const unsigned (*cp)[32] = &g_vdone[((f * NPOLL + w) % NREP) * NH];
    unsigned n = 0;
    while (ld_acquire_cta_shared(sbase + M_HELP + 12) == 0) { __nanosleep(1000); if (++n > SPIN_LIMIT) __trap(); }
    int h = 0;
    bool fast = false;
    while (h < HL) {
        const unsigned r = __ballot_sync(~0u, ld_acquire(&cp[min(h + (lane & 3), HL - 1)][0]) >= 4 * UPP) & 15u;
        if (r & 1) {
            h = min(HL, h + __ffs(~r) - 1);
            __syncwarp();
            if (lane == 0) asm volatile("red.release.cta.shared::cta.max.u32 [%0], %1;" ::"r"(sbase + M_HELP + 20), "r"(h) : "memory");
        }
        if (h < HL - 4) {
            __nanosleep(h ? 300 : 1000);
        } else if (!fast) {
            fast = true;
            const long long t0 = clock64();
            while (clock64() - t0 < w * PGAP) {}
        }
        if (++n > SPIN_LIMIT) __trap();
    }
}
__device__ __forceinline__ void finisher(const Params& p, uint32_t sbase, int f) {
    constexpr int HL = NH;
    const int lane = threadIdx.x & 31;
    {
        const char* wg = reinterpret_cast<const char*>(p.wo);
        const uint32_t dst = sbase + 4 * SLOT + (16 * (lane & 7) + (lane >> 3)) * 16;
#pragma unroll 1
        for (int h = -FPF - 4; h < HL; h++) {
            if (lane == 0 && (unsigned)(h + FPF) < (unsigned)HL) l2_prefetch(wg + (size_t)(h + FPF) * 147456 + f * 2048, 2048);
            if (h >= 0) {
#pragma unroll
                for (int r = 0; r < 4; r++)
                    asm volatile("cp.async.cg.shared.global [%0], [%1], 16;" ::"r"(dst + h * 2048 + ((r & 1) * 4 + (r >> 1) * 8) * 16),
                                 "l"(wg + (size_t)(h * 128 + r * 32 + lane) * (DM * 2) + f * 16) : "memory");
            }
            __nanosleep(FSLEEP);
        }
        asm volatile("cp.async.wait_all;" ::: "memory");
        __syncwarp();
    }
    TS(11);
    const float4* vec = g_oacc + ((lane >> 2) & 3) * 32 + (lane >> 4) * 16 + (lane & 3);
    float acc[2][2][4];
#pragma unroll
    for (int i = 0; i < 16; i++) acc[i >> 3][(i >> 2) & 1][i & 3] = 0.f;
    uint32_t* outp = reinterpret_cast<uint32_t*>(p.out + (lane >> 2) * (2 * DM) + f * 8 + (lane & 3) * 2);
    uint32_t wa = sbase + 4 * SLOT + lane * 16;
    auto project = [&](const float4 (&x)[4], const uint32_t (&w)[4][4]) {
#pragma unroll
        for (int s = 0; s < 4; s++) {
            const uint32_t a[4] = {pack_bf16(x[s].x, x[s].y), 0u, pack_bf16(x[s].z, x[s].w), 0u};
            mma16816(acc[0][s & 1], a, w[s >> 1][(s & 1) * 2], w[s >> 1][(s & 1) * 2 + 1]);
            mma16816(acc[1][s & 1], a, w[2 + (s >> 1)][(s & 1) * 2], w[2 + (s >> 1)][(s & 1) * 2 + 1]);
        }
    };
    int h = 0;
    unsigned n = 0;
    while (h < HL) {
        uint32_t w[4][4];
#pragma unroll
        for (int q = 0; q < 4; q++) ldsm4t(w[q], wa + q * 512);
        int ready;
        while ((ready = ld_acquire_cta_shared(sbase + M_HELP + 20)) <= h) {
            if (h < HL - 3) __nanosleep(100);
            if (++n > (SPIN_LIMIT << 4)) __trap();
        }
        float4 x[4], y[4];
#pragma unroll
        for (int s = 0; s < 4; s++) x[s] = ld_relaxed16(vec + s * 4);
        const bool two = ready > h + 1;
        if (two) {
#pragma unroll
            for (int s = 0; s < 4; s++) y[s] = ld_relaxed16(vec + 128 + s * 4);
        }
        project(x, w);
        if (two) {
#pragma unroll
            for (int q = 0; q < 4; q++) ldsm4t(w[q], wa + 2048 + q * 512);
            project(y, w);
        }
        const int nr = two ? 2 : 1;
        h += nr;
        vec += nr * 128;
        wa += nr * 2048;
        const float o0 = acc[0][0][0] + acc[0][1][0] + __shfl_down_sync(~0u, acc[1][0][0] + acc[1][1][0], 16);
        const float o1 = acc[0][0][1] + acc[0][1][1] + __shfl_down_sync(~0u, acc[1][0][1] + acc[1][1][1], 16);
        asm volatile("{\n.reg .pred p;\nsetp.ne.u32 p, %2, 0;\n@p st.global.u32 [%0], %1;\n}" ::"l"(outp), "r"(pack_bf16(o0, o1)),
                     "r"((uint32_t)(lane < 16 && h == NH)) : "memory");
    }
}

__device__ __noinline__ void f_collect(const unsigned (*flag)[32], unsigned full, const float4* src, bool last, uint32_t sbase) {
    const int lane = threadIdx.x & 31, g = lane >> 2, t = lane & 3;
    unsigned n = 0, todo = 15;
    while (todo) {
        const unsigned v = ld_acquire(&flag[t][0]);
        unsigned m = __ballot_sync(~0u, v == full) & todo;
        if (m == 0) {
            if (!last || (todo == 15 && __shfl_sync(~0u, v, 0) == 0)) __nanosleep(200);
            if (++n > SPIN_LIMIT) __trap();
            continue;
        }
        __syncwarp();
        todo ^= m;
        if (last && todo == 0) TS(16);
        do {
            const int h0 = __ffs(m) - 1, h1 = 31 - __clz(m);
            m &= ~((1u << h0) | (1u << h1));
            float4 x[2][4];
#pragma unroll
            for (int b = 0; b < 8; b++) x[b >> 2][b & 3] = ld_relaxed16(src + ((b & 4) ? h1 : h0) * 128 + (b & 3) * 32 + lane);
#pragma unroll
            for (int b = 0; b < 8; b++) {
                const float4 v = x[b >> 2][b & 3];
                const uint32_t lo = pack_bf16(v.x, v.y), hi = pack_bf16(v.z, v.w);
                const uint32_t o = __shfl_xor_sync(~0u, (g & 1) ? lo : hi, 4);
                const uint32_t e0 = (g & 1) ? o : lo, e1 = (g & 1) ? hi : o;
                asm volatile("st.shared.v2.u32 [%0], {%1,%2};"
                             ::"r"(sbase + F_BF + ((b & 4) ? h1 : h0) * 1024 + t * 256 + ((b ^ t) & 3) * 64 + g * 8),
                               "r"(__byte_perm(e0, e1, 0x5410)), "r"(__byte_perm(e0, e1, 0x7632)) : "memory");
            }
            __syncwarp();
            if (lane < (h0 == h1 ? 1 : 2))
                asm volatile("mbarrier.arrive.shared::cta.b64 _, [%0];" ::"r"(sbase + F_BAR + 32 + (lane ? h1 : h0) * 8) : "memory");
            if (last && (h0 == 2 || h1 == 2)) TS(21);
        } while (m);
    }
    if (last) TS(17);
}

__device__ __noinline__ void f_project(const CUtensorMap* tm, int panel, int rank, int sl, int j, int delay, int step, unsigned tag, uint32_t sbase, uint64_t pol) {
    const int lane = threadIdx.x & 31, g = lane >> 2, t = lane & 3;
    const uint32_t wb = sbase + F_W - sl * 2 * SLOT, bars = sbase + F_BAR + 64 + sl * 32 * PH;
    const uint32_t wa = wb + ((lane & 7) + (lane >> 4) * 8) * 128 + (((2 * j + ((lane >> 3) & 1)) ^ (lane & 7)) * 16);
    const uint32_t ba = sbase + F_BF + (g & 3) * 64 + t * 16;
    const uint32_t rdst = mapa(sbase + F_RX + sl * 1024 + rank * 128 + g * 16 + (t & 1) * 8, 2 * j + (t >> 1));
    const uint32_t rbar = mapa(sbase + F_BAR + 16 + sl * 8, 2 * j + (t >> 1));
    unsigned n = 0;
    if (threadIdx.x >= 224) {
        if (lane == 0) asm volatile("prefetch.tensormap [%0];" ::"l"(tm) : "memory");
        unsigned long long v;
        while (!__all_sync(~0u, (v = ld_relaxed64(&g_dry[blockIdx.x >> 3][g])) >> 32 == tag)) {
            __nanosleep(200);
            if (++n > SPIN_LIMIT) __trap();
        }
        const uint32_t t0 = __shfl_sync(~0u, (uint32_t)v, 0);
        const uint32_t t1 = t0 + (__reduce_add_sync(~0u, (int)((uint32_t)v - t0)) >> 5);
        if (lane == 0) asm volatile("st.shared.u32 [%0+8], %1;\nmbarrier.arrive.shared::cta.b64 _, [%0];" ::"r"(sbase + F_BAR), "r"(t1) : "memory");
        TS(22);
    }
    mbar_wait(sbase + F_BAR, 0);
    if (lane == 0) {
        uint32_t due = lds32(sbase + F_BAR + 8) + delay;
#pragma unroll 1
        for (int q = j * PH; q < (j + 1) * PH; q++, due += step) {
            mbar_expect_tx(bars + q * 8, 16384 / PH);
            while ((int)(time_ns() - due) < 0) {}
            tma3d(wb + q * (16384 / PH), tm, 0, rank * 512 + q * (128 / PH), panel, bars + q * 8, pol);
        }
    }
    __syncwarp();
    TS(18);
#define NCH 2
    float acc[4][4];
#pragma unroll
    for (int i = 0; i < 16; i++) acc[i >> 2][i & 3] = 0.f;
    const bool up = t & 2;
#pragma unroll 1
    for (int h = 0; h < 4; h++) {
        uint32_t wp = wa + h * 16384, bar = bars + h * PH * 8, last = h == 3;
        mbar_spin(sbase + F_BAR + 32 + h * 8);
        uint32_t bf[4][4];
#pragma unroll
        for (int s = 0; s < 4; s++)
            asm volatile("ld.shared.v4.u32 {%0,%1,%2,%3}, [%4];" : "=r"(bf[s][0]), "=r"(bf[s][1]), "=r"(bf[s][2]), "=r"(bf[s][3])
                         : "r"(((ba + h * 1024) ^ (s * 64)) + s * 256) : "memory");
        asm volatile("" : "+r"(wp), "+r"(bar), "+r"(last));
#pragma unroll
        for (int q = 0; q < PH; q++) {
            mbar_spin(bar + q * 8);
            if (h == 3 && q == PH - 1) TS(19);
            uint32_t a[8 / PH][4];
#pragma unroll
            for (int s = 0; s < 8 / PH; s++) ldsm4t(a[s], wp + (q * (8 / PH) + s) * 2048);
#pragma unroll
            for (int s = 0; s < 8 / PH; s++) {
                const int k = q * (8 / PH) + s;
                mma16816(acc[s & (NCH - 1)], a[s], bf[k & 3][(k >> 2) * 2], bf[k & 3][(k >> 2) * 2 + 1]);
            }
        }
        float v0 = up ? acc[0][2] + acc[1][2] : acc[0][0] + acc[1][0], v1 = up ? acc[0][3] + acc[1][3] : acc[0][1] + acc[1][1];
        if (NCH == 4) {
            v0 = (v0 + (up ? acc[2][2] : acc[2][0])) + (up ? acc[3][2] : acc[3][0]);
            v1 = (v1 + (up ? acc[2][3] : acc[2][1])) + (up ? acc[3][3] : acc[3][1]);
        }
        asm volatile("{\n.reg .pred p;\nsetp.ne.u32 p, %4, 0;\n"
                     "@p st.async.weak.shared::cluster.mbarrier::complete_tx::bytes.v2.b32 [%0], {%1,%2}, [%3];\n}"
                     ::"r"(rdst), "r"(__float_as_uint(v0)), "r"(__float_as_uint(v1)), "r"(rbar), "r"(last) : "memory");
    }
    TS(20);
}

__device__ __noinline__ void f_receive(__nv_bfloat16* out, int sl, uint32_t sbase) {
    const int lane = threadIdx.x & 31;
    out += (lane & 3) * (2 * DM) + (lane >> 2);
    unsigned n = 0;
    uint32_t ok;
    do {
        do {
            asm volatile("{\n.reg .pred p;\nmbarrier.test_wait.parity.acquire.cluster.shared::cta.b64 p, [%1], 0;\nselp.u32 %0, 1, 0, p;\n}\n"
                         : "=r"(ok) : "r"(sbase + F_BAR + 16 + sl * 8) : "memory");
            if (n > (SPIN_LIMIT << 2)) __trap();
        } while (n++ && !ok);
        float v[8];
#pragma unroll
        for (int r = 0; r < 8; r++)
            asm volatile("ld.shared.f32 %0, [%1];" : "=f"(v[r]) : "r"(sbase + F_RX + sl * 1024 + r * 128 + lane * 4) : "memory");
        const float o = ((v[0] + v[1]) + (v[2] + v[3])) + ((v[4] + v[5]) + (v[6] + v[7]));
        asm volatile("{\n.reg .pred p;\nsetp.ne.u32 p, %2, 0;\n@p st.global.u16 [%0], %1;\n}"
                     ::"l"(out), "h"((unsigned short)pack_bf16(o, 0.f)), "r"(ok) : "memory");
    } while (!ok);
    TS(15);
}

__device__ __forceinline__ void b_final(const Params& p, uint32_t sbase, int blk, unsigned epoch, uint64_t pol) {
    const int warp = threadIdx.x >> 5;
    const int rank = blk & 7, sl = warp >> 2, panel = (blk >> 3) * 2 + sl;
    asm volatile("barrier.cluster.wait.acquire.aligned;" ::: "memory");
    if (warp == 0) f_collect(&g_cdone[4 * rank], epoch + 1, &g_octx[4 * rank * 128], false, sbase);
    f_project(&p.tm_fb, panel, rank, sl, warp & 3, B0 + (warp & 3) * BJ + sl * BS + rank * BR - max(0, (warp & 3) * 8 + rank - BK) * BC, BJ / PH, epoch + 1, sbase, pol);
    if ((warp & 3) == 0) f_receive(p.out + DM + panel * 64 + rank * 8, sl, sbase);
}

constexpr int BS_WUK = 5, BS_Q = 9, BS_CKV = 11, BS_PART = 27, BS_WUV = 29, BS_END = 33;

__device__ __noinline__ void b_issue(const Params& p, int n, int bi, uint32_t sbase, uint64_t pol) {
    if (n >= BS_END || (n >= BS_Q && n < BS_CKV) || (n >= BS_PART && n < BS_WUV)) return;
    const uint32_t bar = sbase + M_BAR + (NSLOT + n % BRING) * 8;
    const CUtensorMap* tm;
    int row, panel = 2 * bi;
    if (n < BS_WUK) { tm = &p.tm_wq; row = n * 128; }
    else if (n < BS_Q) { tm = &p.tm_wuk; row = (n - BS_WUK) * 128; }
    else if (n < BS_PART) {
        tm = &p.tm_ckv; panel = 0;
        row = (bi >> 3) * SK + ((n - BS_CKV) * 8 + (bi & 7)) * 32;
    }
    else { tm = &p.tm_wuv; row = (n - BS_WUV) * 128; }
    mbar_expect_tx(bar, n == 0 ? 32768 + 4 * 1152 : 32768);
    tma3d(sbase + (n % BRING) * SLOT, tm, 0, row, panel, bar, pol);
}
__device__ __forceinline__ void b_issue_xchg(int n, const void* src, uint32_t sbase, uint64_t pol) {
    asm volatile("fence.proxy.async;" ::: "memory");
#pragma unroll
    for (int i = 0; i < 2; i++) {
        const uint32_t bar = sbase + M_BAR + (NSLOT + (n + i) % BRING) * 8;
        mbar_expect_tx(bar, 32768);
        bulk_load(sbase + ((n + i) % BRING) * SLOT, reinterpret_cast<const char*>(src) + i * 32768, 32768, bar, pol);
    }
}
__device__ __forceinline__ void b_wait(int n, uint32_t sbase) {
    mbar_wait(sbase + M_BAR + (NSLOT + n % BRING) * 8, (n / BRING) & 1);
}

__device__ __noinline__ void b_gemm(const Params& p, uint32_t sbase, int n0, int n1, int ktot, uint32_t xh, uint32_t xl, int pitch,
                                    int bi, uint64_t pol) {
    const int tid = threadIdx.x, warp = tid >> 5, lane = tid & 31, g = lane >> 2, t = lane & 3;
    const uint32_t woff = (warp >> 2) * 16384 + (lane & 15) * 128 + ((((warp & 3) * 2 + (lane >> 4)) ^ (lane & 7)) * 16);
    const uint32_t xoff = (g & 3) * pitch + t * 4;
    float acc[2][4];
#pragma unroll
    for (int i = 0; i < 8; i++) acc[i >> 2][i & 3] = 0.f;
#pragma unroll 1
    for (int n = n0; n < n1; n++) {
        b_wait(n, sbase);
        const uint32_t slot = sbase + (n % BRING) * SLOT + woff;
        const int k0 = (n - n0) * 128;
        const int ns = min(8, (ktot - k0) >> 4);
#pragma unroll 2
        for (int s = 0; s < ns; s++) {
            uint32_t a[4], w[4];
            const uint32_t xo = xoff + (k0 + 16 * s) * 2;
            a[0] = lds32(xh + xo); a[2] = lds32(xh + xo + 16);
            a[1] = xl ? lds32(xl + xo) : 0u; a[3] = xl ? lds32(xl + xo + 16) : 0u;
            ldsm4t(w, slot + s * 2048);
            mma16816(acc[0], a, w[0], w[1]);
            mma16816(acc[1], a, w[2], w[3]);
        }
        __syncthreads();
        if (tid == 0) b_issue(p, n + BD, bi, sbase, pol);
    }
    if (g < 4) {
#pragma unroll
        for (int j = 0; j < 2; j++)
            asm volatile("st.shared.u32 [%0], %1;" ::"r"(sbase + M_QB + g * QP + (warp * 16 + j * 8 + t * 2) * 2),
                         "r"(pack_bf16(acc[j][0] + acc[j][2], acc[j][1] + acc[j][3])) : "memory");
    }
    __syncthreads();
}

__device__ __forceinline__ void b_exchange(unsigned* c, int n, const void* src, uint32_t sbase, uint64_t pol) {
    TS(n == BS_Q ? 24 : 28);
    __syncthreads();
    if (threadIdx.x == 0) {
        TS(n == BS_Q ? 25 : 29);
        fence_gpu();
        TS(n == BS_Q ? 26 : 30);
        red_add_u32(c, 1u);
        wait_count(c, NBCTA);
        TS(n == BS_Q ? 27 : 31);
        b_issue_xchg(n, src, sbase, pol);
    }
}

template <bool CLU>
__device__ __noinline__ void b_chain(const Params& p, char* smem, uint32_t sbase, int bi, unsigned epoch, uint64_t pol) {
    const int tid = threadIdx.x, warp = tid >> 5, lane = tid & 31, g = lane >> 2, t = lane & 3;
    unsigned (*ctl)[32] = g_ctl[epoch & 1];
    float* red = reinterpret_cast<float*>(smem + 5 * SLOT);
    __syncthreads();
    b_gemm(p, sbase, 0, BS_WUK, DM, sbase + M_XB, 0, XP, bi, pol);
    TS(6);
    {
        uint32_t Q[16];
#pragma unroll
        for (int c = 0; c < 16; c++) Q[c] = lds32(sbase + M_QB + (g & 3) * QP + c * 16 + t * 4);
        float* qa = reinterpret_cast<float*>(smem + M_QA);
#pragma unroll 1
        for (int n = BS_WUK; n < BS_Q; n++) {
            b_wait(n, sbase);
            const uint32_t base = sbase + (n % BRING) * SLOT + (warp * 16 + (lane & 15)) * 128;
            float d[2][4];
#pragma unroll
            for (int i = 0; i < 8; i++) d[i >> 2][i & 3] = 0.f;
#pragma unroll
            for (int s = 0; s < 8; s++) {
                uint32_t a[4];
                ldsm4(a, base + (s >> 2) * 16384 + (((2 * (s & 3) + (lane >> 4)) ^ (lane & 7)) * 16));
                mma16816(d[s & 1], a, Q[2 * s], Q[2 * s + 1]);
            }
            const int c = (n - BS_WUK) * 128 + warp * 16 + g + 8 * (t >> 1);
            qa[(2 * (t & 1)) * 512 + c] = (t & 2) ? d[0][2] + d[1][2] : d[0][0] + d[1][0];
            qa[(2 * (t & 1) + 1) * 512 + c] = (t & 2) ? d[0][3] + d[1][3] : d[0][1] + d[1][1];
            __syncthreads();
            if (tid == 0) b_issue(p, n + BD, bi, sbase, pol);
        }
#pragma unroll 1
        for (int r = 0; r < 2; r++) {
            const int id = tid + r * 256;
            const int b = id >> 7, c0 = ((id >> 2) & 31) * 16 + (id & 3) * 2;
            const float2 u0 = *reinterpret_cast<const float2*>(qa + b * 512 + c0);
            const float2 u1 = *reinterpret_cast<const float2*>(qa + b * 512 + c0 + 8);
            const uint32_t h0 = pack_bf16(u0.x, u0.y), h1 = pack_bf16(u1.x, u1.y);
            const uint32_t l0 = pack_bf16(u0.x - bf_lo(h0), u0.y - bf_hi(h0)), l1 = pack_bf16(u1.x - bf_lo(h1), u1.y - bf_hi(h1));
            g_qabs[((id >> 2) * 4 + (bi >> 3)) * 32 + (bi & 7) * 4 + (id & 3)] = make_uint4(h0, l0, h1, l1);
        }
    }
    b_exchange(&ctl[C_BBAR][0], BS_Q, &g_qabs[(bi >> 3) * 4096], sbase, pol);
    {
        uint32_t qf[4][4][4];
        b_wait(BS_Q + (warp >> 2), sbase);
        TS(7);
        {
            const uint4* qs = reinterpret_cast<const uint4*>(smem + ((BS_Q + (warp >> 2)) % BRING) * SLOT) + (warp & 3) * 512 + lane;
#pragma unroll
            for (int s = 0; s < 4; s++)
#pragma unroll
                for (int i = 0; i < 4; i++) {
                    const uint4 v = qs[(s * 4 + i) * 32];
                    qf[i][s][0] = v.x; qf[i][s][1] = v.y; qf[i][s][2] = v.z; qf[i][s][3] = v.w;
                }
        }
        __syncthreads();
        if (tid == 0) { b_issue(p, BS_Q + BD, bi, sbase, pol); b_issue(p, BS_Q + 1 + BD, bi, sbase, pol); }
        float acc[2][8][4];
#pragma unroll
        for (int i = 0; i < 2; i++)
#pragma unroll
            for (int j = 0; j < 8; j++) { acc[i][j][0] = acc[i][j][1] = acc[i][j][2] = acc[i][j][3] = 0.f; }
        float mrun = -INFINITY, lrun = 0.f;
        const int head = tid >> 3, kq = tid & 7;
        float* alpha = reinterpret_cast<float*>(smem + M_ALPHA);
        for (int n = BS_CKV; n < BS_PART; n++) {
            b_wait(n, sbase);
            const uint32_t slot = sbase + (n % BRING) * SLOT;
            float sc[4][4][4];
#pragma unroll
            for (int i = 0; i < 4; i++)
#pragma unroll
                for (int j = 0; j < 4; j++) { sc[i][j][0] = sc[i][j][1] = sc[i][j][2] = sc[i][j][3] = 0.f; }
#pragma unroll
            for (int j = 0; j < 4; j++)
#pragma unroll
                for (int sp = 0; sp < 2; sp++) {
                    uint32_t bf[4];
                    ldsm4(bf, slot + warp * 4096 + (8 * j + (lane & 7)) * 128 + (((4 * sp + (lane >> 3)) ^ (lane & 7)) * 16));
#pragma unroll
                    for (int i = 0; i < 4; i++) {
                        mma16816(sc[i][j], qf[i][2 * sp], bf[0], bf[1]);
                        mma16816(sc[i][j], qf[i][2 * sp + 1], bf[2], bf[3]);
                    }
                }
#pragma unroll
            for (int i = 0; i < 4; i++)
#pragma unroll
                for (int j = 0; j < 4; j++)
                    *reinterpret_cast<float2*>(red + warp * 1024 + (8 * i + g) * 32 + ((8 * j) ^ (8 * (g & 3))) + 2 * t) =
                        make_float2(sc[i][j][0] + sc[i][j][2], sc[i][j][1] + sc[i][j][3]);
            __syncthreads();
            if (tid == 0 && n > BS_CKV) b_issue(p, n - 1 + BD, bi, sbase, pol);
            {
                float4 s = make_float4(0.f, 0.f, 0.f, 0.f);
#pragma unroll
                for (int w = 0; w < 8; w++) {
                    const float4 v = *reinterpret_cast<const float4*>(red + w * 1024 + head * 32 + ((4 * kq) ^ (8 * (head & 3))));
                    s.x += v.x; s.y += v.y; s.z += v.z; s.w += v.w;
                }
                const uint32_t r0 = pack_bf16(s.x, s.y), r1 = pack_bf16(s.z, s.w);
                const uint32_t s0 = pack_bf16(bf_lo(r0) * SCALE, bf_hi(r0) * SCALE);
                const uint32_t s1 = pack_bf16(bf_lo(r1) * SCALE, bf_hi(r1) * SCALE);
                const float f0 = bf_lo(s0), f1 = bf_hi(s0), f2 = bf_lo(s1), f3 = bf_hi(s1);
                float mx = fmaxf(fmaxf(f0, f1), fmaxf(f2, f3));
                mx = fmaxf(mx, __shfl_xor_sync(~0u, mx, 1));
                mx = fmaxf(mx, __shfl_xor_sync(~0u, mx, 2));
                mx = fmaxf(mx, __shfl_xor_sync(~0u, mx, 4));
                const float mnew = fmaxf(mrun, mx);
                const float al = expsub(mrun, mnew);
                const float p0 = expsub(f0, mnew), p1 = expsub(f1, mnew), p2 = expsub(f2, mnew), p3 = expsub(f3, mnew);
                lrun = lrun * al + ((p0 + p1) + (p2 + p3));
                mrun = mnew;
                *reinterpret_cast<uint2*>(smem + M_P + head * 80 + kq * 8) = make_uint2(pack_bf16(p0, p1), pack_bf16(p2, p3));
                if (kq == 0) alpha[head] = al;
            }
            __syncthreads();
            {
                uint32_t pf[2][2][4];
#pragma unroll
                for (int i = 0; i < 2; i++)
#pragma unroll
                    for (int ks = 0; ks < 2; ks++)
                        ldsm4(pf[i][ks], sbase + M_P + (16 * i + (lane & 15)) * 80 + (16 * ks + 8 * (lane >> 4)) * 2);
#pragma unroll
                for (int i = 0; i < 2; i++) {
                    const float a0 = alpha[16 * i + g], a1 = alpha[16 * i + 8 + g];
#pragma unroll
                    for (int j = 0; j < 8; j++) { acc[i][j][0] *= a0; acc[i][j][1] *= a0; acc[i][j][2] *= a1; acc[i][j][3] *= a1; }
                }
#pragma unroll
                for (int j = 0; j < 8; j++) {
                    uint32_t bf[4];
                    ldsm4t(bf, slot + warp * 4096 + lane * 128 + ((j ^ (lane & 7)) * 16));
#pragma unroll
                    for (int i = 0; i < 2; i++) {
                        mma16816(acc[i][j], pf[i][0], bf[0], bf[1]);
                        mma16816(acc[i][j], pf[i][1], bf[2], bf[3]);
                    }
                }
            }
        }
        __syncthreads();
        if (tid == 0) b_issue(p, BS_PART - 1 + BD, bi, sbase, pol);
        lrun += __shfl_xor_sync(~0u, lrun, 1);
        lrun += __shfl_xor_sync(~0u, lrun, 2);
        lrun += __shfl_xor_sync(~0u, lrun, 4);
        if (kq == 0) g_bml[head * NBCTA + bi] = make_float2(mrun, lrun);
#pragma unroll
        for (int i = 0; i < 2; i++)
#pragma unroll
            for (int j = 0; j < 8; j++) {
                g_bpart[((16 * i + g) * NBCTA + bi) * 256 + warp * 32 + j * 4 + t] = make_float2(acc[i][j][0], acc[i][j][1]);
                g_bpart[((16 * i + 8 + g) * NBCTA + bi) * 256 + warp * 32 + j * 4 + t] = make_float2(acc[i][j][2], acc[i][j][3]);
            }
    }
    if (!CLU) {
#pragma unroll 1
        for (int i = tid; i < NH * 36; i += 256) g_outb[bi * NH * 36 + i] = make_uint4(0u, epoch, 0u, epoch);
    }
    b_exchange(&ctl[C_BBAR + 1][0], BS_PART, &g_bpart[bi * NBCTA * 256], sbase, pol);
    {
        float* omega = reinterpret_cast<float*>(smem + M_OMEGA);
        if (warp == 0) {
            __syncwarp();
            const uint2 ml = ld_relaxed8(&g_bml[bi * NBCTA + lane]);
            const float ms = __uint_as_float(ml.x);
            float m = ms;
            m = fmaxf(m, __shfl_xor_sync(~0u, m, 1));
            m = fmaxf(m, __shfl_xor_sync(~0u, m, 2));
            m = fmaxf(m, __shfl_xor_sync(~0u, m, 4));
            const float w = expsub(ms, m);
            float l = w * __uint_as_float(ml.y);
            l += __shfl_xor_sync(~0u, l, 1);
            l += __shfl_xor_sync(~0u, l, 2);
            l += __shfl_xor_sync(~0u, l, 4);
            omega[lane] = w / l;
        }
        __syncthreads();
        b_wait(BS_PART, sbase);
        b_wait(BS_PART + 1, sbase);
#pragma unroll 1
        for (int b = 0; b < 4; b++) {
            const float2* ps = reinterpret_cast<const float2*>(smem + ((BS_PART + (b >> 1)) % BRING) * SLOT) + (b & 1) * 2048 + tid;
            float c0 = 0.f, c1 = 0.f;
#pragma unroll
            for (int s = 0; s < 8; s++) {
                const float w = omega[b * 8 + s];
                const float2 v = ps[s * 256];
                c0 = fmaf(w, v.x, c0);
                c1 = fmaf(w, v.y, c1);
            }
            const uint32_t hi = pack_bf16(c0, c1);
            *reinterpret_cast<uint32_t*>(smem + M_CH + b * CP + tid * 4) = hi;
            *reinterpret_cast<uint32_t*>(smem + M_CL + b * CP + tid * 4) = pack_bf16(c0 - bf_lo(hi), c1 - bf_hi(hi));
        }
        __syncthreads();
        if (tid == 0) { b_issue(p, BS_PART + BD, bi, sbase, pol); b_issue(p, BS_PART + 1 + BD, bi, sbase, pol); }
    }
    b_gemm(p, sbase, BS_WUV, BS_END, 512, sbase + M_CH, sbase + M_CL, CP, bi, pol);
    TS(12);
    if (CLU) {
        if (warp < 4) {
            const unsigned short* c = reinterpret_cast<const unsigned short*>(smem + M_QB + warp * QP) + 16 * t + g;
            g_octx[(bi * 4 + warp) * 32 + lane] = make_float4(bf_lo(c[0]), bf_lo(c[8]), bf_lo(c[64]), bf_lo(c[72]));
        }
        __syncthreads();
        if (tid == 0) asm volatile("st.release.gpu.global.u32 [%0], %1;" ::"l"(&g_cdone[bi][0]), "r"(epoch + 1) : "memory");
        return;
    }
    if (tid == 0) {
#pragma unroll 1
        for (int i = 0; i < 4; i++) {
            mbar_expect_tx(sbase + M_BAR + i * 8, 36864);
            tma3d(sbase + i * 36864, &p.tm_wo, 0, bi * 128 + i * 32, 0, sbase + M_BAR + i * 8, pol);
        }
    }
    TS(8);
    {
        float acc[9][4];
#pragma unroll
        for (int j = 0; j < 9; j++) { acc[j][0] = acc[j][1] = acc[j][2] = acc[j][3] = 0.f; }
#pragma unroll 1
        for (int i = 0; i < 4; i++) {
            const uint32_t xo = sbase + M_QB + (g & 3) * QP + i * 64 + t * 4;
            const uint32_t a0[4] = {lds32(xo), 0u, lds32(xo + 16), 0u}, a1[4] = {lds32(xo + 32), 0u, lds32(xo + 48), 0u};
            mbar_wait(sbase + M_BAR + i * 8, 0);
#pragma unroll
            for (int j = 0; j < 9; j++) {
                const int nt = warp * 9 + j;
                uint32_t w[4];
                ldsm4t(w, sbase + i * 36864 + (nt >> 3) * 4096 + lane * 128 + (((nt & 7) ^ (lane & 7)) * 16));
                mma16816(acc[j], a0, w[0], w[1]);
                mma16816(acc[j], a1, w[2], w[3]);
            }
        }
        if (g < 4) {
#pragma unroll
            for (int j = 0; j < 9; j++) {
                const int c2 = (warp * 9 + j) * 4 + t;
                st_tagged2(&g_outb[((c2 / 9) * NH + bi) * 36 + g * 9 + c2 % 9], acc[j][0], acc[j][1], epoch + 1);
            }
        }
    }
    TS(9);
    {
        const uint4* src = g_outb + (bi * NH + (tid >> 3)) * 36 + (tid & 7);
        float2* part = reinterpret_cast<float2*>(red);
        unsigned n = 0;
        while (true) {
            ulonglong2 v[5];
            bool ok = true;
#pragma unroll
            for (int i = 0; i < 5; i++)
                if (i < 4 || (tid & 7) < 4) v[i] = ld_tagged2(src + i * 8);
#pragma unroll
            for (int i = 0; i < 5; i++)
                if (i < 4 || (tid & 7) < 4) {
                    ok = ok && (unsigned)(v[i].x >> 32) == epoch + 1 && (unsigned)(v[i].y >> 32) == epoch + 1;
                    part[(tid >> 3) * 36 + (tid & 7) + i * 8] = make_float2(__uint_as_float((unsigned)v[i].x), __uint_as_float((unsigned)v[i].y));
                }
            if (ok) break;
            __nanosleep(400);
            if (++n > SPIN_LIMIT) __trap();
        }
        __syncthreads();
        if (tid < 36) {
            float s0 = 0.f, s1 = 0.f;
#pragma unroll 8
            for (int h = 0; h < NH; h++) { const float2 v = part[h * 36 + tid]; s0 += v.x; s1 += v.y; }
            *reinterpret_cast<uint32_t*>(p.out + (tid / 9) * 2 * DM + DM + bi * 18 + (tid % 9) * 2) = pack_bf16(s0, s1);
        }
    }
    TS(10);
}

template <bool CLU>
__global__ void __launch_bounds__(256, 1) fused_decode_kernel(const __grid_constant__ Params p) {
    extern __shared__ __align__(1024) char smem_raw[];
    const uint32_t sbase = (smem_u32(smem_raw) + 1023u) & ~1023u;
    if (CLU && threadIdx.x < 32 && blockIdx.x >= NBCTA) {
        const unsigned u0 = blockIdx.x - NBCTA, u1 = u0 + 8 * MINCL - NBCTA;
        asm volatile("{\n.reg .pred p;\nelect.sync _|p, 0xffffffff;\n"
                     "@p mbarrier.init.shared::cta.b64 [%0], 1;\n"
                     "@p mbarrier.init.shared::cta.b64 [%0+8], 1;\n"
                     "@p fence.mbarrier_init.release.cluster;\n"
                     "@p mbarrier.arrive.expect_tx.shared::cta.b64 _, [%0], 32768;\n"
                     "@p cp.async.bulk.shared::cluster.global.mbarrier::complete_tx::bytes.L2::cache_hint [%1], [%2], 32768, [%0], %4;\n"
                     "@p mbarrier.arrive.expect_tx.shared::cta.b64 _, [%0+8], 32768;\n"
                     "@p cp.async.bulk.shared::cluster.global.mbarrier::complete_tx::bytes.L2::cache_hint [%1+32768], [%3], 32768, [%0+8], %4;\n}"
                     ::"r"(sbase + M_BAR), "r"(sbase), "l"(reinterpret_cast<const char*>(p.kc) + (size_t)u0 * TILE_BYTES),
                       "l"(reinterpret_cast<const char*>(p.kc) + (size_t)((u1 >> 7) * 1024 + (u1 & 127)) * TILE_BYTES), "l"(0x12F0000000000000ull) : "memory");
    }
    char* smem = smem_raw + (sbase - smem_u32(smem_raw));
    const int tid = threadIdx.x, warp = tid >> 5, lane = tid & 31;
    const int blk = blockIdx.x;
    const bool isB = CLU ? blk < NBCTA : (blk & 3) == 0 && (blk >> 2) < NBCTA;
    const int bi = CLU ? blk : blk >> 2;
    const int nb = CLU ? blk - NBCTA : blk - min(NBCTA, (blk + 3) >> 2);
    const int nnb = gridDim.x - NBCTA;
    const int nstatic = nnb * (NW + XW);
    uint64_t pol;
    asm volatile("createpolicy.fractional.L2::evict_first.b64 %0, 1.0;" : "=l"(pol));
    const uint32_t wbar = sbase + M_BAR + warp * 8, wslot = sbase + warp * SLOT;
    const int u0 = warp * nnb + nb;
    const bool hold = ((blk >> 2) >> KMIN << KMIN) * 4 * UPP < nstatic;
    const uint32_t jbar = sbase + M_BAR + (NSLOT + BRING) * 8;
    if (warp == 7) {
        if (lane == 0 && blk < 128) {
            mbar_init(jbar, 1);
            asm volatile("fence.mbarrier_init.release.cluster;" ::: "memory");
            uint64_t poln;
            asm volatile("createpolicy.fractional.L2::evict_normal.b64 %0, 1.0;" : "=l"(poln));
            mbar_expect_tx(jbar, 36864 + 4 * 1152);
            tma3d(sbase + J0W, &p.tm_j0, blk * 32, 0, 0, jbar, poln);
            bulk_load(sbase + M_XA, p.xa, 4608, jbar, poln);
        }
        if (lane < 8) reinterpret_cast<unsigned*>(smem + M_HELP)[lane] = 0;
        __syncwarp();
        if (!isB) asm volatile("bar.arrive 2, %0;" ::"n"(32 * (NW + XW + 1)) : "memory");
    }
    if (warp < 4 && lane == 0 && (!CLU || isB || warp >= 2)) {
        mbar_init(wbar, 1);

        asm volatile("fence.mbarrier_init.release.cluster;" ::: "memory");
        if (warp < NEARLY && !isB && !hold) {
            mbar_expect_tx(wbar, TILE_BYTES);
            bulk_load(wslot, block_src(p.kc, unit_block<CLU>(u0)), TILE_BYTES, wbar, pol);
        }
    }
    unsigned epoch = 0;
    if (lane == 0) epoch = ld_relaxed4(&g_epoch);
    TS(0);
    if (CLU) {
        if (warp == 6) {
            if (lane < 8 + 8 * PH && lane != 1) mbar_init(sbase + F_BAR + lane * 8, 1);
            if ((lane >> 1) == 1) mbar_expect_tx(sbase + F_BAR + lane * 8, 1024);
            asm volatile("fence.mbarrier_init.release.cluster;" ::: "memory");
        }
        asm volatile("barrier.cluster.arrive.relaxed.aligned;" ::: "memory");
    }
    if ((warp >> 1) == 2 && blk < 128) st_relaxed64(&g_qll[((tid - 128) >> 4) * 2048 + blk * 16 + (tid & 15)], 0ull);
    if (isB || warp >= NW + XW) epoch = __shfl_sync(~0u, epoch, 0);
    if (isB && warp == 3) asm volatile("bar.sync 1, 160;" ::: "memory");
    if (isB && tid == 96) {
#pragma unroll 1
        for (int i = 0; i < BRING; i++) mbar_init(sbase + M_BAR + (NSLOT + i) * 8, 1);
        asm volatile("fence.mbarrier_init.release.cluster;" ::: "memory");
        if (hold) { unsigned n = 0; while (ld_acquire_cta_shared(sbase + M_HELP + 24) < 2) { if (++n > (SPIN_LIMIT << 4)) __trap(); } }
#pragma unroll 1
        for (int b = 0; b < 4; b++) bulk_load(sbase + M_XB + b * XP, p.xb + b * DM, 1152, sbase + M_BAR + NSLOT * 8, pol);
#pragma unroll 1
        for (int n = 0; n < BD; n++) b_issue(p, n, bi, sbase, pol);
    }
    if (warp >= 4 && blk < 128) {
        const int g = lane >> 2, t = lane & 3, j = tid - 128;
        asm volatile("bar.sync 1, %0;" ::"r"(isB ? 160 : 128) : "memory");
#pragma unroll 1
        for (int sl = blk, ph = 0;; sl += 128 - gridDim.x, ph = 1) {
        mbar_wait(jbar, ph);
        TS(13);
        float acc[4][4];
#pragma unroll
        for (int i = 0; i < 16; i++) acc[i >> 2][i & 3] = 0.f;
        const uint32_t wa = sbase + J0W + ((warp - 4) * 144 + (lane & 15)) * 64;
        const uint32_t sw = (lane >> 1) & 3, xa = sbase + M_XA + (g & 3) * 1152 + (warp - 4) * 288 + t * 4;
#pragma unroll 3
        for (int s = 0; s < 9; s++) {
            const uint32_t a[4] = {lds32(xa + s * 32), 0u, lds32(xa + s * 32 + 16), 0u};
            uint32_t w0[4], w1[4];
            ldsm4t(w0, wa + s * 1024 + (((lane >> 4) ^ sw) * 16));
            ldsm4t(w1, wa + s * 1024 + (((2 + (lane >> 4)) ^ sw) * 16));
            mma16816(acc[0], a, w0[0], w0[1]);
            mma16816(acc[1], a, w0[2], w0[3]);
            mma16816(acc[2], a, w1[0], w1[1]);
            mma16816(acc[3], a, w1[2], w1[3]);
        }
        float2* j0 = reinterpret_cast<float2*>(smem + M_J0);
        if (g < 4) {
#pragma unroll
            for (int i = 0; i < 4; i++) j0[(warp - 4) * 64 + g * 16 + i * 4 + t] = make_float2(acc[i][0], acc[i][1]);
        }
        asm volatile("bar.sync 1, 128;" ::: "memory");
        const bool again = sl == blk && blk + 128 - (int)gridDim.x >= (int)gridDim.x;
        if (again && tid == 224) {
            mbar_expect_tx(jbar, 36864);
            tma3d(sbase + J0W, &p.tm_j0, (blk + 128 - gridDim.x) * 32, 0, 0, jbar, pol);
        }
        if (warp < 6) {
            const float2 v0 = j0[j], v1 = j0[64 + j], v2 = j0[128 + j], v3 = j0[192 + j];
            st_relaxed64(&g_qll[(j >> 4) * 2048 + sl * 16 + (j & 15)],
                         (unsigned long long)pack_bf16((v0.x + v1.x) + (v2.x + v3.x), (v0.y + v1.y) + (v2.y + v3.y)) |
                             ((unsigned long long)(epoch + 1) << 32));
            __syncwarp();
            if (lane == 0) asm volatile("red.relaxed.cta.shared::cta.add.u32 [%0], 1;" ::"r"(sbase + M_HELP + 24) : "memory");
        } else if (warp == 7) {
            if (blk < C_LINES) g_ctl[(epoch & 1) ^ 1][blk][lane] = 0;
        }
        TS(1);
        if (!again) break;
        asm volatile("bar.sync 1, 128;" ::: "memory");
        }
    }
    if (isB) {
        b_chain<CLU>(p, smem, sbase, bi, epoch, pol);
        if (CLU) b_final(p, sbase, blk, epoch, pol);
        return;
    }
    const int sl = nb >> 3, rank = blk & 7;
    if (warp < NW + XW) {
        a_worker<CLU>(p, u0, warp >= NW + ((nb & 3) < (CLU ? X3C : X3) ? 1 : 0), warp < NEARLY && !hold, hold, nstatic, wslot, wbar, sbase + M_HELP,
                      epoch, pol);
        if (CLU && warp == 3 && sl < 10) {
            epoch = __shfl_sync(~0u, epoch, 0);
            unsigned n = 0;
            while (ld_acquire_cta_shared(sbase + M_HELP + 12) == 0) { __nanosleep(1000); if (++n > SPIN_LIMIT) __trap(); }
            asm volatile("barrier.cluster.wait.acquire.aligned;" ::: "memory");
            f_collect((sl < 9 ? g_vdone : g_cdone) + 4 * rank, sl < 9 ? 4 * UPP : epoch + 1, (sl < 9 ? g_oacc : g_octx) + 4 * rank * 128,
                      sl < 9 && rank == 7, sbase);
            mbar_wait(sbase + F_BAR, 0);
            f_receive(p.out + (sl < 9 ? sl * 64 : DM + 512) + rank * 8, 0, sbase);
        }
        return;
    }
    if (warp == 7) {
#pragma unroll 1
        for (int i = nb; i < 4 * NH; i += nnb) g_oacc[i * 32 + lane] = make_float4(0.f, 0.f, 0.f, 0.f);
        if (nb < NREP * NH) g_vdone[nb][lane] = 0;
        __syncwarp();
        k_helper(sbase + M_HELP, epoch);
        if (nb == 0 && lane == 0) g_epoch = epoch + 1;
        __syncwarp();
    }
    if (CLU) {
        if (sl < 10) {
            const CUtensorMap* tm = sl < 9 ? &p.tm_fa : &p.tm_fb;
            asm volatile("barrier.cluster.wait.acquire.aligned;" ::: "memory");
            f_project(tm, min(sl, 8), rank, 0, warp & 3, A0 + (warp & 3) * AJ + rank * AR - max(0, (warp & 3) * 8 + rank - AK) * AC, AJ / PH, epoch + 1, sbase, pol);
        }
    } else if (warp == 6 && nb < NFIN) {
        finisher(p, sbase, nb);
        TS(4);
    } else if (warp != 7 && warp >= 6 - NPOLL && nb < NFIN) {
        v_poller(sbase, nb, warp - (6 - NPOLL));
    }
}

}

typedef CUresult (*EncodeFn)(CUtensorMap*, CUtensorMapDataType, cuuint32_t, void*, const cuuint64_t*, const cuuint64_t*,
                             const cuuint32_t*, const cuuint32_t*, CUtensorMapInterleave, CUtensorMapSwizzle,
                             CUtensorMapL2promotion, CUtensorMapFloatOOBfill);

extern "C" void kernel_launch(void* const* d_in, const int* in_sizes, int n_in, void* d_out, int out_size) {
    (void)in_sizes; (void)n_in; (void)out_size;
    static int nsm = 0, ncl = 0;
    static EncodeFn encode = nullptr;
    cudaLaunchConfig_t cfg = {};
    cudaLaunchAttribute at[1];
    at[0].id = cudaLaunchAttributeClusterDimension;
    at[0].val.clusterDim.x = 8; at[0].val.clusterDim.y = 1; at[0].val.clusterDim.z = 1;
    cfg.blockDim = dim3(256); cfg.dynamicSmemBytes = SMEM_BYTES; cfg.stream = cudaStreamPerThread; cfg.attrs = at; cfg.numAttrs = 1;
    if (nsm == 0) {
        int dev = 0;
        cudaGetDevice(&dev);
        cudaDeviceGetAttribute(&nsm, cudaDevAttrMultiProcessorCount, dev);
        cudaFuncSetAttribute(fused_decode_kernel<false>, cudaFuncAttributeMaxDynamicSharedMemorySize, SMEM_BYTES);
        cudaFuncSetAttribute(fused_decode_kernel<true>, cudaFuncAttributeMaxDynamicSharedMemorySize, SMEM_BYTES);
        cfg.gridDim = dim3(128);
        if (cudaOccupancyMaxActiveClusters(&ncl, fused_decode_kernel<true>, &cfg) != cudaSuccess) { ncl = 0; (void)cudaGetLastError(); }
        if (ncl > MINCL) ncl = MINCL;
        void* fn = nullptr;
        cudaDriverEntryPointQueryResult qr;
        cudaGetDriverEntryPoint("cuTensorMapEncodeTiled", &fn, cudaEnableDefault, &qr);
        encode = (EncodeFn)fn;
    }
    Params p;
    auto panels = [&](CUtensorMap* tm, void* ptr, int rows, int cols, int box_rows, int box_panels,
                      CUtensorMapL2promotion promo = CU_TENSOR_MAP_L2_PROMOTION_L2_256B) {
        const cuuint64_t gd[3] = {64, (cuuint64_t)rows, (cuuint64_t)(cols / 64)}, gs[2] = {(cuuint64_t)cols * 2, 128};
        const cuuint32_t box[3] = {64, (cuuint32_t)box_rows, (cuuint32_t)box_panels}, es[3] = {1, 1, 1};
        encode(tm, CU_TENSOR_MAP_DATA_TYPE_BFLOAT16, 3, ptr, gd, gs, box, es, CU_TENSOR_MAP_INTERLEAVE_NONE,
               CU_TENSOR_MAP_SWIZZLE_128B, promo, CU_TENSOR_MAP_FLOAT_OOB_FILL_NONE);
    };
    panels(&p.tm_wq, d_in[7], DM, 4096, 128, 2);
    panels(&p.tm_wuk, d_in[8], 512, 4096, 128, 2);
    panels(&p.tm_wuv, d_in[9], 512, 4096, 128, 2);
    panels(&p.tm_wo, d_in[10], 4096, DM, 32, 9);
    panels(&p.tm_ckv, d_in[6], 4 * SK, 512, 32, 8);
    panels(&p.tm_fa, d_in[4], 4096, DM, 128 / PH, 1, CU_TENSOR_MAP_L2_PROMOTION_L2_128B);
    panels(&p.tm_fb, d_in[10], 4096, DM, 128 / PH, 1, CU_TENSOR_MAP_L2_PROMOTION_L2_128B);
    {
        const cuuint64_t gd[3] = {4096, 192, 3}, gs[2] = {8192, 192 * 8192};
        const cuuint32_t box[3] = {32, 192, 3}, es[3] = {1, 1, 1};
        encode(&p.tm_j0, CU_TENSOR_MAP_DATA_TYPE_BFLOAT16, 3, d_in[3], gd, gs, box, es, CU_TENSOR_MAP_INTERLEAVE_NONE,
               CU_TENSOR_MAP_SWIZZLE_64B, CU_TENSOR_MAP_L2_PROMOTION_L2_128B, CU_TENSOR_MAP_FLOAT_OOB_FILL_NONE);
    }
    p.xa = (const __nv_bfloat16*)d_in[0];
    p.kc = (const __nv_bfloat16*)d_in[1];
    p.vc = (const __nv_bfloat16*)d_in[2];
    p.wo = (const __nv_bfloat16*)d_in[4];
    p.xb = (const __nv_bfloat16*)d_in[5];
    p.out = (__nv_bfloat16*)d_out;
    if (ncl >= MINCL) {
        cfg.gridDim = dim3(8 * ncl);
        cudaLaunchKernelEx(&cfg, fused_decode_kernel<true>, p);
    } else {
        fused_decode_kernel<false><<<nsm, 256, SMEM_BYTES, cudaStreamPerThread>>>(p);
    }
}
```

```cpp
#include <cuda_runtime.h>
#include <cuda.h>
#include <cuda_bf16.h>
#include <stdint.h>

namespace {

constexpr int NH = 32, SK = 4096, DM = 576;
constexpr int KEYS = 128;
constexpr int UPP = SK / KEYS;
constexpr int NUK = 4 * NH * UPP;
constexpr int TILE_BYTES = KEYS * 256;
#define NWORK 2
constexpr int NW = NWORK;
constexpr int NBCTA = 32;
constexpr int MINCL = 15;
constexpr int NFIN = 72;
constexpr int SLOT = 32768;
constexpr int NSLOT = 6;
constexpr int BRING = 5;
constexpr int J0W = 5 * SLOT;
constexpr int MISC = NSLOT * SLOT + 4096;
constexpr int XP = 1168, CP = 1040, QP = 272;
constexpr int M_XA = MISC;
constexpr int M_XB = M_XA + 4 * XP;
constexpr int M_CH = M_XB + 4 * XP;
constexpr int M_CL = M_CH + 4 * CP;
constexpr int M_QB = M_CL + 4 * CP;
constexpr int M_QA = M_CH;
constexpr int M_J0 = M_QB + 4 * QP;
constexpr int M_P = M_J0 + 2048;
constexpr int M_ALPHA = M_P + 2560;
constexpr int M_OMEGA = M_ALPHA + 128;
constexpr int M_BAR = M_OMEGA + 128;
constexpr int M_HELP = M_BAR + 128;
#define PH 1
constexpr int F_W = 4 * SLOT;
constexpr int F_BF = (M_HELP + 128 + 255) / 256 * 256;
constexpr int F_RX = F_BF + 4096;
constexpr int F_BAR = F_RX + 2048;
constexpr int SMEM_BYTES = F_BAR + 64 + 64 * PH + 1024;
static_assert(SMEM_BYTES <= 232448 && M_BAR % 8 == 0 && M_QA % 16 == 0 && M_P % 16 == 0, "smem layout");
#define XW 2
#define X3 1
#define X3C 3
#define NEARLY 3
#define BD 5
#define FPF 3
#define FSLEEP 800
#define VS0 24
#define EARLY 100
#define ELOG 5
#define TPU 159
#define A0 3000
#define AJ 700
#define AR (AJ / 8 / PH)
#define CM2 10
#define AK 24
#define AC 0
#define BK 24
#define BC 0
#define B0 2500
#define BJ 700
#define BS (300 / PH)
#define BR (BJ / 8 / PH)
#define NPOLL 2
#define PGAP 200
static_assert(X3C <= 3 && NW == 2, "warp 2 of rank 7 is free");
static_assert(NW + XW <= 4 && NEARLY <= NW + XW && BD <= BRING, "slots 4 and 5 hold the finisher weights");
#define KMAX 4
#define VMAX 4
constexpr int KMIN = 2, VMIN = 0;
constexpr float SCALE = 0.08838834764831845f;
constexpr float LOG2E = 1.4426950408889634f;
constexpr unsigned SPIN_LIMIT = 1u << 24;

#define NREP 2
#define NREPC 1
constexpr int C_QUEUE = 0, C_KDONE = 1, C_BBAR = 3, C_LINES = 5;

struct Params {
    const __nv_bfloat16 *kc, *xa, *vc, *wo, *xb;
    __nv_bfloat16* out;
    CUtensorMap tm_j0;
    CUtensorMap tm_wq, tm_wuk, tm_ckv, tm_wuv, tm_wo;
    CUtensorMap tm_fa, tm_fb;
};

__device__ unsigned g_epoch;
__device__ unsigned g_ctl[2][C_LINES][32];
__device__ uint2 g_qll[4 * 2048];
__device__ uint2 g_scores[128 * SK / 4];
__device__ float2 g_stats[128 * UPP];
__device__ float4 g_oacc[128 * 32];
__device__ unsigned g_vdone[NREP * NH][32];
__device__ float4 g_octx[128 * 32];
__device__ unsigned g_cdone[NH][32];
__device__ unsigned long long g_dry[16][16];
__device__ uint4 g_qabs[4 * 8 * 4 * 4 * 32];
__device__ float2 g_bpart[NBCTA * NH * 256];
__device__ float2 g_bml[NBCTA * NH];
__device__ uint4 g_outb[NBCTA * NH * 36];

#define TS(i)
#define TSV(i, v)
#define LAND(i)
#define CLK(x)
#define ACC(a, x, y)

__device__ __forceinline__ uint32_t smem_u32(const void* p) { return (uint32_t)__cvta_generic_to_shared(p); }
__device__ __forceinline__ void mbar_init(uint32_t bar, uint32_t cnt) {
    asm volatile("mbarrier.init.shared::cta.b64 [%0], %1;" ::"r"(bar), "r"(cnt) : "memory");
}
__device__ __forceinline__ void mbar_expect_tx(uint32_t bar, uint32_t bytes) {
    asm volatile("mbarrier.arrive.expect_tx.shared::cta.b64 _, [%0], %1;" ::"r"(bar), "r"(bytes) : "memory");
}
__device__ __forceinline__ bool mbar_try(uint32_t bar, uint32_t parity) {
    uint32_t ok;
    asm volatile("{\n.reg .pred p;\nmbarrier.try_wait.parity.shared::cta.b64 p, [%1], %2;\nselp.u32 %0, 1, 0, p;\n}\n"
                 : "=r"(ok) : "r"(bar), "r"(parity) : "memory");
    return ok;
}
__device__ __forceinline__ void mbar_wait(uint32_t bar, uint32_t parity) {
    unsigned n = 0;
    while (!mbar_try(bar, parity)) { if (++n > SPIN_LIMIT) __trap(); }
}
__device__ __forceinline__ void mbar_spin(uint32_t bar) {
    asm volatile("{\n.reg .pred p;\n.reg .u32 n;\nmov.u32 n, 0;\nSPIN:\nmbarrier.test_wait.parity.shared::cta.b64 p, [%0], 0;\n@p bra.uni DONE;\n"
                 "add.u32 n, n, 1;\nsetp.lt.u32 p, n, 0x4000000;\n@p bra.uni SPIN;\ntrap;\nDONE:\n}" ::"r"(bar) : "memory");
}
__device__ __forceinline__ void bulk_load(uint32_t dst, const void* src, uint32_t bytes, uint32_t bar, uint64_t pol) {
    asm volatile("cp.async.bulk.shared::cluster.global.mbarrier::complete_tx::bytes.L2::cache_hint [%0], [%1], %2, [%3], %4;"
                 ::"r"(dst), "l"(src), "r"(bytes), "r"(bar), "l"(pol) : "memory");
}
__device__ __forceinline__ void tma3d(uint32_t dst, const CUtensorMap* tm, int c0, int c1, int c2, uint32_t bar, uint64_t pol) {
    asm volatile("cp.async.bulk.tensor.3d.shared::cluster.global.mbarrier::complete_tx::bytes.L2::cache_hint [%0], [%1, {%3,%4,%5}], [%2], %6;"
                 ::"r"(dst), "l"(tm), "r"(bar), "r"(c0), "r"(c1), "r"(c2), "l"(pol) : "memory");
}
__device__ __forceinline__ void l2_prefetch(const void* src, uint32_t bytes) {
    asm volatile("cp.async.bulk.prefetch.L2.global [%0], %1;" ::"l"(src), "r"(bytes) : "memory");
}
__device__ __forceinline__ void ldsm4(uint32_t (&r)[4], uint32_t addr) {
    asm volatile("ldmatrix.sync.aligned.m8n8.x4.shared.b16 {%0,%1,%2,%3}, [%4];"
                 : "=r"(r[0]), "=r"(r[1]), "=r"(r[2]), "=r"(r[3]) : "r"(addr));
}
__device__ __forceinline__ void ldsm4t(uint32_t (&r)[4], uint32_t addr) {
    asm volatile("ldmatrix.sync.aligned.m8n8.x4.trans.shared.b16 {%0,%1,%2,%3}, [%4];"
                 : "=r"(r[0]), "=r"(r[1]), "=r"(r[2]), "=r"(r[3]) : "r"(addr));
}
__device__ __forceinline__ void mma16816(float (&d)[4], const uint32_t (&a)[4], uint32_t b0, uint32_t b1) {
    asm("mma.sync.aligned.m16n8k16.row.col.f32.bf16.bf16.f32 {%0,%1,%2,%3}, {%4,%5,%6,%7}, {%8,%9}, {%0,%1,%2,%3};"
        : "+f"(d[0]), "+f"(d[1]), "+f"(d[2]), "+f"(d[3])
        : "r"(a[0]), "r"(a[1]), "r"(a[2]), "r"(a[3]), "r"(b0), "r"(b1));
}
__device__ __forceinline__ uint32_t lds32(uint32_t a) {
    uint32_t v;
    asm volatile("ld.shared.u32 %0, [%1];" : "=r"(v) : "r"(a));
    return v;
}
__device__ __forceinline__ unsigned ld_acquire(const unsigned* p) {
    unsigned v;
    asm volatile("ld.acquire.gpu.global.u32 %0, [%1];" : "=r"(v) : "l"(p) : "memory");
    return v;
}
__device__ __forceinline__ uint2 ld_relaxed8(const void* p) {
    uint2 v;
    asm volatile("ld.relaxed.gpu.global.v2.u32 {%0,%1}, [%2];" : "=r"(v.x), "=r"(v.y) : "l"(p) : "memory");
    return v;
}
__device__ __forceinline__ unsigned ld_relaxed4(const void* p) {
    unsigned v;
    asm volatile("ld.relaxed.gpu.global.u32 %0, [%1];" : "=r"(v) : "l"(p) : "memory");
    return v;
}
__device__ __forceinline__ unsigned atom_inc(unsigned* p) {
    unsigned v;
    asm volatile("atom.relaxed.gpu.global.inc.u32 %0, [%1], 0x7fffffff;" : "=r"(v) : "l"(p) : "memory");
    return v;
}
__device__ __forceinline__ unsigned long long ld_relaxed64(const void* p) {
    unsigned long long v;
    asm volatile("ld.relaxed.gpu.global.u64 %0, [%1];" : "=l"(v) : "l"(p) : "memory");
    return v;
}
__device__ __forceinline__ void st_relaxed64(void* p, unsigned long long v) {
    asm volatile("st.relaxed.gpu.global.u64 [%0], %1;" ::"l"(p), "l"(v) : "memory");
}
__device__ __forceinline__ float4 ld_relaxed16(const void* p) {
    float4 v;
    asm volatile("ld.relaxed.gpu.global.v4.f32 {%0,%1,%2,%3}, [%4];" : "=f"(v.x), "=f"(v.y), "=f"(v.z), "=f"(v.w) : "l"(p) : "memory");
    return v;
}
__device__ __forceinline__ uint32_t mapa(uint32_t a, uint32_t rank) {
    uint32_t r;
    asm("mapa.shared::cluster.u32 %0, %1, %2;" : "=r"(r) : "r"(a), "r"(rank));
    return r;
}
__device__ __forceinline__ uint32_t time_ns() { uint32_t t; asm volatile("mov.u32 %0, %globaltimer_lo;" : "=r"(t)); return t; }
__device__ __forceinline__ void fence_gpu() { asm volatile("fence.acq_rel.gpu;" ::: "memory"); }
__device__ __forceinline__ void red_add_u32(unsigned* p, unsigned v) {
    asm volatile("red.relaxed.gpu.global.add.u32 [%0], %1;" ::"l"(p), "r"(v) : "memory");
}
__device__ __forceinline__ void st_tagged2(void* p, float a, float b, unsigned tag) {
    const unsigned long long hi = (unsigned long long)tag << 32;
    asm volatile("st.relaxed.gpu.global.v2.b64 [%0], {%1,%2};" ::"l"(p), "l"(hi | __float_as_uint(a)), "l"(hi | __float_as_uint(b)) : "memory");
}
__device__ __forceinline__ ulonglong2 ld_tagged2(const void* p) {
    ulonglong2 v;
    asm volatile("ld.relaxed.gpu.global.v2.b64 {%0,%1}, [%2];" : "=l"(v.x), "=l"(v.y) : "l"(p) : "memory");
    return v;
}
__device__ __forceinline__ float4 atom_add_f4(void* p, float a, float b, float c, float d) {
    float4 r;
    asm volatile("atom.relaxed.gpu.global.add.v4.f32 {%0,%1,%2,%3}, [%4], {%5,%6,%7,%8};"
                 : "=f"(r.x), "=f"(r.y), "=f"(r.z), "=f"(r.w) : "l"(p), "f"(a), "f"(b), "f"(c), "f"(d) : "memory");
    return r;
}
__device__ __forceinline__ void red_release_cta_shared(uint32_t a, unsigned v) {
    asm volatile("red.release.cta.shared::cta.add.u32 [%0], %1;" ::"r"(a), "r"(v) : "memory");
}
__device__ __forceinline__ unsigned ld_acquire_cta_shared(uint32_t a) {
    unsigned v;
    asm volatile("ld.acquire.cta.shared::cta.u32 %0, [%1];" : "=r"(v) : "r"(a) : "memory");
    return v;
}
__device__ __forceinline__ void st_release_cta_shared(uint32_t a, unsigned v) {
    asm volatile("st.release.cta.shared::cta.u32 [%0], %1;" ::"r"(a), "r"(v) : "memory");
}
__device__ __forceinline__ void wait_count(const unsigned* p, unsigned target) {
    unsigned n = 0;
    while (ld_acquire(p) < target) { if (++n > SPIN_LIMIT) __trap(); }
}
__device__ __forceinline__ uint32_t pack_bf16(float lo, float hi) {
    uint32_t r;
    asm("cvt.rn.bf16x2.f32 %0, %1, %2;" : "=r"(r) : "f"(hi), "f"(lo));
    return r;
}
__device__ __forceinline__ float bf_lo(uint32_t v) { return __uint_as_float(v << 16); }
__device__ __forceinline__ float bf_hi(uint32_t v) { return __uint_as_float(v & 0xffff0000u); }
__device__ __forceinline__ float ex2(float x) { float y; asm("ex2.approx.ftz.f32 %0, %1;" : "=f"(y) : "f"(x)); return y; }
__device__ __forceinline__ float expsub(float a, float b) { return ex2((a - b) * LOG2E); }
__device__ __forceinline__ float warp_max(float v) {
#pragma unroll
    for (int m = 16; m; m >>= 1) v = fmaxf(v, __shfl_xor_sync(~0u, v, m));
    return v;
}
__device__ __forceinline__ float warp_sum(float v) {
#pragma unroll
    for (int m = 16; m; m >>= 1) v += __shfl_xor_sync(~0u, v, m);
    return v;
}
template <bool CLU>
__device__ __forceinline__ unsigned unit_block(int u) {
    const unsigned x = ((unsigned)u & (NUK - 1)) / UPP;
    const int lg = u < NUK ? min(KMAX, max(KMIN, 29 - __clz(x | 1))) : (CLU && (int)x >= 4 * VS0 ? 0 : min(VMAX, max(VMIN, 29 - __clz((127 - x) | 1))));
    const unsigned r = x & ((4u << lg) - 1);
    return ((x - r + (r & ((1u << lg) - 1)) * 4 + (r >> lg)) * UPP) | ((unsigned)u & (UPP - 1));
}
__device__ __forceinline__ const char* block_src(const void* base, unsigned blk) {
    const unsigned po = blk / UPP;
    return reinterpret_cast<const char*>(base) + (size_t)(((po & 3) * NH + (po >> 2)) * UPP + blk % UPP) * TILE_BYTES;
}

template <bool CLU>
__device__ __forceinline__ void a_worker(const Params& p, int un, bool once, bool pre, bool hold, int nstatic, uint32_t slot, uint32_t bar,
                                         uint32_t help, unsigned epoch, uint64_t pol) {
    constexpr int NU = 2 * NUK, NR = CLU ? NREPC : NREP;
    const int lane = threadIdx.x & 31, g = lane >> 2, t = lane & 3;
    const int li = lane & 7;
    uint32_t kaddr[4], vaddr[8];
    {
        const int e = (lane >> 3) & 1, kk = lane >> 4;
#pragma unroll
        for (int s = 0; s < 4; s++) kaddr[s] = slot + (16 * li + e) * 256 + ((2 * s + kk + li) & 7) * 16;
        const int vrow = 4 * (li >> 1) + (li & 1) + 2 * kk;
#pragma unroll
        for (int c = 0; c < 8; c++) vaddr[c] = slot + vrow * 256 + e * 128 + ((c + li) & 7) * 16;
#pragma unroll
        for (int c = 0; c < 8; c++) asm volatile("" : "+r"(vaddr[c]));
    }
    const uint32_t vmask = (g >> 1) != t ? 0u : ((g & 1) ? 0xffff0000u : 0xffffu);
    int kseen = -1;
    unsigned long long H0 = 0, H1 = 0;
    auto header = [&](int v, unsigned vb) {
        if (v >= NU) return;
        const void *a0, *a1;
        if (v < NUK) {
            const unsigned po = vb / UPP;
            a0 = g_qll + (po & 3) * 2048 + (po >> 2) * 64 + lane;
            a1 = reinterpret_cast<const uint2*>(a0) + 32;
        } else {
            const int half = vb / (NUK / 2);
            if (half > kseen) {
                unsigned n = 0;
                while (ld_acquire_cta_shared(help + 12 + 4 * half) == 0) { if (++n > (SPIN_LIMIT << 4)) __trap(); }
                kseen = half;
            }
            a0 = &g_scores[vb * (KEYS / 4) + lane];
            a1 = &g_stats[(vb / UPP) * UPP + lane];
        }
        H0 = ld_relaxed64(a0);
        H1 = ld_relaxed64(a1);
    };
    asm volatile("bar.sync 2, %0;" ::"n"(32 * (NW + XW + 1)) : "memory");
    epoch = __shfl_sync(~0u, epoch, 0);
    if (hold) { unsigned n = 0; while (ld_acquire_cta_shared(help + 24) < 2) { if (++n > (SPIN_LIMIT << 4)) __trap(); } }
    unsigned (*ctl)[32] = g_ctl[epoch & 1];
    const unsigned tag = epoch + 1;
    unsigned nxt = once ? NU : 0;
    int u = -1;
    unsigned bu = 0, bn = unit_block<CLU>(un);
    bool have = false;
    uint32_t phase = 0;
    unsigned kpend = 0;
    const unsigned zero = gridDim.x >> 24;
    uint32_t Q[16];
    float4 oret = make_float4(0.f, 0.f, 0.f, 0.f);
    while (true) {
        const char* nsrc = block_src(un < NUK ? p.kc : p.vc, bn);
        float4* odst = &g_oacc[(bu / UPP) * 32 + lane];
        unsigned* vdst = &g_vdone[(lane & (NR - 1)) * NH + bu / (4 * UPP)][0];
        float d[8][4];
        CLK(c1);
        asm volatile("" : "+l"(odst));
        if (u >= NUK) {
#pragma unroll
            for (int j = 0; j < 8; j++) { d[j][0] = d[j][1] = d[j][2] = d[j][3] = 0.f; }
            mbar_wait(bar, phase);
            LAND(NUK + bu);
            uint32_t a[2][8][4];
#pragma unroll
            for (int c = 0; c < 8; c++) ldsm4t(a[0][c], vaddr[c]);
#pragma unroll
            for (int j = 0; j < 8; j++) {
                if (j < 7) {
#pragma unroll
                    for (int c = 0; c < 8; c++) ldsm4t(a[(j + 1) & 1][c], vaddr[c] + (j + 1) * 4096);
                }
#pragma unroll
                for (int c = 0; c < 8; c++) mma16816(d[c], a[j & 1][c], Q[2 * j], Q[2 * j + 1]);
            }
            float o[4];
#pragma unroll
            for (int r = 0; r < 2; r++) {
                o[2 * r] = d[0][2 * r] + d[7][2 * r + 1];
                o[2 * r + 1] = d[0][2 * r + 1] + d[1][2 * r];
#pragma unroll
                for (int k = 1; k < 4; k++) {
                    const int src = (lane & 28) | ((t - k) & 3);
                    o[2 * r] += __shfl_sync(~0u, d[2 * k][2 * r] + d[2 * k - 1][2 * r + 1], src);
                    o[2 * r + 1] += __shfl_sync(~0u, d[2 * k][2 * r + 1] + d[2 * k + 1][2 * r], src);
                }
            }
            oret = atom_add_f4(odst, o[0], o[1], o[2], o[3]);
        } else if (u >= 0) {
#pragma unroll
            for (int j = 0; j < 8; j++) { d[j][0] = d[j][1] = d[j][2] = d[j][3] = 0.f; }
            mbar_wait(bar, phase);
            LAND(bu);
            uint32_t a[2][8][4];
#pragma unroll
            for (int j = 0; j < 8; j++) ldsm4(a[0][j], kaddr[0] + (4 * (j & 3) + 2 * (j >> 2)) * 256);
#pragma unroll
            for (int s = 0; s < 8; s++) {
                if (s < 7) {
#pragma unroll
                    for (int j = 0; j < 8; j++)
                        ldsm4(a[(s + 1) & 1][j], kaddr[(s + 1) & 3] + (4 * (j & 3) + 2 * (j >> 2)) * 256 + ((s + 1) >> 2) * 128);
                }
#pragma unroll
                for (int j = 0; j < 8; j++)
                    mma16816(d[j], a[s & 1][j], Q[(s & 4) * 2 + ((2 * s - 2 * j) & 7)], Q[(s & 4) * 2 + ((2 * s + 1 - 2 * j) & 7)]);
            }
        }
        if (u >= 0) phase ^= 1;
        CLK(c2b);
        if (un < NU && lane == 0) {
            if (!once) nxt = atom_inc(&ctl[C_QUEUE][0]);
            if (u >= 0 || !pre) {
                mbar_expect_tx(bar, TILE_BYTES);
                bulk_load(slot, nsrc, TILE_BYTES, bar, pol);
            }
        }
        const uint32_t tk = clock();
        CLK(c3);
        if ((unsigned)u < (unsigned)NUK) {
            const int j0 = (t - (g >> 1)) & 3;
            float v[4];
#pragma unroll
            for (int q = 0; q < 4; q++) {
                const int jq = (q >> 1) * 4, e = (q & 1) * 2;
                const float x0 = (g & 1) ? d[jq + 0][e + 1] : d[jq + 0][e];
                const float x1 = (g & 1) ? d[jq + 1][e + 1] : d[jq + 1][e];
                const float x2 = (g & 1) ? d[jq + 2][e + 1] : d[jq + 2][e];
                const float x3 = (g & 1) ? d[jq + 3][e + 1] : d[jq + 3][e];
                const float y0 = (j0 & 1) ? x1 : x0, y1 = (j0 & 1) ? x3 : x2;
                v[q] = (j0 & 2) ? y1 : y0;
            }
            const uint32_t r0 = pack_bf16(v[0], v[1]), r1 = pack_bf16(v[2], v[3]);
            const uint32_t s0 = pack_bf16(bf_lo(r0) * SCALE, bf_hi(r0) * SCALE);
            const uint32_t s1 = pack_bf16(bf_lo(r1) * SCALE, bf_hi(r1) * SCALE);
            g_scores[bu * (KEYS / 4) + 4 * g + j0] = make_uint2(s0, s1);
            const float f0 = bf_lo(s0), f1 = bf_hi(s0), f2 = bf_lo(s1), f3 = bf_hi(s1);
            const float m = warp_max(fmaxf(fmaxf(f0, f1), fmaxf(f2, f3)));
            const float l = warp_sum((expsub(f0, m) + expsub(f1, m)) + (expsub(f2, m) + expsub(f3, m)));
            if (lane == 0) g_stats[bu] = make_float2(m, l);
            kpend++;
            if (un / (NUK / 2) != u / (NUK / 2)) {
                __syncwarp();
                if (lane == 0) {
                    red_release_cta_shared(help + 4 * (u / (NUK / 2)), kpend);
                    if (un >= NUK) red_release_cta_shared(help + 8, 1u);
                }
                kpend = 0;
            }
        }
        CLK(c4);
        int unn = NU;
        if (un < NU) {
            unsigned n = 0;
            while (true) {
                if (!have) header(un, bn);
                if (un >= NUK || __all_sync(~0u, (uint32_t)(H0 >> 32) == tag && (uint32_t)(H1 >> 32) == tag)) break;
                if (++n > SPIN_LIMIT) __trap();
                have = false;
            }
            if (un >= NUK) {
                const uint32_t s0 = (uint32_t)H0, s1 = (uint32_t)(H0 >> 32);
                const float mu = __uint_as_float((uint32_t)H1);
                const float m = warp_max(mu);
                const float l = warp_sum(__uint_as_float((uint32_t)(H1 >> 32)) * expsub(mu, m));
                const float inv = 1.0f / l;
                const uint32_t w0 = pack_bf16(expsub(bf_lo(s0), m) * inv, expsub(bf_hi(s0), m) * inv);
                const uint32_t w1 = pack_bf16(expsub(bf_lo(s1), m) * inv, expsub(bf_hi(s1), m) * inv);
#pragma unroll
                for (int j = 0; j < 8; j++) {
                    Q[2 * j] = __shfl_sync(~0u, w0, 4 * j + t) & vmask;
                    Q[2 * j + 1] = __shfl_sync(~0u, w1, 4 * j + t) & vmask;
                }
            } else {
#pragma unroll
                for (int j = 0; j < 8; j++) {
                    const int src = (((j + g) & 7) << 2) + t;
                    Q[j] = __shfl_sync(~0u, (uint32_t)H0, src);
                    Q[8 + j] = __shfl_sync(~0u, (uint32_t)H1, src);
                }
            }
            unn = nstatic + (int)__shfl_sync(~0u, nxt, 0);
            if (CLU && ((NU - EARLY - unn) & ~(7 << ELOG)) == 0 && lane < MINCL)
                st_relaxed64(&g_dry[lane][(NU - EARLY - unn) >> ELOG],
                             (time_ns() - (((uint32_t)clock() - tk) >> 1) + (NU - unn) * TPU / 16) | (unsigned long long)tag << 32);
        }
        if (u >= NUK && lane < NR)
            red_add_u32(vdst,
                        1u + ((__float_as_uint(oret.x) | __float_as_uint(oret.y) | __float_as_uint(oret.z) | __float_as_uint(oret.w)) & zero));
        if (un >= NU) break;
        bu = bn;
        have = !(un < NUK && unn >= NUK && !(un >= NUK / 2 && unn < NUK + NUK / 2));
        bn = unit_block<CLU>(unn);
        if (have) header(unn, bn);
        u = un;
        un = unn;
    }
}

__device__ __forceinline__ void k_helper(uint32_t help, unsigned epoch) {
    if ((threadIdx.x & 31) != 0) return;
    unsigned (*ctl)[32] = g_ctl[epoch & 1];
    unsigned sent0 = 0, sent1 = 0, n = 0;
    int seen = 0;
    bool fin = false;
    while (!fin || seen < 2) {
        if (!fin) {
            fin = ld_acquire_cta_shared(help + 8) == NW + XW;
            const unsigned c0 = ld_acquire_cta_shared(help), c1 = ld_acquire_cta_shared(help + 4);
            if (c0 != sent0 || c1 != sent1) {
                fence_gpu();
                if (c0 != sent0) red_add_u32(&ctl[C_KDONE][0], c0 - sent0);
                if (c1 != sent1) red_add_u32(&ctl[C_KDONE + 1][0], c1 - sent1);
                sent0 = c0; sent1 = c1;
            }
        }
        if (seen < 2 && ld_acquire(&ctl[C_KDONE + seen][0]) >= NUK / 2) {
            st_release_cta_shared(help + 12 + 4 * seen, 1u);
            seen++;
        } else {
            __nanosleep(300);
        }
        if (++n > SPIN_LIMIT) __trap();
    }
}

__device__ __forceinline__ void v_poller(uint32_t sbase, int f, int w) {
    constexpr int HL = NH;
    const int lane = threadIdx.x & 31;
    const unsigned (*cp)[32] = &g_vdone[((f * NPOLL + w) % NREP) * NH];
    unsigned n = 0;
    while (ld_acquire_cta_shared(sbase + M_HELP + 12) == 0) { __nanosleep(1000); if (++n > SPIN_LIMIT) __trap(); }
    int h = 0;
    bool fast = false;
    while (h < HL) {
        const unsigned r = __ballot_sync(~0u, ld_acquire(&cp[min(h + (lane & 3), HL - 1)][0]) >= 4 * UPP) & 15u;
        if (r & 1) {
            h = min(HL, h + __ffs(~r) - 1);
            __syncwarp();
            if (lane == 0) asm volatile("red.release.cta.shared::cta.max.u32 [%0], %1;" ::"r"(sbase + M_HELP + 20), "r"(h) : "memory");
        }
        if (h < HL - 4) {
            __nanosleep(h ? 300 : 1000);
        } else if (!fast) {
            fast = true;
            const long long t0 = clock64();
            while (clock64() - t0 < w * PGAP) {}
        }
        if (++n > SPIN_LIMIT) __trap();
    }
}
__device__ __forceinline__ void finisher(const Params& p, uint32_t sbase, int f) {
    constexpr int HL = NH;
    const int lane = threadIdx.x & 31;
    {
        const char* wg = reinterpret_cast<const char*>(p.wo);
        const uint32_t dst = sbase + 4 * SLOT + (16 * (lane & 7) + (lane >> 3)) * 16;
#pragma unroll 1
        for (int h = -FPF - 4; h < HL; h++) {
            if (lane == 0 && (unsigned)(h + FPF) < (unsigned)HL) l2_prefetch(wg + (size_t)(h + FPF) * 147456 + f * 2048, 2048);
            if (h >= 0) {
#pragma unroll
                for (int r = 0; r < 4; r++)
                    asm volatile("cp.async.cg.shared.global [%0], [%1], 16;" ::"r"(dst + h * 2048 + ((r & 1) * 4 + (r >> 1) * 8) * 16),
                                 "l"(wg + (size_t)(h * 128 + r * 32 + lane) * (DM * 2) + f * 16) : "memory");
            }
            __nanosleep(FSLEEP);
        }
        asm volatile("cp.async.wait_all;" ::: "memory");
        __syncwarp();
    }
    TS(11);
    const float4* vec = g_oacc + ((lane >> 2) & 3) * 32 + (lane >> 4) * 16 + (lane & 3);
    float acc[2][2][4];
#pragma unroll
    for (int i = 0; i < 16; i++) acc[i >> 3][(i >> 2) & 1][i & 3] = 0.f;
    uint32_t* outp = reinterpret_cast<uint32_t*>(p.out + (lane >> 2) * (2 * DM) + f * 8 + (lane & 3) * 2);
    uint32_t wa = sbase + 4 * SLOT + lane * 16;
    auto project = [&](const float4 (&x)[4], const uint32_t (&w)[4][4]) {
#pragma unroll
        for (int s = 0; s < 4; s++) {
            const uint32_t a[4] = {pack_bf16(x[s].x, x[s].y), 0u, pack_bf16(x[s].z, x[s].w), 0u};
            mma16816(acc[0][s & 1], a, w[s >> 1][(s & 1) * 2], w[s >> 1][(s & 1) * 2 + 1]);
            mma16816(acc[1][s & 1], a, w[2 + (s >> 1)][(s & 1) * 2], w[2 + (s >> 1)][(s & 1) * 2 + 1]);
        }
    };
    int h = 0;
    unsigned n = 0;
    while (h < HL) {
        uint32_t w[4][4];
#pragma unroll
        for (int q = 0; q < 4; q++) ldsm4t(w[q], wa + q * 512);
        int ready;
        while ((ready = ld_acquire_cta_shared(sbase + M_HELP + 20)) <= h) {
            if (h < HL - 3) __nanosleep(100);
            if (++n > (SPIN_LIMIT << 4)) __trap();
        }
        float4 x[4], y[4];
#pragma unroll
        for (int s = 0; s < 4; s++) x[s] = ld_relaxed16(vec + s * 4);
        const bool two = ready > h + 1;
        if (two) {
#pragma unroll
            for (int s = 0; s < 4; s++) y[s] = ld_relaxed16(vec + 128 + s * 4);
        }
        project(x, w);
        if (two) {
#pragma unroll
            for (int q = 0; q < 4; q++) ldsm4t(w[q], wa + 2048 + q * 512);
            project(y, w);
        }
        const int nr = two ? 2 : 1;
        h += nr;
        vec += nr * 128;
        wa += nr * 2048;
        const float o0 = acc[0][0][0] + acc[0][1][0] + __shfl_down_sync(~0u, acc[1][0][0] + acc[1][1][0], 16);
        const float o1 = acc[0][0][1] + acc[0][1][1] + __shfl_down_sync(~0u, acc[1][0][1] + acc[1][1][1], 16);
        asm volatile("{\n.reg .pred p;\nsetp.ne.u32 p, %2, 0;\n@p st.global.u32 [%0], %1;\n}" ::"l"(outp), "r"(pack_bf16(o0, o1)),
                     "r"((uint32_t)(lane < 16 && h == NH)) : "memory");
    }
}

__device__ __noinline__ void f_collect(const unsigned (*flag)[32], unsigned full, const float4* src, unsigned todo, uint32_t sbase) {
    const int lane = threadIdx.x & 31, g = lane >> 2, t = lane & 3;
    const bool last = todo != 15;
    unsigned n = 0;
    while (todo) {
        const unsigned v = ld_acquire(&flag[t][0]);
        unsigned m = __ballot_sync(~0u, v == full) & todo;
        if (m == 0) {
            if (!last || __shfl_sync(~0u, v, 0) == 0) __nanosleep(200);
            if (++n > SPIN_LIMIT) __trap();
            continue;
        }
        __syncwarp();
        todo ^= m;
        if (last) TS(16);
        do {
            const int h0 = __ffs(m) - 1, h1 = 31 - __clz(m);
            m &= ~((1u << h0) | (1u << h1));
            float4 x[8];
#pragma unroll
            for (int b = 0; b < 8; b++) x[b] = ld_relaxed16(src + ((b & 4) ? h1 : h0) * 128 + (b & 3) * 32 + lane);
#pragma unroll
            for (int b = 0; b < 8; b++) {
                const uint32_t lo = pack_bf16(x[b].x, x[b].y), hi = pack_bf16(x[b].z, x[b].w);
                const uint32_t o = __shfl_xor_sync(~0u, (g & 1) ? lo : hi, 4);
                const uint32_t e0 = (g & 1) ? o : lo, e1 = (g & 1) ? hi : o;
                asm volatile("st.shared.v2.u32 [%0], {%1,%2};"
                             ::"r"(sbase + F_BF + ((b & 4) ? h1 : h0) * 1024 + t * 256 + ((b ^ t) & 3) * 64 + g * 8),
                               "r"(__byte_perm(e0, e1, 0x5410)), "r"(__byte_perm(e0, e1, 0x7632)) : "memory");
            }
            __syncwarp();
            if (lane < (h0 == h1 ? 1 : 2))
                asm volatile("mbarrier.arrive.shared::cta.b64 _, [%0];" ::"r"(sbase + F_BAR + 32 + (lane ? h1 : h0) * 8) : "memory");
        } while (m);
    }
    if (last) TS(17);
}

__device__ __noinline__ void f_project(const CUtensorMap* tm, int panel, int rank, int sl, int j, int delay, int step, unsigned tag, uint32_t sbase, uint64_t pol) {
    const int lane = threadIdx.x & 31, g = lane >> 2, t = lane & 3;
    const uint32_t wb = sbase + F_W - sl * 2 * SLOT, bars = sbase + F_BAR + 64 + sl * 32 * PH;
    const uint32_t wa = wb + ((lane & 7) + (lane >> 4) * 8) * 128 + (((2 * j + ((lane >> 3) & 1)) ^ (lane & 7)) * 16);
    const uint32_t ba = sbase + F_BF + (g & 3) * 64 + t * 16;
    const uint32_t rdst = mapa(sbase + F_RX + sl * 1024 + rank * 128 + g * 16 + (t & 1) * 8, 2 * j + (t >> 1));
    const uint32_t rbar = mapa(sbase + F_BAR + 16 + sl * 8, 2 * j + (t >> 1));
    unsigned n = 0;
    if (threadIdx.x >= 224) {
        if (lane == 0) asm volatile("prefetch.tensormap [%0];" ::"l"(tm) : "memory");
        unsigned long long v;
        while (!__all_sync(~0u, (v = ld_relaxed64(&g_dry[blockIdx.x >> 3][g])) >> 32 == tag)) {
            __nanosleep(200);
            if (++n > SPIN_LIMIT) __trap();
        }
        const uint32_t t0 = __shfl_sync(~0u, (uint32_t)v, 0);
        const uint32_t t1 = t0 + (__reduce_add_sync(~0u, (int)((uint32_t)v - t0)) >> 5);
        if (lane == 0) asm volatile("st.shared.u32 [%0+8], %1;\nmbarrier.arrive.shared::cta.b64 _, [%0];" ::"r"(sbase + F_BAR), "r"(t1) : "memory");
        TS(22);
    }
    mbar_wait(sbase + F_BAR, 0);
    if (lane == 0) {
        uint32_t due = lds32(sbase + F_BAR + 8) + delay;
#pragma unroll 1
        for (int q = j * PH; q < (j + 1) * PH; q++, due += step) {
            mbar_expect_tx(bars + q * 8, 16384 / PH);
            while ((int)(time_ns() - due) < 0) {}
            tma3d(wb + q * (16384 / PH), tm, 0, rank * 512 + q * (128 / PH), panel, bars + q * 8, pol);
        }
    }
    __syncwarp();
    TS(18);
#define NCH 2
    float acc[4][4];
#pragma unroll
    for (int i = 0; i < 16; i++) acc[i >> 2][i & 3] = 0.f;
    const bool up = t & 2;
#pragma unroll 1
    for (int h = 0; h < 4; h++) {
        uint32_t wp = wa + h * 16384, bar = bars + h * PH * 8, last = h == 3;
        mbar_spin(sbase + F_BAR + 32 + h * 8);
        uint32_t bf[4][4];
#pragma unroll
        for (int s = 0; s < 4; s++)
            asm volatile("ld.shared.v4.u32 {%0,%1,%2,%3}, [%4];" : "=r"(bf[s][0]), "=r"(bf[s][1]), "=r"(bf[s][2]), "=r"(bf[s][3])
                         : "r"(((ba + h * 1024) ^ (s * 64)) + s * 256) : "memory");
        asm volatile("" : "+r"(wp), "+r"(bar), "+r"(last));
#pragma unroll
        for (int q = 0; q < PH; q++) {
            mbar_spin(bar + q * 8);
            if (h == 3 && q == PH - 1) TS(19);
            uint32_t a[8 / PH][4];
#pragma unroll
            for (int s = 0; s < 8 / PH; s++) ldsm4t(a[s], wp + (q * (8 / PH) + s) * 2048);
#pragma unroll
            for (int s = 0; s < 8 / PH; s++) {
                const int k = q * (8 / PH) + s;
                mma16816(acc[s & (NCH - 1)], a[s], bf[k & 3][(k >> 2) * 2], bf[k & 3][(k >> 2) * 2 + 1]);
            }
        }
        float v0 = up ? acc[0][2] + acc[1][2] : acc[0][0] + acc[1][0], v1 = up ? acc[0][3] + acc[1][3] : acc[0][1] + acc[1][1];
        if (NCH == 4) {
            v0 = (v0 + (up ? acc[2][2] : acc[2][0])) + (up ? acc[3][2] : acc[3][0]);
            v1 = (v1 + (up ? acc[2][3] : acc[2][1])) + (up ? acc[3][3] : acc[3][1]);
        }
        asm volatile("{\n.reg .pred p;\nsetp.ne.u32 p, %4, 0;\n"
                     "@p st.async.weak.shared::cluster.mbarrier::complete_tx::bytes.v2.b32 [%0], {%1,%2}, [%3];\n}"
                     ::"r"(rdst), "r"(__float_as_uint(v0)), "r"(__float_as_uint(v1)), "r"(rbar), "r"(last) : "memory");
    }
    TS(20);
}

__device__ __noinline__ void f_receive(__nv_bfloat16* out, int sl, bool dry, uint32_t sbase) {
    const int lane = threadIdx.x & 31;
    out += (lane & 3) * (2 * DM) + (lane >> 2);
    uint32_t src = sbase + F_RX + sl * 1024 + lane * 4;
    asm volatile("" : "+l"(out), "+r"(src));
    asm volatile("{\n.reg .pred p;\n.reg .u32 n;\nmov.u32 n, 0;\nSPIN:\nmbarrier.test_wait.parity.acquire.cluster.shared::cta.b64 p, [%0], 0;\n"
                 "@p bra.uni DONE;\nadd.u32 n, n, 1;\nsetp.lt.u32 p, n, 0x4000000;\n@p bra.uni SPIN;\ntrap;\nDONE:\n}"
                 ::"r"(sbase + F_BAR + (dry ? 0 : 16 + sl * 8)) : "memory");
    float v[8];
#pragma unroll
    for (int r = 0; r < 8; r++) asm volatile("ld.shared.f32 %0, [%1];" : "=f"(v[r]) : "r"(src + r * 128) : "memory");
    const float o = ((v[0] + v[1]) + (v[2] + v[3])) + ((v[4] + v[5]) + (v[6] + v[7]));
    asm volatile("{\n.reg .pred p;\nsetp.eq.u32 p, %2, 0;\n@p st.global.u16 [%0], %1;\n}"
                 ::"l"(out), "h"((unsigned short)pack_bf16(o, 0.f)), "r"((uint32_t)dry) : "memory");
    TS(15);
}

__device__ __forceinline__ void b_final(const Params& p, uint32_t sbase, int blk, unsigned epoch, uint64_t pol) {
    const int warp = threadIdx.x >> 5;
    const int rank = blk & 7, sl = warp >> 2, panel = (blk >> 3) * 2 + sl;
    asm volatile("barrier.cluster.wait.acquire.aligned;" ::: "memory");
    if (warp == 0) f_collect(&g_cdone[4 * rank], epoch + 1, &g_octx[4 * rank * 128], 15, sbase);
    if ((warp & 3) == 0) {
        mbar_wait(sbase + F_BAR, 0);
        f_receive(p.out, sl, true, sbase);
    }
    f_project(&p.tm_fb, panel, rank, sl, warp & 3, B0 + (warp & 3) * BJ + sl * BS + rank * BR - max(0, (warp & 3) * 8 + rank - BK) * BC, BJ / PH, epoch + 1, sbase, pol);
    if ((warp & 3) == 0) f_receive(p.out + DM + panel * 64 + rank * 8, sl, false, sbase);
}

constexpr int BS_WUK = 5, BS_Q = 9, BS_CKV = 11, BS_PART = 27, BS_WUV = 29, BS_END = 33;

__device__ __noinline__ void b_issue(const Params& p, int n, int bi, uint32_t sbase, uint64_t pol) {
    if (n >= BS_END || (n >= BS_Q && n < BS_CKV) || (n >= BS_PART && n < BS_WUV)) return;
    const uint32_t bar = sbase + M_BAR + (NSLOT + n % BRING) * 8;
    const CUtensorMap* tm;
    int row, panel = 2 * bi;
    if (n < BS_WUK) { tm = &p.tm_wq; row = n * 128; }
    else if (n < BS_Q) { tm = &p.tm_wuk; row = (n - BS_WUK) * 128; }
    else if (n < BS_PART) {
        tm = &p.tm_ckv; panel = 0;
        row = (bi >> 3) * SK + ((n - BS_CKV) * 8 + (bi & 7)) * 32;
    }
    else { tm = &p.tm_wuv; row = (n - BS_WUV) * 128; }
    mbar_expect_tx(bar, n == 0 ? 32768 + 4 * 1152 : 32768);
    tma3d(sbase + (n % BRING) * SLOT, tm, 0, row, panel, bar, pol);
}
__device__ __forceinline__ void b_issue_xchg(int n, const void* src, uint32_t sbase, uint64_t pol) {
    asm volatile("fence.proxy.async;" ::: "memory");
#pragma unroll
    for (int i = 0; i < 2; i++) {
        const uint32_t bar = sbase + M_BAR + (NSLOT + (n + i) % BRING) * 8;
        mbar_expect_tx(bar, 32768);
        bulk_load(sbase + ((n + i) % BRING) * SLOT, reinterpret_cast<const char*>(src) + i * 32768, 32768, bar, pol);
    }
}
__device__ __forceinline__ void b_wait(int n, uint32_t sbase) {
    mbar_wait(sbase + M_BAR + (NSLOT + n % BRING) * 8, (n / BRING) & 1);
}

__device__ __noinline__ void b_gemm(const Params& p, uint32_t sbase, int n0, int n1, int ktot, uint32_t xh, uint32_t xl, int pitch,
                                    int bi, uint64_t pol) {
    const int tid = threadIdx.x, warp = tid >> 5, lane = tid & 31, g = lane >> 2, t = lane & 3;
    const uint32_t woff = (warp >> 2) * 16384 + (lane & 15) * 128 + ((((warp & 3) * 2 + (lane >> 4)) ^ (lane & 7)) * 16);
    const uint32_t xoff = (g & 3) * pitch + t * 4;
    float acc[2][4];
#pragma unroll
    for (int i = 0; i < 8; i++) acc[i >> 2][i & 3] = 0.f;
#pragma unroll 1
    for (int n = n0; n < n1; n++) {
        b_wait(n, sbase);
        const uint32_t slot = sbase + (n % BRING) * SLOT + woff;
        const int k0 = (n - n0) * 128;
        const int ns = min(8, (ktot - k0) >> 4);
#pragma unroll 2
        for (int s = 0; s < ns; s++) {
            uint32_t a[4], w[4];
            const uint32_t xo = xoff + (k0 + 16 * s) * 2;
            a[0] = lds32(xh + xo); a[2] = lds32(xh + xo + 16);
            a[1] = xl ? lds32(xl + xo) : 0u; a[3] = xl ? lds32(xl + xo + 16) : 0u;
            ldsm4t(w, slot + s * 2048);
            mma16816(acc[0], a, w[0], w[1]);
            mma16816(acc[1], a, w[2], w[3]);
        }
        __syncthreads();
        if (tid == 0) b_issue(p, n + BD, bi, sbase, pol);
    }
    if (g < 4) {
#pragma unroll
        for (int j = 0; j < 2; j++)
            asm volatile("st.shared.u32 [%0], %1;" ::"r"(sbase + M_QB + g * QP + (warp * 16 + j * 8 + t * 2) * 2),
                         "r"(pack_bf16(acc[j][0] + acc[j][2], acc[j][1] + acc[j][3])) : "memory");
    }
    __syncthreads();
}

__device__ __forceinline__ void b_exchange(unsigned* c, int n, const void* src, uint32_t sbase, uint64_t pol) {
    TS(n == BS_Q ? 24 : 28);
    __syncthreads();
    if (threadIdx.x == 0) {
        TS(n == BS_Q ? 25 : 29);
        fence_gpu();
        TS(n == BS_Q ? 26 : 30);
        red_add_u32(c, 1u);
        wait_count(c, NBCTA);
        TS(n == BS_Q ? 27 : 31);
        b_issue_xchg(n, src, sbase, pol);
    }
}

template <bool CLU>
__device__ __noinline__ void b_chain(const Params& p, char* smem, uint32_t sbase, int bi, unsigned epoch, uint64_t pol) {
    const int tid = threadIdx.x, warp = tid >> 5, lane = tid & 31, g = lane >> 2, t = lane & 3;
    unsigned (*ctl)[32] = g_ctl[epoch & 1];
    float* red = reinterpret_cast<float*>(smem + 5 * SLOT);
    __syncthreads();
    b_gemm(p, sbase, 0, BS_WUK, DM, sbase + M_XB, 0, XP, bi, pol);
    TS(6);
    {
        uint32_t Q[16];
#pragma unroll
        for (int c = 0; c < 16; c++) Q[c] = lds32(sbase + M_QB + (g & 3) * QP + c * 16 + t * 4);
        float* qa = reinterpret_cast<float*>(smem + M_QA);
#pragma unroll 1
        for (int n = BS_WUK; n < BS_Q; n++) {
            b_wait(n, sbase);
            const uint32_t base = sbase + (n % BRING) * SLOT + (warp * 16 + (lane & 15)) * 128;
            float d[2][4];
#pragma unroll
            for (int i = 0; i < 8; i++) d[i >> 2][i & 3] = 0.f;
#pragma unroll
            for (int s = 0; s < 8; s++) {
                uint32_t a[4];
                ldsm4(a, base + (s >> 2) * 16384 + (((2 * (s & 3) + (lane >> 4)) ^ (lane & 7)) * 16));
                mma16816(d[s & 1], a, Q[2 * s], Q[2 * s + 1]);
            }
            const int c = (n - BS_WUK) * 128 + warp * 16 + g + 8 * (t >> 1);
            qa[(2 * (t & 1)) * 512 + c] = (t & 2) ? d[0][2] + d[1][2] : d[0][0] + d[1][0];
            qa[(2 * (t & 1) + 1) * 512 + c] = (t & 2) ? d[0][3] + d[1][3] : d[0][1] + d[1][1];
            __syncthreads();
            if (tid == 0) b_issue(p, n + BD, bi, sbase, pol);
        }
#pragma unroll 1
        for (int r = 0; r < 2; r++) {
            const int id = tid + r * 256;
            const int b = id >> 7, c0 = ((id >> 2) & 31) * 16 + (id & 3) * 2;
            const float2 u0 = *reinterpret_cast<const float2*>(qa + b * 512 + c0);
            const float2 u1 = *reinterpret_cast<const float2*>(qa + b * 512 + c0 + 8);
            const uint32_t h0 = pack_bf16(u0.x, u0.y), h1 = pack_bf16(u1.x, u1.y);
            const uint32_t l0 = pack_bf16(u0.x - bf_lo(h0), u0.y - bf_hi(h0)), l1 = pack_bf16(u1.x - bf_lo(h1), u1.y - bf_hi(h1));
            g_qabs[((id >> 2) * 4 + (bi >> 3)) * 32 + (bi & 7) * 4 + (id & 3)] = make_uint4(h0, l0, h1, l1);
        }
    }
    b_exchange(&ctl[C_BBAR][0], BS_Q, &g_qabs[(bi >> 3) * 4096], sbase, pol);
    {
        uint32_t qf[4][4][4];
        b_wait(BS_Q + (warp >> 2), sbase);
        TS(7);
        {
            const uint4* qs = reinterpret_cast<const uint4*>(smem + ((BS_Q + (warp >> 2)) % BRING) * SLOT) + (warp & 3) * 512 + lane;
#pragma unroll
            for (int s = 0; s < 4; s++)
#pragma unroll
                for (int i = 0; i < 4; i++) {
                    const uint4 v = qs[(s * 4 + i) * 32];
                    qf[i][s][0] = v.x; qf[i][s][1] = v.y; qf[i][s][2] = v.z; qf[i][s][3] = v.w;
                }
        }
        __syncthreads();
        if (tid == 0) { b_issue(p, BS_Q + BD, bi, sbase, pol); b_issue(p, BS_Q + 1 + BD, bi, sbase, pol); }
        float acc[2][8][4];
#pragma unroll
        for (int i = 0; i < 2; i++)
#pragma unroll
            for (int j = 0; j < 8; j++) { acc[i][j][0] = acc[i][j][1] = acc[i][j][2] = acc[i][j][3] = 0.f; }
        float mrun = -INFINITY, lrun = 0.f;
        const int head = tid >> 3, kq = tid & 7;
        float* alpha = reinterpret_cast<float*>(smem + M_ALPHA);
        for (int n = BS_CKV; n < BS_PART; n++) {
            b_wait(n, sbase);
            const uint32_t slot = sbase + (n % BRING) * SLOT;
            float sc[4][4][4];
#pragma unroll
            for (int i = 0; i < 4; i++)
#pragma unroll
                for (int j = 0; j < 4; j++) { sc[i][j][0] = sc[i][j][1] = sc[i][j][2] = sc[i][j][3] = 0.f; }
#pragma unroll
            for (int j = 0; j < 4; j++)
#pragma unroll
                for (int sp = 0; sp < 2; sp++) {
                    uint32_t bf[4];
                    ldsm4(bf, slot + warp * 4096 + (8 * j + (lane & 7)) * 128 + (((4 * sp + (lane >> 3)) ^ (lane & 7)) * 16));
#pragma unroll
                    for (int i = 0; i < 4; i++) {
                        mma16816(sc[i][j], qf[i][2 * sp], bf[0], bf[1]);
                        mma16816(sc[i][j], qf[i][2 * sp + 1], bf[2], bf[3]);
                    }
                }
#pragma unroll
            for (int i = 0; i < 4; i++)
#pragma unroll
                for (int j = 0; j < 4; j++)
                    *reinterpret_cast<float2*>(red + warp * 1024 + (8 * i + g) * 32 + ((8 * j) ^ (8 * (g & 3))) + 2 * t) =
                        make_float2(sc[i][j][0] + sc[i][j][2], sc[i][j][1] + sc[i][j][3]);
            __syncthreads();
            if (tid == 0 && n > BS_CKV) b_issue(p, n - 1 + BD, bi, sbase, pol);
            {
                float4 s = make_float4(0.f, 0.f, 0.f, 0.f);
#pragma unroll
                for (int w = 0; w < 8; w++) {
                    const float4 v = *reinterpret_cast<const float4*>(red + w * 1024 + head * 32 + ((4 * kq) ^ (8 * (head & 3))));
                    s.x += v.x; s.y += v.y; s.z += v.z; s.w += v.w;
                }
                const uint32_t r0 = pack_bf16(s.x, s.y), r1 = pack_bf16(s.z, s.w);
                const uint32_t s0 = pack_bf16(bf_lo(r0) * SCALE, bf_hi(r0) * SCALE);
                const uint32_t s1 = pack_bf16(bf_lo(r1) * SCALE, bf_hi(r1) * SCALE);
                const float f0 = bf_lo(s0), f1 = bf_hi(s0), f2 = bf_lo(s1), f3 = bf_hi(s1);
                float mx = fmaxf(fmaxf(f0, f1), fmaxf(f2, f3));
                mx = fmaxf(mx, __shfl_xor_sync(~0u, mx, 1));
                mx = fmaxf(mx, __shfl_xor_sync(~0u, mx, 2));
                mx = fmaxf(mx, __shfl_xor_sync(~0u, mx, 4));
                const float mnew = fmaxf(mrun, mx);
                const float al = expsub(mrun, mnew);
                const float p0 = expsub(f0, mnew), p1 = expsub(f1, mnew), p2 = expsub(f2, mnew), p3 = expsub(f3, mnew);
                lrun = lrun * al + ((p0 + p1) + (p2 + p3));
                mrun = mnew;
                *reinterpret_cast<uint2*>(smem + M_P + head * 80 + kq * 8) = make_uint2(pack_bf16(p0, p1), pack_bf16(p2, p3));
                if (kq == 0) alpha[head] = al;
            }
            __syncthreads();
            {
                uint32_t pf[2][2][4];
#pragma unroll
                for (int i = 0; i < 2; i++)
#pragma unroll
                    for (int ks = 0; ks < 2; ks++)
                        ldsm4(pf[i][ks], sbase + M_P + (16 * i + (lane & 15)) * 80 + (16 * ks + 8 * (lane >> 4)) * 2);
#pragma unroll
                for (int i = 0; i < 2; i++) {
                    const float a0 = alpha[16 * i + g], a1 = alpha[16 * i + 8 + g];
#pragma unroll
                    for (int j = 0; j < 8; j++) { acc[i][j][0] *= a0; acc[i][j][1] *= a0; acc[i][j][2] *= a1; acc[i][j][3] *= a1; }
                }
#pragma unroll
                for (int j = 0; j < 8; j++) {
                    uint32_t bf[4];
                    ldsm4t(bf, slot + warp * 4096 + lane * 128 + ((j ^ (lane & 7)) * 16));
#pragma unroll
                    for (int i = 0; i < 2; i++) {
                        mma16816(acc[i][j], pf[i][0], bf[0], bf[1]);
                        mma16816(acc[i][j], pf[i][1], bf[2], bf[3]);
                    }
                }
            }
        }
        __syncthreads();
        if (tid == 0) b_issue(p, BS_PART - 1 + BD, bi, sbase, pol);
        lrun += __shfl_xor_sync(~0u, lrun, 1);
        lrun += __shfl_xor_sync(~0u, lrun, 2);
        lrun += __shfl_xor_sync(~0u, lrun, 4);
        if (kq == 0) g_bml[head * NBCTA + bi] = make_float2(mrun, lrun);
#pragma unroll
        for (int i = 0; i < 2; i++)
#pragma unroll
            for (int j = 0; j < 8; j++) {
                g_bpart[((16 * i + g) * NBCTA + bi) * 256 + warp * 32 + j * 4 + t] = make_float2(acc[i][j][0], acc[i][j][1]);
                g_bpart[((16 * i + 8 + g) * NBCTA + bi) * 256 + warp * 32 + j * 4 + t] = make_float2(acc[i][j][2], acc[i][j][3]);
            }
    }
    if (!CLU) {
#pragma unroll 1
        for (int i = tid; i < NH * 36; i += 256) g_outb[bi * NH * 36 + i] = make_uint4(0u, epoch, 0u, epoch);
    }
    b_exchange(&ctl[C_BBAR + 1][0], BS_PART, &g_bpart[bi * NBCTA * 256], sbase, pol);
    {
        float* omega = reinterpret_cast<float*>(smem + M_OMEGA);
        if (warp == 0) {
            __syncwarp();
            const uint2 ml = ld_relaxed8(&g_bml[bi * NBCTA + lane]);
            const float ms = __uint_as_float(ml.x);
            float m = ms;
            m = fmaxf(m, __shfl_xor_sync(~0u, m, 1));
            m = fmaxf(m, __shfl_xor_sync(~0u, m, 2));
            m = fmaxf(m, __shfl_xor_sync(~0u, m, 4));
            const float w = expsub(ms, m);
            float l = w * __uint_as_float(ml.y);
            l += __shfl_xor_sync(~0u, l, 1);
            l += __shfl_xor_sync(~0u, l, 2);
            l += __shfl_xor_sync(~0u, l, 4);
            omega[lane] = w / l;
        }
        __syncthreads();
        b_wait(BS_PART, sbase);
        b_wait(BS_PART + 1, sbase);
#pragma unroll 1
        for (int b = 0; b < 4; b++) {
            const float2* ps = reinterpret_cast<const float2*>(smem + ((BS_PART + (b >> 1)) % BRING) * SLOT) + (b & 1) * 2048 + tid;
            float c0 = 0.f, c1 = 0.f;
#pragma unroll
            for (int s = 0; s < 8; s++) {
                const float w = omega[b * 8 + s];
                const float2 v = ps[s * 256];
                c0 = fmaf(w, v.x, c0);
                c1 = fmaf(w, v.y, c1);
            }
            const uint32_t hi = pack_bf16(c0, c1);
            *reinterpret_cast<uint32_t*>(smem + M_CH + b * CP + tid * 4) = hi;
            *reinterpret_cast<uint32_t*>(smem + M_CL + b * CP + tid * 4) = pack_bf16(c0 - bf_lo(hi), c1 - bf_hi(hi));
        }
        __syncthreads();
        if (tid == 0) { b_issue(p, BS_PART + BD, bi, sbase, pol); b_issue(p, BS_PART + 1 + BD, bi, sbase, pol); }
    }
    b_gemm(p, sbase, BS_WUV, BS_END, 512, sbase + M_CH, sbase + M_CL, CP, bi, pol);
    TS(12);
    if (CLU) {
        if (warp < 4) {
            const unsigned short* c = reinterpret_cast<const unsigned short*>(smem + M_QB + warp * QP) + 16 * t + g;
            g_octx[(bi * 4 + warp) * 32 + lane] = make_float4(bf_lo(c[0]), bf_lo(c[8]), bf_lo(c[64]), bf_lo(c[72]));
        }
        __syncthreads();
        if (tid == 0) asm volatile("st.release.gpu.global.u32 [%0], %1;" ::"l"(&g_cdone[bi][0]), "r"(epoch + 1) : "memory");
        return;
    }
    if (tid == 0) {
#pragma unroll 1
        for (int i = 0; i < 4; i++) {
            mbar_expect_tx(sbase + M_BAR + i * 8, 36864);
            tma3d(sbase + i * 36864, &p.tm_wo, 0, bi * 128 + i * 32, 0, sbase + M_BAR + i * 8, pol);
        }
    }
    TS(8);
    {
        float acc[9][4];
#pragma unroll
        for (int j = 0; j < 9; j++) { acc[j][0] = acc[j][1] = acc[j][2] = acc[j][3] = 0.f; }
#pragma unroll 1
        for (int i = 0; i < 4; i++) {
            const uint32_t xo = sbase + M_QB + (g & 3) * QP + i * 64 + t * 4;
            const uint32_t a0[4] = {lds32(xo), 0u, lds32(xo + 16), 0u}, a1[4] = {lds32(xo + 32), 0u, lds32(xo + 48), 0u};
            mbar_wait(sbase + M_BAR + i * 8, 0);
#pragma unroll
            for (int j = 0; j < 9; j++) {
                const int nt = warp * 9 + j;
                uint32_t w[4];
                ldsm4t(w, sbase + i * 36864 + (nt >> 3) * 4096 + lane * 128 + (((nt & 7) ^ (lane & 7)) * 16));
                mma16816(acc[j], a0, w[0], w[1]);
                mma16816(acc[j], a1, w[2], w[3]);
            }
        }
        if (g < 4) {
#pragma unroll
            for (int j = 0; j < 9; j++) {
                const int c2 = (warp * 9 + j) * 4 + t;
                st_tagged2(&g_outb[((c2 / 9) * NH + bi) * 36 + g * 9 + c2 % 9], acc[j][0], acc[j][1], epoch + 1);
            }
        }
    }
    TS(9);
    {
        const uint4* src = g_outb + (bi * NH + (tid >> 3)) * 36 + (tid & 7);
        float2* part = reinterpret_cast<float2*>(red);
        unsigned n = 0;
        while (true) {
            ulonglong2 v[5];
            bool ok = true;
#pragma unroll
            for (int i = 0; i < 5; i++)
                if (i < 4 || (tid & 7) < 4) v[i] = ld_tagged2(src + i * 8);
#pragma unroll
            for (int i = 0; i < 5; i++)
                if (i < 4 || (tid & 7) < 4) {
                    ok = ok && (unsigned)(v[i].x >> 32) == epoch + 1 && (unsigned)(v[i].y >> 32) == epoch + 1;
                    part[(tid >> 3) * 36 + (tid & 7) + i * 8] = make_float2(__uint_as_float((unsigned)v[i].x), __uint_as_float((unsigned)v[i].y));
                }
            if (ok) break;
            __nanosleep(400);
            if (++n > SPIN_LIMIT) __trap();
        }
        __syncthreads();
        if (tid < 36) {
            float s0 = 0.f, s1 = 0.f;
#pragma unroll 8
            for (int h = 0; h < NH; h++) { const float2 v = part[h * 36 + tid]; s0 += v.x; s1 += v.y; }
            *reinterpret_cast<uint32_t*>(p.out + (tid / 9) * 2 * DM + DM + bi * 18 + (tid % 9) * 2) = pack_bf16(s0, s1);
        }
    }
    TS(10);
}

template <bool CLU>
__global__ void __launch_bounds__(256, 1) fused_decode_kernel(const __grid_constant__ Params p) {
    extern __shared__ __align__(1024) char smem_raw[];
    const uint32_t sbase = (smem_u32(smem_raw) + 1023u) & ~1023u;
    if (CLU && threadIdx.x < 32 && blockIdx.x >= NBCTA) {
        const unsigned u0 = blockIdx.x - NBCTA, u1 = u0 + 8 * MINCL - NBCTA;
        asm volatile("{\n.reg .pred p;\nelect.sync _|p, 0xffffffff;\n"
                     "@p mbarrier.init.shared::cta.b64 [%0], 1;\n"
                     "@p mbarrier.init.shared::cta.b64 [%0+8], 1;\n"
                     "@p fence.mbarrier_init.release.cluster;\n"
                     "@p mbarrier.arrive.expect_tx.shared::cta.b64 _, [%0], 32768;\n"
                     "@p cp.async.bulk.shared::cluster.global.mbarrier::complete_tx::bytes.L2::cache_hint [%1], [%2], 32768, [%0], %4;\n"
                     "@p mbarrier.arrive.expect_tx.shared::cta.b64 _, [%0+8], 32768;\n"
                     "@p cp.async.bulk.shared::cluster.global.mbarrier::complete_tx::bytes.L2::cache_hint [%1+32768], [%3], 32768, [%0+8], %4;\n}"
                     ::"r"(sbase + M_BAR), "r"(sbase), "l"(reinterpret_cast<const char*>(p.kc) + (size_t)u0 * TILE_BYTES),
                       "l"(reinterpret_cast<const char*>(p.kc) + (size_t)((u1 >> 7) * 1024 + (u1 & 127)) * TILE_BYTES), "l"(0x12F0000000000000ull) : "memory");
    }
    char* smem = smem_raw + (sbase - smem_u32(smem_raw));
    const int tid = threadIdx.x, warp = tid >> 5, lane = tid & 31;
    const int blk = blockIdx.x;
    const bool isB = CLU ? blk < NBCTA : (blk & 3) == 0 && (blk >> 2) < NBCTA;
    const int bi = CLU ? blk : blk >> 2;
    const int nb = CLU ? blk - NBCTA : blk - min(NBCTA, (blk + 3) >> 2);
    const int nnb = gridDim.x - NBCTA;
    const int nstatic = nnb * (NW + XW);
    uint64_t pol;
    asm volatile("createpolicy.fractional.L2::evict_first.b64 %0, 1.0;" : "=l"(pol));
    const uint32_t wbar = sbase + M_BAR + warp * 8, wslot = sbase + warp * SLOT;
    const int u0 = warp * nnb + nb;
    const bool hold = ((blk >> 2) >> KMIN << KMIN) * 4 * UPP < nstatic;
    const uint32_t jbar = sbase + M_BAR + (NSLOT + BRING) * 8;
    if (warp == 7) {
        if (lane == 0 && blk < 128) {
            mbar_init(jbar, 1);
            asm volatile("fence.mbarrier_init.release.cluster;" ::: "memory");
            uint64_t poln;
            asm volatile("createpolicy.fractional.L2::evict_normal.b64 %0, 1.0;" : "=l"(poln));
            mbar_expect_tx(jbar, 36864 + 4 * 1152);
            tma3d(sbase + J0W, &p.tm_j0, blk * 32, 0, 0, jbar, poln);
            bulk_load(sbase + M_XA, p.xa, 4608, jbar, poln);
        }
        if (lane < 8) reinterpret_cast<unsigned*>(smem + M_HELP)[lane] = 0;
        __syncwarp();
        if (!isB) asm volatile("bar.arrive 2, %0;" ::"n"(32 * (NW + XW + 1)) : "memory");
    }
    if (warp < 4 && lane == 0 && (!CLU || isB || warp >= 2)) {
        mbar_init(wbar, 1);

        asm volatile("fence.mbarrier_init.release.cluster;" ::: "memory");
        if (warp < NEARLY && !isB && !hold) {
            mbar_expect_tx(wbar, TILE_BYTES);
            bulk_load(wslot, block_src(p.kc, unit_block<CLU>(u0)), TILE_BYTES, wbar, pol);
        }
    }
    unsigned epoch = 0;
    if (lane == 0) epoch = ld_relaxed4(&g_epoch);
    TS(0);
    if (CLU) {
        if (warp == 6) {
            if (lane < 8 + 8 * PH && lane != 1) mbar_init(sbase + F_BAR + lane * 8, 1);
            if ((lane >> 1) == 1) mbar_expect_tx(sbase + F_BAR + lane * 8, 1024);
            asm volatile("fence.mbarrier_init.release.cluster;" ::: "memory");
        }
        asm volatile("barrier.cluster.arrive.relaxed.aligned;" ::: "memory");
    }
    if ((warp >> 1) == 2 && blk < 128) st_relaxed64(&g_qll[((tid - 128) >> 4) * 2048 + blk * 16 + (tid & 15)], 0ull);
    if (isB || warp >= NW + XW) epoch = __shfl_sync(~0u, epoch, 0);
    if (isB && warp == 3) asm volatile("bar.sync 1, 160;" ::: "memory");
    if (isB && tid == 96) {
#pragma unroll 1
        for (int i = 0; i < BRING; i++) mbar_init(sbase + M_BAR + (NSLOT + i) * 8, 1);
        asm volatile("fence.mbarrier_init.release.cluster;" ::: "memory");
        if (hold) { unsigned n = 0; while (ld_acquire_cta_shared(sbase + M_HELP + 24) < 2) { if (++n > (SPIN_LIMIT << 4)) __trap(); } }
#pragma unroll 1
        for (int b = 0; b < 4; b++) bulk_load(sbase + M_XB + b * XP, p.xb + b * DM, 1152, sbase + M_BAR + NSLOT * 8, pol);
#pragma unroll 1
        for (int n = 0; n < BD; n++) b_issue(p, n, bi, sbase, pol);
    }
    if (warp >= 4 && blk < 128) {
        const int g = lane >> 2, t = lane & 3, j = tid - 128;
        asm volatile("bar.sync 1, %0;" ::"r"(isB ? 160 : 128) : "memory");
#pragma unroll 1
        for (int sl = blk, ph = 0;; sl += 128 - gridDim.x, ph = 1) {
        mbar_wait(jbar, ph);
        TS(13);
        float acc[4][4];
#pragma unroll
        for (int i = 0; i < 16; i++) acc[i >> 2][i & 3] = 0.f;
        const uint32_t wa = sbase + J0W + ((warp - 4) * 144 + (lane & 15)) * 64;
        const uint32_t sw = (lane >> 1) & 3, xa = sbase + M_XA + (g & 3) * 1152 + (warp - 4) * 288 + t * 4;
#pragma unroll 3
        for (int s = 0; s < 9; s++) {
            const uint32_t a[4] = {lds32(xa + s * 32), 0u, lds32(xa + s * 32 + 16), 0u};
            uint32_t w0[4], w1[4];
            ldsm4t(w0, wa + s * 1024 + (((lane >> 4) ^ sw) * 16));
            ldsm4t(w1, wa + s * 1024 + (((2 + (lane >> 4)) ^ sw) * 16));
            mma16816(acc[0], a, w0[0], w0[1]);
            mma16816(acc[1], a, w0[2], w0[3]);
            mma16816(acc[2], a, w1[0], w1[1]);
            mma16816(acc[3], a, w1[2], w1[3]);
        }
        float2* j0 = reinterpret_cast<float2*>(smem + M_J0);
        if (g < 4) {
#pragma unroll
            for (int i = 0; i < 4; i++) j0[(warp - 4) * 64 + g * 16 + i * 4 + t] = make_float2(acc[i][0], acc[i][1]);
        }
        asm volatile("bar.sync 1, 128;" ::: "memory");
        const bool again = sl == blk && blk + 128 - (int)gridDim.x >= (int)gridDim.x;
        if (again && tid == 224) {
            mbar_expect_tx(jbar, 36864);
            tma3d(sbase + J0W, &p.tm_j0, (blk + 128 - gridDim.x) * 32, 0, 0, jbar, pol);
        }
        if (warp < 6) {
            const float2 v0 = j0[j], v1 = j0[64 + j], v2 = j0[128 + j], v3 = j0[192 + j];
            st_relaxed64(&g_qll[(j >> 4) * 2048 + sl * 16 + (j & 15)],
                         (unsigned long long)pack_bf16((v0.x + v1.x) + (v2.x + v3.x), (v0.y + v1.y) + (v2.y + v3.y)) |
                             ((unsigned long long)(epoch + 1) << 32));
            __syncwarp();
            if (lane == 0) asm volatile("red.relaxed.cta.shared::cta.add.u32 [%0], 1;" ::"r"(sbase + M_HELP + 24) : "memory");
        } else if (warp == 7) {
            if (blk < C_LINES) g_ctl[(epoch & 1) ^ 1][blk][lane] = 0;
        }
        TS(1);
        if (!again) break;
        asm volatile("bar.sync 1, 128;" ::: "memory");
        }
    }
    if (isB) {
        b_chain<CLU>(p, smem, sbase, bi, epoch, pol);
        if (CLU) b_final(p, sbase, blk, epoch, pol);
        return;
    }
    const int sl = nb >> 3, rank = blk & 7;
    if (warp < NW + XW) {
        a_worker<CLU>(p, u0, warp >= NW + ((nb & 3) < (CLU ? X3C : X3) ? 1 : 0), warp < NEARLY && !hold, hold, nstatic, wslot, wbar, sbase + M_HELP,
                      epoch, pol);
        const bool two = sl < 9 && rank == 7;
        if (CLU && (warp == 3 || (warp == 2 && two)) && sl < 10) {
            epoch = __shfl_sync(~0u, epoch, 0);
            unsigned n = 0;
            while (ld_acquire_cta_shared(sbase + M_HELP + 12) == 0) { __nanosleep(1000); if (++n > SPIN_LIMIT) __trap(); }
            asm volatile("barrier.cluster.wait.acquire.aligned;" ::: "memory");
            f_collect((sl < 9 ? g_vdone : g_cdone) + 4 * rank, sl < 9 ? 4 * UPP : epoch + 1, (sl < 9 ? g_oacc : g_octx) + 4 * rank * 128,
                      two ? (warp == 2 ? CM2 : 15 - CM2) : 15, sbase);
            if (warp == 2) return;
            mbar_wait(sbase + F_BAR, 0);
#pragma unroll 1
            for (int i = 0; i < 2; i++) f_receive(p.out + (sl < 9 ? sl * 64 : DM + 512) + rank * 8, 0, i == 0, sbase);
        }
        return;
    }
    if (warp == 7) {
#pragma unroll 1
        for (int i = nb; i < 4 * NH; i += nnb) g_oacc[i * 32 + lane] = make_float4(0.f, 0.f, 0.f, 0.f);
        if (nb < NREP * NH) g_vdone[nb][lane] = 0;
        __syncwarp();
        k_helper(sbase + M_HELP, epoch);
        if (nb == 0 && lane == 0) g_epoch = epoch + 1;
        __syncwarp();
    }
    if (CLU) {
        if (sl < 10) {
            const CUtensorMap* tm = sl < 9 ? &p.tm_fa : &p.tm_fb;
            asm volatile("barrier.cluster.wait.acquire.aligned;" ::: "memory");
            f_project(tm, min(sl, 8), rank, 0, warp & 3, A0 + (warp & 3) * AJ + rank * AR - max(0, (warp & 3) * 8 + rank - AK) * AC, AJ / PH, epoch + 1, sbase, pol);
        }
    } else if (warp == 6 && nb < NFIN) {
        finisher(p, sbase, nb);
        TS(4);
    } else if (warp != 7 && warp >= 6 - NPOLL && nb < NFIN) {
        v_poller(sbase, nb, warp - (6 - NPOLL));
    }
}

}

typedef CUresult (*EncodeFn)(CUtensorMap*, CUtensorMapDataType, cuuint32_t, void*, const cuuint64_t*, const cuuint64_t*,
                             const cuuint32_t*, const cuuint32_t*, CUtensorMapInterleave, CUtensorMapSwizzle,
                             CUtensorMapL2promotion, CUtensorMapFloatOOBfill);

extern "C" void kernel_launch(void* const* d_in, const int* in_sizes, int n_in, void* d_out, int out_size) {
    (void)in_sizes; (void)n_in; (void)out_size;
    static int nsm = 0, ncl = 0;
    static EncodeFn encode = nullptr;
    cudaLaunchConfig_t cfg = {};
    cudaLaunchAttribute at[1];
    at[0].id = cudaLaunchAttributeClusterDimension;
    at[0].val.clusterDim.x = 8; at[0].val.clusterDim.y = 1; at[0].val.clusterDim.z = 1;
    cfg.blockDim = dim3(256); cfg.dynamicSmemBytes = SMEM_BYTES; cfg.stream = cudaStreamPerThread; cfg.attrs = at; cfg.numAttrs = 1;
    if (nsm == 0) {
        int dev = 0;
        cudaGetDevice(&dev);
        cudaDeviceGetAttribute(&nsm, cudaDevAttrMultiProcessorCount, dev);
        cudaFuncSetAttribute(fused_decode_kernel<false>, cudaFuncAttributeMaxDynamicSharedMemorySize, SMEM_BYTES);
        cudaFuncSetAttribute(fused_decode_kernel<true>, cudaFuncAttributeMaxDynamicSharedMemorySize, SMEM_BYTES);
        cfg.gridDim = dim3(128);
        if (cudaOccupancyMaxActiveClusters(&ncl, fused_decode_kernel<true>, &cfg) != cudaSuccess) { ncl = 0; (void)cudaGetLastError(); }
        if (ncl > MINCL) ncl = MINCL;
        void* fn = nullptr;
        cudaDriverEntryPointQueryResult qr;
        cudaGetDriverEntryPoint("cuTensorMapEncodeTiled", &fn, cudaEnableDefault, &qr);
        encode = (EncodeFn)fn;
    }
    Params p;
    auto panels = [&](CUtensorMap* tm, void* ptr, int rows, int cols, int box_rows, int box_panels,
                      CUtensorMapL2promotion promo = CU_TENSOR_MAP_L2_PROMOTION_L2_256B) {
        const cuuint64_t gd[3] = {64, (cuuint64_t)rows, (cuuint64_t)(cols / 64)}, gs[2] = {(cuuint64_t)cols * 2, 128};
        const cuuint32_t box[3] = {64, (cuuint32_t)box_rows, (cuuint32_t)box_panels}, es[3] = {1, 1, 1};
        encode(tm, CU_TENSOR_MAP_DATA_TYPE_BFLOAT16, 3, ptr, gd, gs, box, es, CU_TENSOR_MAP_INTERLEAVE_NONE,
               CU_TENSOR_MAP_SWIZZLE_128B, promo, CU_TENSOR_MAP_FLOAT_OOB_FILL_NONE);
    };
    panels(&p.tm_wq, d_in[7], DM, 4096, 128, 2);
    panels(&p.tm_wuk, d_in[8], 512, 4096, 128, 2);
    panels(&p.tm_wuv, d_in[9], 512, 4096, 128, 2);
    panels(&p.tm_wo, d_in[10], 4096, DM, 32, 9);
    panels(&p.tm_ckv, d_in[6], 4 * SK, 512, 32, 8);
    panels(&p.tm_fa, d_in[4], 4096, DM, 128 / PH, 1, CU_TENSOR_MAP_L2_PROMOTION_L2_128B);
    panels(&p.tm_fb, d_in[10], 4096, DM, 128 / PH, 1, CU_TENSOR_MAP_L2_PROMOTION_L2_128B);
    {
        const cuuint64_t gd[3] = {4096, 192, 3}, gs[2] = {8192, 192 * 8192};
        const cuuint32_t box[3] = {32, 192, 3}, es[3] = {1, 1, 1};
        encode(&p.tm_j0, CU_TENSOR_MAP_DATA_TYPE_BFLOAT16, 3, d_in[3], gd, gs, box, es, CU_TENSOR_MAP_INTERLEAVE_NONE,
               CU_TENSOR_MAP_SWIZZLE_64B, CU_TENSOR_MAP_L2_PROMOTION_L2_128B, CU_TENSOR_MAP_FLOAT_OOB_FILL_NONE);
    }
    p.xa = (const __nv_bfloat16*)d_in[0];
    p.kc = (const __nv_bfloat16*)d_in[1];
    p.vc = (const __nv_bfloat16*)d_in[2];
    p.wo = (const __nv_bfloat16*)d_in[4];
    p.xb = (const __nv_bfloat16*)d_in[5];
    p.out = (__nv_bfloat16*)d_out;
    if (ncl >= MINCL) {
        cfg.gridDim = dim3(8 * ncl);
        cudaLaunchKernelEx(&cfg, fused_decode_kernel<true>, p);
    } else {
        fused_decode_kernel<false><<<nsm, 256, SMEM_BYTES, cudaStreamPerThread>>>(p);
    }
}
```

```cpp
#include <cuda_runtime.h>
#include <cuda.h>
#include <cuda_bf16.h>
#include <stdint.h>

namespace {

constexpr int NH = 32, SK = 4096, DM = 576;
constexpr int KEYS = 128;
constexpr int UPP = SK / KEYS;
constexpr int NUK = 4 * NH * UPP;
constexpr int TILE_BYTES = KEYS * 256;
#define NWORK 2
constexpr int NW = NWORK;
constexpr int NBCTA = 32;
constexpr int MINCL = 15;
constexpr int NFIN = 72;
constexpr int SLOT = 32768;
constexpr int NSLOT = 6;
constexpr int BRING = 5;
constexpr int J0W = 5 * SLOT;
constexpr int MISC = NSLOT * SLOT + 4096;
constexpr int XP = 1168, CP = 1040, QP = 272;
constexpr int M_XA = MISC;
constexpr int M_XB = M_XA + 4 * XP;
constexpr int M_CH = M_XB + 4 * XP;
constexpr int M_CL = M_CH + 4 * CP;
constexpr int M_QB = M_CL + 4 * CP;
constexpr int M_QA = M_CH;
constexpr int M_J0 = M_QB + 4 * QP;
constexpr int M_P = M_J0 + 2048;
constexpr int M_ALPHA = M_P + 2560;
constexpr int M_OMEGA = M_ALPHA + 128;
constexpr int M_BAR = M_OMEGA + 128;
constexpr int M_HELP = M_BAR + 128;
#define PH 1
constexpr int F_W = 4 * SLOT;
constexpr int F_BF = (M_HELP + 128 + 255) / 256 * 256;
constexpr int F_RX = F_BF + 4096;
constexpr int F_BAR = F_RX + 2048;
constexpr int SMEM_BYTES = F_BAR + 64 + 64 * PH + 1024;
static_assert(SMEM_BYTES <= 232448 && M_BAR % 8 == 0 && M_QA % 16 == 0 && M_P % 16 == 0, "smem layout");
#define XW 2
#define X3 1
#define X3C 3
#define NEARLY 3
#define BD 5
#define FPF 3
#define FSLEEP 800
#define VS0 24
#define EARLY 100
#define ELOG 5
#define TPU 159
#define A0 3000
#define AJ 700
#define AR (AJ / 8 / PH)
#define PFN 96
#define PFS 128
#define PFC PFN
#define PFLD 0
#define PF0 128
#define PFOFF 0
#define CM2 10
#define AK 24
#define AC 0
#define BK 24
#define BC 0
#define B0 2500
#define BJ 700
#define BS (300 / PH)
#define BR (BJ / 8 / PH)
#define NPOLL 2
#define PGAP 200
static_assert(X3C <= 3 && NW == 2, "warp 2 of rank 7 is free");
static_assert(NW + XW <= 4 && NEARLY <= NW + XW && BD <= BRING, "slots 4 and 5 hold the finisher weights");
#define KMAX 4
#define VMAX 4
constexpr int KMIN = 2, VMIN = 0;
constexpr float SCALE = 0.08838834764831845f;
constexpr float LOG2E = 1.4426950408889634f;
constexpr unsigned SPIN_LIMIT = 1u << 24;

#define NREP 2
#define NREPC 1
constexpr int C_QUEUE = 0, C_KDONE = 1, C_BBAR = 3, C_LINES = 5;

struct Params {
    const char* pf;
    const __nv_bfloat16 *kc, *xa, *vc, *wo, *xb;
    __nv_bfloat16* out;
    CUtensorMap tm_j0;
    CUtensorMap tm_wq, tm_wuk, tm_ckv, tm_wuv, tm_wo;
    CUtensorMap tm_fa, tm_fb;
};

__device__ unsigned g_epoch;
__device__ unsigned g_ctl[2][C_LINES][32];
__device__ uint2 g_qll[4 * 2048];
__device__ uint2 g_scores[128 * SK / 4];
__device__ float2 g_stats[128 * UPP];
__device__ float4 g_oacc[128 * 32];
__device__ unsigned g_vdone[NREP * NH][32];
__device__ float4 g_octx[128 * 32];
__device__ unsigned g_cdone[NH][32];
__device__ unsigned long long g_dry[16][16];
__device__ uint4 g_qabs[4 * 8 * 4 * 4 * 32];
__device__ float2 g_bpart[NBCTA * NH * 256];
__device__ float2 g_bml[NBCTA * NH];
__device__ uint4 g_outb[NBCTA * NH * 36];

#define TS(i)
#define TSV(i, v)
#define LAND(i)
#define CLK(x)
#define ACC(a, x, y)

__device__ __forceinline__ uint32_t smem_u32(const void* p) { return (uint32_t)__cvta_generic_to_shared(p); }
__device__ __forceinline__ void mbar_init(uint32_t bar, uint32_t cnt) {
    asm volatile("mbarrier.init.shared::cta.b64 [%0], %1;" ::"r"(bar), "r"(cnt) : "memory");
}
__device__ __forceinline__ void mbar_expect_tx(uint32_t bar, uint32_t bytes) {
    asm volatile("mbarrier.arrive.expect_tx.shared::cta.b64 _, [%0], %1;" ::"r"(bar), "r"(bytes) : "memory");
}
__device__ __forceinline__ bool mbar_try(uint32_t bar, uint32_t parity) {
    uint32_t ok;
    asm volatile("{\n.reg .pred p;\nmbarrier.try_wait.parity.shared::cta.b64 p, [%1], %2;\nselp.u32 %0, 1, 0, p;\n}\n"
                 : "=r"(ok) : "r"(bar), "r"(parity) : "memory");
    return ok;
}
__device__ __forceinline__ void mbar_wait(uint32_t bar, uint32_t parity) {
    unsigned n = 0;
    while (!mbar_try(bar, parity)) { if (++n > SPIN_LIMIT) __trap(); }
}
__device__ __forceinline__ void mbar_spin(uint32_t bar) {
    asm volatile("{\n.reg .pred p;\n.reg .u32 n;\nmov.u32 n, 0;\nSPIN:\nmbarrier.test_wait.parity.shared::cta.b64 p, [%0], 0;\n@p bra.uni DONE;\n"
                 "add.u32 n, n, 1;\nsetp.lt.u32 p, n, 0x4000000;\n@p bra.uni SPIN;\ntrap;\nDONE:\n}" ::"r"(bar) : "memory");
}
__device__ __forceinline__ void bulk_load(uint32_t dst, const void* src, uint32_t bytes, uint32_t bar, uint64_t pol) {
    asm volatile("cp.async.bulk.shared::cluster.global.mbarrier::complete_tx::bytes.L2::cache_hint [%0], [%1], %2, [%3], %4;"
                 ::"r"(dst), "l"(src), "r"(bytes), "r"(bar), "l"(pol) : "memory");
}
__device__ __forceinline__ void tma3d(uint32_t dst, const CUtensorMap* tm, int c0, int c1, int c2, uint32_t bar, uint64_t pol) {
    asm volatile("cp.async.bulk.tensor.3d.shared::cluster.global.mbarrier::complete_tx::bytes.L2::cache_hint [%0], [%1, {%3,%4,%5}], [%2], %6;"
                 ::"r"(dst), "l"(tm), "r"(bar), "r"(c0), "r"(c1), "r"(c2), "l"(pol) : "memory");
}
__device__ __forceinline__ void l2_prefetch(const void* src, uint32_t bytes) {
    asm volatile("cp.async.bulk.prefetch.L2.global [%0], %1;" ::"l"(src), "r"(bytes) : "memory");
}
__device__ __forceinline__ void ldsm4(uint32_t (&r)[4], uint32_t addr) {
    asm volatile("ldmatrix.sync.aligned.m8n8.x4.shared.b16 {%0,%1,%2,%3}, [%4];"
                 : "=r"(r[0]), "=r"(r[1]), "=r"(r[2]), "=r"(r[3]) : "r"(addr));
}
__device__ __forceinline__ void ldsm4t(uint32_t (&r)[4], uint32_t addr) {
    asm volatile("ldmatrix.sync.aligned.m8n8.x4.trans.shared.b16 {%0,%1,%2,%3}, [%4];"
                 : "=r"(r[0]), "=r"(r[1]), "=r"(r[2]), "=r"(r[3]) : "r"(addr));
}
__device__ __forceinline__ void mma16816(float (&d)[4], const uint32_t (&a)[4], uint32_t b0, uint32_t b1) {
    asm("mma.sync.aligned.m16n8k16.row.col.f32.bf16.bf16.f32 {%0,%1,%2,%3}, {%4,%5,%6,%7}, {%8,%9}, {%0,%1,%2,%3};"
        : "+f"(d[0]), "+f"(d[1]), "+f"(d[2]), "+f"(d[3])
        : "r"(a[0]), "r"(a[1]), "r"(a[2]), "r"(a[3]), "r"(b0), "r"(b1));
}
__device__ __forceinline__ uint32_t lds32(uint32_t a) {
    uint32_t v;
    asm volatile("ld.shared.u32 %0, [%1];" : "=r"(v) : "r"(a));
    return v;
}
__device__ __forceinline__ unsigned ld_acquire(const unsigned* p) {
    unsigned v;
    asm volatile("ld.acquire.gpu.global.u32 %0, [%1];" : "=r"(v) : "l"(p) : "memory");
    return v;
}
__device__ __forceinline__ uint2 ld_relaxed8(const void* p) {
    uint2 v;
    asm volatile("ld.relaxed.gpu.global.v2.u32 {%0,%1}, [%2];" : "=r"(v.x), "=r"(v.y) : "l"(p) : "memory");
    return v;
}
__device__ __forceinline__ unsigned ld_relaxed4(const void* p) {
    unsigned v;
    asm volatile("ld.relaxed.gpu.global.u32 %0, [%1];" : "=r"(v) : "l"(p) : "memory");
    return v;
}
__device__ __forceinline__ unsigned atom_inc(unsigned* p) {
    unsigned v;
    asm volatile("atom.relaxed.gpu.global.inc.u32 %0, [%1], 0x7fffffff;" : "=r"(v) : "l"(p) : "memory");
    return v;
}
__device__ __forceinline__ unsigned long long ld_relaxed64(const void* p) {
    unsigned long long v;
    asm volatile("ld.relaxed.gpu.global.u64 %0, [%1];" : "=l"(v) : "l"(p) : "memory");
    return v;
}
__device__ __forceinline__ void st_relaxed64(void* p, unsigned long long v) {
    asm volatile("st.relaxed.gpu.global.u64 [%0], %1;" ::"l"(p), "l"(v) : "memory");
}
__device__ __forceinline__ float4 ld_relaxed16(const void* p) {
    float4 v;
    asm volatile("ld.relaxed.gpu.global.v4.f32 {%0,%1,%2,%3}, [%4];" : "=f"(v.x), "=f"(v.y), "=f"(v.z), "=f"(v.w) : "l"(p) : "memory");
    return v;
}
__device__ __forceinline__ uint32_t mapa(uint32_t a, uint32_t rank) {
    uint32_t r;
    asm("mapa.shared::cluster.u32 %0, %1, %2;" : "=r"(r) : "r"(a), "r"(rank));
    return r;
}
__device__ __forceinline__ uint32_t time_ns() { uint32_t t; asm volatile("mov.u32 %0, %globaltimer_lo;" : "=r"(t)); return t; }
__device__ __forceinline__ void fence_gpu() { asm volatile("fence.acq_rel.gpu;" ::: "memory"); }
__device__ __forceinline__ void red_add_u32(unsigned* p, unsigned v) {
    asm volatile("red.relaxed.gpu.global.add.u32 [%0], %1;" ::"l"(p), "r"(v) : "memory");
}
__device__ __forceinline__ void st_tagged2(void* p, float a, float b, unsigned tag) {
    const unsigned long long hi = (unsigned long long)tag << 32;
    asm volatile("st.relaxed.gpu.global.v2.b64 [%0], {%1,%2};" ::"l"(p), "l"(hi | __float_as_uint(a)), "l"(hi | __float_as_uint(b)) : "memory");
}
__device__ __forceinline__ ulonglong2 ld_tagged2(const void* p) {
    ulonglong2 v;
    asm volatile("ld.relaxed.gpu.global.v2.b64 {%0,%1}, [%2];" : "=l"(v.x), "=l"(v.y) : "l"(p) : "memory");
    return v;
}
__device__ __forceinline__ float4 atom_add_f4(void* p, float a, float b, float c, float d) {
    float4 r;
    asm volatile("atom.relaxed.gpu.global.add.v4.f32 {%0,%1,%2,%3}, [%4], {%5,%6,%7,%8};"
                 : "=f"(r.x), "=f"(r.y), "=f"(r.z), "=f"(r.w) : "l"(p), "f"(a), "f"(b), "f"(c), "f"(d) : "memory");
    return r;
}
__device__ __forceinline__ void red_release_cta_shared(uint32_t a, unsigned v) {
    asm volatile("red.release.cta.shared::cta.add.u32 [%0], %1;" ::"r"(a), "r"(v) : "memory");
}
__device__ __forceinline__ unsigned ld_acquire_cta_shared(uint32_t a) {
    unsigned v;
    asm volatile("ld.acquire.cta.shared::cta.u32 %0, [%1];" : "=r"(v) : "r"(a) : "memory");
    return v;
}
__device__ __forceinline__ void st_release_cta_shared(uint32_t a, unsigned v) {
    asm volatile("st.release.cta.shared::cta.u32 [%0], %1;" ::"r"(a), "r"(v) : "memory");
}
__device__ __forceinline__ void wait_count(const unsigned* p, unsigned target) {
    unsigned n = 0;
    while (ld_acquire(p) < target) { if (++n > SPIN_LIMIT) __trap(); }
}
__device__ __forceinline__ uint32_t pack_bf16(float lo, float hi) {
    uint32_t r;
    asm("cvt.rn.bf16x2.f32 %0, %1, %2;" : "=r"(r) : "f"(hi), "f"(lo));
    return r;
}
__device__ __forceinline__ float bf_lo(uint32_t v) { return __uint_as_float(v << 16); }
__device__ __forceinline__ float bf_hi(uint32_t v) { return __uint_as_float(v & 0xffff0000u); }
__device__ __forceinline__ float ex2(float x) { float y; asm("ex2.approx.ftz.f32 %0, %1;" : "=f"(y) : "f"(x)); return y; }
__device__ __forceinline__ float expsub(float a, float b) { return ex2((a - b) * LOG2E); }
__device__ __forceinline__ float warp_max(float v) {
#pragma unroll
    for (int m = 16; m; m >>= 1) v = fmaxf(v, __shfl_xor_sync(~0u, v, m));
    return v;
}
__device__ __forceinline__ float warp_sum(float v) {
#pragma unroll
    for (int m = 16; m; m >>= 1) v += __shfl_xor_sync(~0u, v, m);
    return v;
}
template <bool CLU>
__device__ __forceinline__ unsigned unit_block(int u) {
    const unsigned x = ((unsigned)u & (NUK - 1)) / UPP;
    const int lg = u < NUK ? min(KMAX, max(KMIN, 29 - __clz(x | 1))) : (CLU && (int)x >= 4 * VS0 ? 0 : min(VMAX, max(VMIN, 29 - __clz((127 - x) | 1))));
    const unsigned r = x & ((4u << lg) - 1);
    return ((x - r + (r & ((1u << lg) - 1)) * 4 + (r >> lg)) * UPP) | ((unsigned)u & (UPP - 1));
}
__device__ __forceinline__ const char* block_src(const void* base, unsigned blk) {
    const unsigned po = blk / UPP;
    return reinterpret_cast<const char*>(base) + (size_t)(((po & 3) * NH + (po >> 2)) * UPP + blk % UPP) * TILE_BYTES;
}

template <bool CLU>
__device__ __forceinline__ void a_worker(const Params& p, int un, bool once, bool pre, bool hold, int nstatic, uint32_t slot, uint32_t bar,
                                         uint32_t help, unsigned epoch, uint64_t pol) {
    constexpr int NU = 2 * NUK, NR = CLU ? NREPC : NREP;
    const int lane = threadIdx.x & 31, g = lane >> 2, t = lane & 3;
    const int li = lane & 7;
    uint32_t kaddr[4], vaddr[8];
    {
        const int e = (lane >> 3) & 1, kk = lane >> 4;
#pragma unroll
        for (int s = 0; s < 4; s++) kaddr[s] = slot + (16 * li + e) * 256 + ((2 * s + kk + li) & 7) * 16;
        const int vrow = 4 * (li >> 1) + (li & 1) + 2 * kk;
#pragma unroll
        for (int c = 0; c < 8; c++) vaddr[c] = slot + vrow * 256 + e * 128 + ((c + li) & 7) * 16;
#pragma unroll
        for (int c = 0; c < 8; c++) asm volatile("" : "+r"(vaddr[c]));
    }
    const uint32_t vmask = (g >> 1) != t ? 0u : ((g & 1) ? 0xffff0000u : 0xffffu);
    int kseen = -1;
    unsigned long long H0 = 0, H1 = 0;
    auto header = [&](int v, unsigned vb) {
        if (v >= NU) return;
        const void *a0, *a1;
        if (v < NUK) {
            const unsigned po = vb / UPP;
            a0 = g_qll + (po & 3) * 2048 + (po >> 2) * 64 + lane;
            a1 = reinterpret_cast<const uint2*>(a0) + 32;
        } else {
            const int half = vb / (NUK / 2);
            if (half > kseen) {
                unsigned n = 0;
                while (ld_acquire_cta_shared(help + 12 + 4 * half) == 0) { if (++n > (SPIN_LIMIT << 4)) __trap(); }
                kseen = half;
            }
            a0 = &g_scores[vb * (KEYS / 4) + lane];
            a1 = &g_stats[(vb / UPP) * UPP + lane];
        }
        H0 = ld_relaxed64(a0);
        H1 = ld_relaxed64(a1);
    };
    asm volatile("bar.sync 2, %0;" ::"n"(32 * (NW + XW + 1)) : "memory");
    epoch = __shfl_sync(~0u, epoch, 0);
    if (hold) { unsigned n = 0; while (ld_acquire_cta_shared(help + 24) < 2) { if (++n > (SPIN_LIMIT << 4)) __trap(); } }
    unsigned (*ctl)[32] = g_ctl[epoch & 1];
    const unsigned tag = epoch + 1;
    unsigned nxt = once ? NU : 0;
    int u = -1;
    unsigned bu = 0, bn = unit_block<CLU>(un);
    bool have = false;
    uint32_t phase = 0;
    unsigned kpend = 0;
    const unsigned zero = gridDim.x >> 24;
    uint32_t Q[16];
    float4 oret = make_float4(0.f, 0.f, 0.f, 0.f);
    while (true) {
        const char* nsrc = block_src(un < NUK ? p.kc : p.vc, bn);
        float4* odst = &g_oacc[(bu / UPP) * 32 + lane];
        unsigned* vdst = &g_vdone[(lane & (NR - 1)) * NH + bu / (4 * UPP)][0];
        float d[8][4];
        CLK(c1);
        asm volatile("" : "+l"(odst));
        if (u >= NUK) {
#pragma unroll
            for (int j = 0; j < 8; j++) { d[j][0] = d[j][1] = d[j][2] = d[j][3] = 0.f; }
            mbar_wait(bar, phase);
            LAND(NUK + bu);
            uint32_t a[2][8][4];
#pragma unroll
            for (int c = 0; c < 8; c++) ldsm4t(a[0][c], vaddr[c]);
#pragma unroll
            for (int j = 0; j < 8; j++) {
                if (j < 7) {
#pragma unroll
                    for (int c = 0; c < 8; c++) ldsm4t(a[(j + 1) & 1][c], vaddr[c] + (j + 1) * 4096);
                }
#pragma unroll
                for (int c = 0; c < 8; c++) mma16816(d[c], a[j & 1][c], Q[2 * j], Q[2 * j + 1]);
            }
            float o[4];
#pragma unroll
            for (int r = 0; r < 2; r++) {
                o[2 * r] = d[0][2 * r] + d[7][2 * r + 1];
                o[2 * r + 1] = d[0][2 * r + 1] + d[1][2 * r];
#pragma unroll
                for (int k = 1; k < 4; k++) {
                    const int src = (lane & 28) | ((t - k) & 3);
                    o[2 * r] += __shfl_sync(~0u, d[2 * k][2 * r] + d[2 * k - 1][2 * r + 1], src);
                    o[2 * r + 1] += __shfl_sync(~0u, d[2 * k][2 * r + 1] + d[2 * k + 1][2 * r], src);
                }
            }
            oret = atom_add_f4(odst, o[0], o[1], o[2], o[3]);
        } else if (u >= 0) {
#pragma unroll
            for (int j = 0; j < 8; j++) { d[j][0] = d[j][1] = d[j][2] = d[j][3] = 0.f; }
            mbar_wait(bar, phase);
            LAND(bu);
            uint32_t a[2][8][4];
#pragma unroll
            for (int j = 0; j < 8; j++) ldsm4(a[0][j], kaddr[0] + (4 * (j & 3) + 2 * (j >> 2)) * 256);
#pragma unroll
            for (int s = 0; s < 8; s++) {
                if (s < 7) {
#pragma unroll
                    for (int j = 0; j < 8; j++)
                        ldsm4(a[(s + 1) & 1][j], kaddr[(s + 1) & 3] + (4 * (j & 3) + 2 * (j >> 2)) * 256 + ((s + 1) >> 2) * 128);
                }
#pragma unroll
                for (int j = 0; j < 8; j++)
                    mma16816(d[j], a[s & 1][j], Q[(s & 4) * 2 + ((2 * s - 2 * j) & 7)], Q[(s & 4) * 2 + ((2 * s + 1 - 2 * j) & 7)]);
            }
        }
        if (u >= 0) phase ^= 1;
        CLK(c2b);
        if (un < NU && lane == 0) {
            if (!once) nxt = atom_inc(&ctl[C_QUEUE][0]);
            if (u >= 0 || !pre) {
                mbar_expect_tx(bar, TILE_BYTES);
                bulk_load(slot, nsrc, TILE_BYTES, bar, pol);
            }
        }
        const uint32_t tk = clock();
        CLK(c3);
        if ((unsigned)u < (unsigned)NUK) {
            const int j0 = (t - (g >> 1)) & 3;
            float v[4];
#pragma unroll
            for (int q = 0; q < 4; q++) {
                const int jq = (q >> 1) * 4, e = (q & 1) * 2;
                const float x0 = (g & 1) ? d[jq + 0][e + 1] : d[jq + 0][e];
                const float x1 = (g & 1) ? d[jq + 1][e + 1] : d[jq + 1][e];
                const float x2 = (g & 1) ? d[jq + 2][e + 1] : d[jq + 2][e];
                const float x3 = (g & 1) ? d[jq + 3][e + 1] : d[jq + 3][e];
                const float y0 = (j0 & 1) ? x1 : x0, y1 = (j0 & 1) ? x3 : x2;
                v[q] = (j0 & 2) ? y1 : y0;
            }
            const uint32_t r0 = pack_bf16(v[0], v[1]), r1 = pack_bf16(v[2], v[3]);
            const uint32_t s0 = pack_bf16(bf_lo(r0) * SCALE, bf_hi(r0) * SCALE);
            const uint32_t s1 = pack_bf16(bf_lo(r1) * SCALE, bf_hi(r1) * SCALE);
            g_scores[bu * (KEYS / 4) + 4 * g + j0] = make_uint2(s0, s1);
            const float f0 = bf_lo(s0), f1 = bf_hi(s0), f2 = bf_lo(s1), f3 = bf_hi(s1);
            const float m = warp_max(fmaxf(fmaxf(f0, f1), fmaxf(f2, f3)));
            const float l = warp_sum((expsub(f0, m) + expsub(f1, m)) + (expsub(f2, m) + expsub(f3, m)));
            if (lane == 0) g_stats[bu] = make_float2(m, l);
            kpend++;
            if (un / (NUK / 2) != u / (NUK / 2)) {
                __syncwarp();
                if (lane == 0) {
                    red_release_cta_shared(help + 4 * (u / (NUK / 2)), kpend);
                    if (un >= NUK) red_release_cta_shared(help + 8, 1u);
                }
                kpend = 0;
            }
        }
        CLK(c4);
        int unn = NU;
        if (un < NU) {
            unsigned n = 0;
            while (true) {
                if (!have) header(un, bn);
                if (un >= NUK || __all_sync(~0u, (uint32_t)(H0 >> 32) == tag && (uint32_t)(H1 >> 32) == tag)) break;
                if (++n > SPIN_LIMIT) __trap();
                have = false;
            }
            if (un >= NUK) {
                const uint32_t s0 = (uint32_t)H0, s1 = (uint32_t)(H0 >> 32);
                const float mu = __uint_as_float((uint32_t)H1);
                const float m = warp_max(mu);
                const float l = warp_sum(__uint_as_float((uint32_t)(H1 >> 32)) * expsub(mu, m));
                const float inv = 1.0f / l;
                const uint32_t w0 = pack_bf16(expsub(bf_lo(s0), m) * inv, expsub(bf_hi(s0), m) * inv);
                const uint32_t w1 = pack_bf16(expsub(bf_lo(s1), m) * inv, expsub(bf_hi(s1), m) * inv);
#pragma unroll
                for (int j = 0; j < 8; j++) {
                    Q[2 * j] = __shfl_sync(~0u, w0, 4 * j + t) & vmask;
                    Q[2 * j + 1] = __shfl_sync(~0u, w1, 4 * j + t) & vmask;
                }
            } else {
#pragma unroll
                for (int j = 0; j < 8; j++) {
                    const int src = (((j + g) & 7) << 2) + t;
                    Q[j] = __shfl_sync(~0u, (uint32_t)H0, src);
                    Q[8 + j] = __shfl_sync(~0u, (uint32_t)H1, src);
                }
            }
            unn = nstatic + (int)__shfl_sync(~0u, nxt, 0);
            if (CLU && ((NU - EARLY - unn) & ~(7 << ELOG)) == 0 && lane < MINCL)
                st_relaxed64(&g_dry[lane][(NU - EARLY - unn) >> ELOG],
                             (time_ns() - (((uint32_t)clock() - tk) >> 1) + (NU - unn) * TPU / 16) | (unsigned long long)tag << 32);
        }
        if (u >= NUK && lane < NR)
            red_add_u32(vdst,
                        1u + ((__float_as_uint(oret.x) | __float_as_uint(oret.y) | __float_as_uint(oret.z) | __float_as_uint(oret.w)) & zero));
        if (un >= NU) break;
        bu = bn;
        have = !(un < NUK && unn >= NUK && !(un >= NUK / 2 && unn < NUK + NUK / 2));
        bn = unit_block<CLU>(unn);
        if (have) header(unn, bn);
        u = un;
        un = unn;
    }
}

__device__ __forceinline__ void k_helper(uint32_t help, unsigned epoch) {
    if ((threadIdx.x & 31) != 0) return;
    unsigned (*ctl)[32] = g_ctl[epoch & 1];
    unsigned sent0 = 0, sent1 = 0, n = 0;
    int seen = 0;
    bool fin = false;
    while (!fin || seen < 2) {
        if (!fin) {
            fin = ld_acquire_cta_shared(help + 8) == NW + XW;
            const unsigned c0 = ld_acquire_cta_shared(help), c1 = ld_acquire_cta_shared(help + 4);
            if (c0 != sent0 || c1 != sent1) {
                fence_gpu();
                if (c0 != sent0) red_add_u32(&ctl[C_KDONE][0], c0 - sent0);
                if (c1 != sent1) red_add_u32(&ctl[C_KDONE + 1][0], c1 - sent1);
                sent0 = c0; sent1 = c1;
            }
        }
        if (seen < 2 && ld_acquire(&ctl[C_KDONE + seen][0]) >= NUK / 2) {
            st_release_cta_shared(help + 12 + 4 * seen, 1u);
            seen++;
        } else {
            __nanosleep(300);
        }
        if (++n > SPIN_LIMIT) __trap();
    }
}

__device__ __forceinline__ void v_poller(uint32_t sbase, int f, int w) {
    constexpr int HL = NH;
    const int lane = threadIdx.x & 31;
    const unsigned (*cp)[32] = &g_vdone[((f * NPOLL + w) % NREP) * NH];
    unsigned n = 0;
    while (ld_acquire_cta_shared(sbase + M_HELP + 12) == 0) { __nanosleep(1000); if (++n > SPIN_LIMIT) __trap(); }
    int h = 0;
    bool fast = false;
    while (h < HL) {
        const unsigned r = __ballot_sync(~0u, ld_acquire(&cp[min(h + (lane & 3), HL - 1)][0]) >= 4 * UPP) & 15u;
        if (r & 1) {
            h = min(HL, h + __ffs(~r) - 1);
            __syncwarp();
            if (lane == 0) asm volatile("red.release.cta.shared::cta.max.u32 [%0], %1;" ::"r"(sbase + M_HELP + 20), "r"(h) : "memory");
        }
        if (h < HL - 4) {
            __nanosleep(h ? 300 : 1000);
        } else if (!fast) {
            fast = true;
            const long long t0 = clock64();
            while (clock64() - t0 < w * PGAP) {}
        }
        if (++n > SPIN_LIMIT) __trap();
    }
}
__device__ __forceinline__ void finisher(const Params& p, uint32_t sbase, int f) {
    constexpr int HL = NH;
    const int lane = threadIdx.x & 31;
    {
        const char* wg = reinterpret_cast<const char*>(p.wo);
        const uint32_t dst = sbase + 4 * SLOT + (16 * (lane & 7) + (lane >> 3)) * 16;
#pragma unroll 1
        for (int h = -FPF - 4; h < HL; h++) {
            if (lane == 0 && (unsigned)(h + FPF) < (unsigned)HL) l2_prefetch(wg + (size_t)(h + FPF) * 147456 + f * 2048, 2048);
            if (h >= 0) {
#pragma unroll
                for (int r = 0; r < 4; r++)
                    asm volatile("cp.async.cg.shared.global [%0], [%1], 16;" ::"r"(dst + h * 2048 + ((r & 1) * 4 + (r >> 1) * 8) * 16),
                                 "l"(wg + (size_t)(h * 128 + r * 32 + lane) * (DM * 2) + f * 16) : "memory");
            }
            __nanosleep(FSLEEP);
        }
        asm volatile("cp.async.wait_all;" ::: "memory");
        __syncwarp();
    }
    TS(11);
    const float4* vec = g_oacc + ((lane >> 2) & 3) * 32 + (lane >> 4) * 16 + (lane & 3);
    float acc[2][2][4];
#pragma unroll
    for (int i = 0; i < 16; i++) acc[i >> 3][(i >> 2) & 1][i & 3] = 0.f;
    uint32_t* outp = reinterpret_cast<uint32_t*>(p.out + (lane >> 2) * (2 * DM) + f * 8 + (lane & 3) * 2);
    uint32_t wa = sbase + 4 * SLOT + lane * 16;
    auto project = [&](const float4 (&x)[4], const uint32_t (&w)[4][4]) {
#pragma unroll
        for (int s = 0; s < 4; s++) {
            const uint32_t a[4] = {pack_bf16(x[s].x, x[s].y), 0u, pack_bf16(x[s].z, x[s].w), 0u};
            mma16816(acc[0][s & 1], a, w[s >> 1][(s & 1) * 2], w[s >> 1][(s & 1) * 2 + 1]);
            mma16816(acc[1][s & 1], a, w[2 + (s >> 1)][(s & 1) * 2], w[2 + (s >> 1)][(s & 1) * 2 + 1]);
        }
    };
    int h = 0;
    unsigned n = 0;
    while (h < HL) {
        uint32_t w[4][4];
#pragma unroll
        for (int q = 0; q < 4; q++) ldsm4t(w[q], wa + q * 512);
        int ready;
        while ((ready = ld_acquire_cta_shared(sbase + M_HELP + 20)) <= h) {
            if (h < HL - 3) __nanosleep(100);
            if (++n > (SPIN_LIMIT << 4)) __trap();
        }
        float4 x[4], y[4];
#pragma unroll
        for (int s = 0; s < 4; s++) x[s] = ld_relaxed16(vec + s * 4);
        const bool two = ready > h + 1;
        if (two) {
#pragma unroll
            for (int s = 0; s < 4; s++) y[s] = ld_relaxed16(vec + 128 + s * 4);
        }
        project(x, w);
        if (two) {
#pragma unroll
            for (int q = 0; q < 4; q++) ldsm4t(w[q], wa + 2048 + q * 512);
            project(y, w);
        }
        const int nr = two ? 2 : 1;
        h += nr;
        vec += nr * 128;
        wa += nr * 2048;
        const float o0 = acc[0][0][0] + acc[0][1][0] + __shfl_down_sync(~0u, acc[1][0][0] + acc[1][1][0], 16);
        const float o1 = acc[0][0][1] + acc[0][1][1] + __shfl_down_sync(~0u, acc[1][0][1] + acc[1][1][1], 16);
        asm volatile("{\n.reg .pred p;\nsetp.ne.u32 p, %2, 0;\n@p st.global.u32 [%0], %1;\n}" ::"l"(outp), "r"(pack_bf16(o0, o1)),
                     "r"((uint32_t)(lane < 16 && h == NH)) : "memory");
    }
}

__device__ __noinline__ void f_collect(const unsigned (*flag)[32], unsigned full, const float4* src, unsigned todo, uint32_t sbase) {
    const int lane = threadIdx.x & 31, g = lane >> 2, t = lane & 3;
    const bool last = todo != 15;
    unsigned n = 0;
    while (todo) {
        const unsigned v = ld_acquire(&flag[t][0]);
        unsigned m = __ballot_sync(~0u, v == full) & todo;
        if (m == 0) {
            if (!last || __shfl_sync(~0u, v, 0) == 0) __nanosleep(200);
            if (++n > SPIN_LIMIT) __trap();
            continue;
        }
        __syncwarp();
        todo ^= m;
        if (last) TS(16);
        do {
            const int h0 = __ffs(m) - 1, h1 = 31 - __clz(m);
            m &= ~((1u << h0) | (1u << h1));
            float4 x[8];
#pragma unroll
            for (int b = 0; b < 8; b++) x[b] = ld_relaxed16(src + ((b & 4) ? h1 : h0) * 128 + (b & 3) * 32 + lane);
#pragma unroll
            for (int b = 0; b < 8; b++) {
                const uint32_t lo = pack_bf16(x[b].x, x[b].y), hi = pack_bf16(x[b].z, x[b].w);
                const uint32_t o = __shfl_xor_sync(~0u, (g & 1) ? lo : hi, 4);
                const uint32_t e0 = (g & 1) ? o : lo, e1 = (g & 1) ? hi : o;
                asm volatile("st.shared.v2.u32 [%0], {%1,%2};"
                             ::"r"(sbase + F_BF + ((b & 4) ? h1 : h0) * 1024 + t * 256 + ((b ^ t) & 3) * 64 + g * 8),
                               "r"(__byte_perm(e0, e1, 0x5410)), "r"(__byte_perm(e0, e1, 0x7632)) : "memory");
            }
            __syncwarp();
            if (lane < (h0 == h1 ? 1 : 2))
                asm volatile("mbarrier.arrive.shared::cta.b64 _, [%0];" ::"r"(sbase + F_BAR + 32 + (lane ? h1 : h0) * 8) : "memory");
        } while (m);
    }
    if (last) TS(17);
}

__device__ __noinline__ void f_project(const CUtensorMap* tm, int panel, int rank, int sl, int j, int delay, int step, unsigned tag, uint32_t sbase, uint64_t pol) {
    const int lane = threadIdx.x & 31, g = lane >> 2, t = lane & 3;
    const uint32_t wb = sbase + F_W - sl * 2 * SLOT, bars = sbase + F_BAR + 64 + sl * 32 * PH;
    const uint32_t wa = wb + ((lane & 7) + (lane >> 4) * 8) * 128 + (((2 * j + ((lane >> 3) & 1)) ^ (lane & 7)) * 16);
    const uint32_t ba = sbase + F_BF + (g & 3) * 64 + t * 16;
    const uint32_t rdst = mapa(sbase + F_RX + sl * 1024 + rank * 128 + g * 16 + (t & 1) * 8, 2 * j + (t >> 1));
    const uint32_t rbar = mapa(sbase + F_BAR + 16 + sl * 8, 2 * j + (t >> 1));
    unsigned n = 0;
    if (threadIdx.x >= 224) {
        if (lane == 0) asm volatile("prefetch.tensormap [%0];" ::"l"(tm) : "memory");
        unsigned long long v;
        while (!__all_sync(~0u, (v = ld_relaxed64(&g_dry[blockIdx.x >> 3][g])) >> 32 == tag)) {
            __nanosleep(200);
            if (++n > SPIN_LIMIT) __trap();
        }
        const uint32_t t0 = __shfl_sync(~0u, (uint32_t)v, 0);
        const uint32_t t1 = t0 + (__reduce_add_sync(~0u, (int)((uint32_t)v - t0)) >> 5);
        if (lane == 0) asm volatile("st.shared.u32 [%0+8], %1;\nmbarrier.arrive.shared::cta.b64 _, [%0];" ::"r"(sbase + F_BAR), "r"(t1) : "memory");
        TS(22);
    }
    mbar_wait(sbase + F_BAR, 0);
    if (lane == 0) {
        uint32_t due = lds32(sbase + F_BAR + 8) + delay;
#pragma unroll 1
        for (int q = j * PH; q < (j + 1) * PH; q++, due += step) {
            mbar_expect_tx(bars + q * 8, 16384 / PH);
            while ((int)(time_ns() - due) < 0) {}
            tma3d(wb + q * (16384 / PH), tm, 0, rank * 512 + q * (128 / PH), panel, bars + q * 8, pol);
        }
    }
    __syncwarp();
    TS(18);
#define NCH 2
    float acc[4][4];
#pragma unroll
    for (int i = 0; i < 16; i++) acc[i >> 2][i & 3] = 0.f;
    const bool up = t & 2;
#pragma unroll 1
    for (int h = 0; h < 4; h++) {
        uint32_t wp = wa + h * 16384, bar = bars + h * PH * 8, last = h == 3;
        mbar_spin(sbase + F_BAR + 32 + h * 8);
        uint32_t bf[4][4];
#pragma unroll
        for (int s = 0; s < 4; s++)
            asm volatile("ld.shared.v4.u32 {%0,%1,%2,%3}, [%4];" : "=r"(bf[s][0]), "=r"(bf[s][1]), "=r"(bf[s][2]), "=r"(bf[s][3])
                         : "r"(((ba + h * 1024) ^ (s * 64)) + s * 256) : "memory");
        asm volatile("" : "+r"(wp), "+r"(bar), "+r"(last));
#pragma unroll
        for (int q = 0; q < PH; q++) {
            mbar_spin(bar + q * 8);
            if (h == 3 && q == PH - 1) TS(19);
            uint32_t a[8 / PH][4];
#pragma unroll
            for (int s = 0; s < 8 / PH; s++) ldsm4t(a[s], wp + (q * (8 / PH) + s) * 2048);
#pragma unroll
            for (int s = 0; s < 8 / PH; s++) {
                const int k = q * (8 / PH) + s;
                mma16816(acc[s & (NCH - 1)], a[s], bf[k & 3][(k >> 2) * 2], bf[k & 3][(k >> 2) * 2 + 1]);
            }
        }
        float v0 = up ? acc[0][2] + acc[1][2] : acc[0][0] + acc[1][0], v1 = up ? acc[0][3] + acc[1][3] : acc[0][1] + acc[1][1];
        if (NCH == 4) {
            v0 = (v0 + (up ? acc[2][2] : acc[2][0])) + (up ? acc[3][2] : acc[3][0]);
            v1 = (v1 + (up ? acc[2][3] : acc[2][1])) + (up ? acc[3][3] : acc[3][1]);
        }
        asm volatile("{\n.reg .pred p;\nsetp.ne.u32 p, %4, 0;\n"
                     "@p st.async.weak.shared::cluster.mbarrier::complete_tx::bytes.v2.b32 [%0], {%1,%2}, [%3];\n}"
                     ::"r"(rdst), "r"(__float_as_uint(v0)), "r"(__float_as_uint(v1)), "r"(rbar), "r"(last) : "memory");
    }
    TS(20);
}

__device__ __noinline__ void f_receive(__nv_bfloat16* out, int sl, bool dry, uint32_t sbase) {
    const int lane = threadIdx.x & 31;
    out += (lane & 3) * (2 * DM) + (lane >> 2);
    uint32_t src = sbase + F_RX + sl * 1024 + lane * 4;
    asm volatile("" : "+l"(out), "+r"(src));
    asm volatile("{\n.reg .pred p;\n.reg .u32 n;\nmov.u32 n, 0;\nSPIN:\nmbarrier.test_wait.parity.acquire.cluster.shared::cta.b64 p, [%0], 0;\n"
                 "@p bra.uni DONE;\nadd.u32 n, n, 1;\nsetp.lt.u32 p, n, 0x4000000;\n@p bra.uni SPIN;\ntrap;\nDONE:\n}"
                 ::"r"(sbase + F_BAR + (dry ? 0 : 16 + sl * 8)) : "memory");
    float v[8];
#pragma unroll
    for (int r = 0; r < 8; r++) asm volatile("ld.shared.f32 %0, [%1];" : "=f"(v[r]) : "r"(src + r * 128) : "memory");
    const float o = ((v[0] + v[1]) + (v[2] + v[3])) + ((v[4] + v[5]) + (v[6] + v[7]));
    asm volatile("{\n.reg .pred p;\nsetp.eq.u32 p, %2, 0;\n@p st.global.u16 [%0], %1;\n}"
                 ::"l"(out), "h"((unsigned short)pack_bf16(o, 0.f)), "r"((uint32_t)dry) : "memory");
    TS(15);
}

__device__ __forceinline__ void b_final(const Params& p, uint32_t sbase, int blk, unsigned epoch, uint64_t pol) {
    const int warp = threadIdx.x >> 5;
    const int rank = blk & 7, sl = warp >> 2, panel = (blk >> 3) * 2 + sl;
    asm volatile("barrier.cluster.wait.acquire.aligned;" ::: "memory");
    if (warp == 0) f_collect(&g_cdone[4 * rank], epoch + 1, &g_octx[4 * rank * 128], 15, sbase);
    if ((warp & 3) == 0) {
        mbar_wait(sbase + F_BAR, 0);
        f_receive(p.out, sl, true, sbase);
    }
    f_project(&p.tm_fb, panel, rank, sl, warp & 3, B0 + (warp & 3) * BJ + sl * BS + rank * BR - max(0, (warp & 3) * 8 + rank - BK) * BC, BJ / PH, epoch + 1, sbase, pol);
    if ((warp & 3) == 0) f_receive(p.out + DM + panel * 64 + rank * 8, sl, false, sbase);
}

constexpr int BS_WUK = 5, BS_Q = 9, BS_CKV = 11, BS_PART = 27, BS_WUV = 29, BS_END = 33;

__device__ __noinline__ void b_issue(const Params& p, int n, int bi, uint32_t sbase, uint64_t pol) {
    if (n >= BS_END || (n >= BS_Q && n < BS_CKV) || (n >= BS_PART && n < BS_WUV)) return;
    const uint32_t bar = sbase + M_BAR + (NSLOT + n % BRING) * 8;
    const CUtensorMap* tm;
    int row, panel = 2 * bi;
    if (n < BS_WUK) { tm = &p.tm_wq; row = n * 128; }
    else if (n < BS_Q) { tm = &p.tm_wuk; row = (n - BS_WUK) * 128; }
    else if (n < BS_PART) {
        tm = &p.tm_ckv; panel = 0;
        row = (bi >> 3) * SK + ((n - BS_CKV) * 8 + (bi & 7)) * 32;
    }
    else { tm = &p.tm_wuv; row = (n - BS_WUV) * 128; }
    mbar_expect_tx(bar, n == 0 ? 32768 + 4 * 1152 : 32768);
    tma3d(sbase + (n % BRING) * SLOT, tm, 0, row, panel, bar, pol);
}
__device__ __forceinline__ void b_issue_xchg(int n, const void* src, uint32_t sbase, uint64_t pol) {
    asm volatile("fence.proxy.async;" ::: "memory");
#pragma unroll
    for (int i = 0; i < 2; i++) {
        const uint32_t bar = sbase + M_BAR + (NSLOT + (n + i) % BRING) * 8;
        mbar_expect_tx(bar, 32768);
        bulk_load(sbase + ((n + i) % BRING) * SLOT, reinterpret_cast<const char*>(src) + i * 32768, 32768, bar, pol);
    }
}
__device__ __forceinline__ void b_wait(int n, uint32_t sbase) {
    mbar_wait(sbase + M_BAR + (NSLOT + n % BRING) * 8, (n / BRING) & 1);
}

__device__ __noinline__ void b_gemm(const Params& p, uint32_t sbase, int n0, int n1, int ktot, uint32_t xh, uint32_t xl, int pitch,
                                    int bi, uint64_t pol) {
    const int tid = threadIdx.x, warp = tid >> 5, lane = tid & 31, g = lane >> 2, t = lane & 3;
    const uint32_t woff = (warp >> 2) * 16384 + (lane & 15) * 128 + ((((warp & 3) * 2 + (lane >> 4)) ^ (lane & 7)) * 16);
    const uint32_t xoff = (g & 3) * pitch + t * 4;
    float acc[2][4];
#pragma unroll
    for (int i = 0; i < 8; i++) acc[i >> 2][i & 3] = 0.f;
#pragma unroll 1
    for (int n = n0; n < n1; n++) {
        b_wait(n, sbase);
        const uint32_t slot = sbase + (n % BRING) * SLOT + woff;
        const int k0 = (n - n0) * 128;
        const int ns = min(8, (ktot - k0) >> 4);
#pragma unroll 2
        for (int s = 0; s < ns; s++) {
            uint32_t a[4], w[4];
            const uint32_t xo = xoff + (k0 + 16 * s) * 2;
            a[0] = lds32(xh + xo); a[2] = lds32(xh + xo + 16);
            a[1] = xl ? lds32(xl + xo) : 0u; a[3] = xl ? lds32(xl + xo + 16) : 0u;
            ldsm4t(w, slot + s * 2048);
            mma16816(acc[0], a, w[0], w[1]);
            mma16816(acc[1], a, w[2], w[3]);
        }
        __syncthreads();
        if (tid == 0) b_issue(p, n + BD, bi, sbase, pol);
    }
    if (g < 4) {
#pragma unroll
        for (int j = 0; j < 2; j++)
            asm volatile("st.shared.u32 [%0], %1;" ::"r"(sbase + M_QB + g * QP + (warp * 16 + j * 8 + t * 2) * 2),
                         "r"(pack_bf16(acc[j][0] + acc[j][2], acc[j][1] + acc[j][3])) : "memory");
    }
    __syncthreads();
}

__device__ __forceinline__ void b_exchange(unsigned* c, int n, const void* src, uint32_t sbase, uint64_t pol) {
    TS(n == BS_Q ? 24 : 28);
    __syncthreads();
    if (threadIdx.x == 0) {
        TS(n == BS_Q ? 25 : 29);
        fence_gpu();
        TS(n == BS_Q ? 26 : 30);
        red_add_u32(c, 1u);
        wait_count(c, NBCTA);
        TS(n == BS_Q ? 27 : 31);
        b_issue_xchg(n, src, sbase, pol);
    }
}

template <bool CLU>
__device__ __noinline__ void b_chain(const Params& p, char* smem, uint32_t sbase, int bi, unsigned epoch, uint64_t pol) {
    const int tid = threadIdx.x, warp = tid >> 5, lane = tid & 31, g = lane >> 2, t = lane & 3;
    unsigned (*ctl)[32] = g_ctl[epoch & 1];
    float* red = reinterpret_cast<float*>(smem + 5 * SLOT);
    __syncthreads();
    b_gemm(p, sbase, 0, BS_WUK, DM, sbase + M_XB, 0, XP, bi, pol);
    TS(6);
    {
        uint32_t Q[16];
#pragma unroll
        for (int c = 0; c < 16; c++) Q[c] = lds32(sbase + M_QB + (g & 3) * QP + c * 16 + t * 4);
        float* qa = reinterpret_cast<float*>(smem + M_QA);
#pragma unroll 1
        for (int n = BS_WUK; n < BS_Q; n++) {
            b_wait(n, sbase);
            const uint32_t base = sbase + (n % BRING) * SLOT + (warp * 16 + (lane & 15)) * 128;
            float d[2][4];
#pragma unroll
            for (int i = 0; i < 8; i++) d[i >> 2][i & 3] = 0.f;
#pragma unroll
            for (int s = 0; s < 8; s++) {
                uint32_t a[4];
                ldsm4(a, base + (s >> 2) * 16384 + (((2 * (s & 3) + (lane >> 4)) ^ (lane & 7)) * 16));
                mma16816(d[s & 1], a, Q[2 * s], Q[2 * s + 1]);
            }
            const int c = (n - BS_WUK) * 128 + warp * 16 + g + 8 * (t >> 1);
            qa[(2 * (t & 1)) * 512 + c] = (t & 2) ? d[0][2] + d[1][2] : d[0][0] + d[1][0];
            qa[(2 * (t & 1) + 1) * 512 + c] = (t & 2) ? d[0][3] + d[1][3] : d[0][1] + d[1][1];
            __syncthreads();
            if (tid == 0) b_issue(p, n + BD, bi, sbase, pol);
        }
#pragma unroll 1
        for (int r = 0; r < 2; r++) {
            const int id = tid + r * 256;
            const int b = id >> 7, c0 = ((id >> 2) & 31) * 16 + (id & 3) * 2;
            const float2 u0 = *reinterpret_cast<const float2*>(qa + b * 512 + c0);
            const float2 u1 = *reinterpret_cast<const float2*>(qa + b * 512 + c0 + 8);
            const uint32_t h0 = pack_bf16(u0.x, u0.y), h1 = pack_bf16(u1.x, u1.y);
            const uint32_t l0 = pack_bf16(u0.x - bf_lo(h0), u0.y - bf_hi(h0)), l1 = pack_bf16(u1.x - bf_lo(h1), u1.y - bf_hi(h1));
            g_qabs[((id >> 2) * 4 + (bi >> 3)) * 32 + (bi & 7) * 4 + (id & 3)] = make_uint4(h0, l0, h1, l1);
        }
    }
    b_exchange(&ctl[C_BBAR][0], BS_Q, &g_qabs[(bi >> 3) * 4096], sbase, pol);
    {
        uint32_t qf[4][4][4];
        b_wait(BS_Q + (warp >> 2), sbase);
        TS(7);
        {
            const uint4* qs = reinterpret_cast<const uint4*>(smem + ((BS_Q + (warp >> 2)) % BRING) * SLOT) + (warp & 3) * 512 + lane;
#pragma unroll
            for (int s = 0; s < 4; s++)
#pragma unroll
                for (int i = 0; i < 4; i++) {
                    const uint4 v = qs[(s * 4 + i) * 32];
                    qf[i][s][0] = v.x; qf[i][s][1] = v.y; qf[i][s][2] = v.z; qf[i][s][3] = v.w;
                }
        }
        __syncthreads();
        if (tid == 0) { b_issue(p, BS_Q + BD, bi, sbase, pol); b_issue(p, BS_Q + 1 + BD, bi, sbase, pol); }
        float acc[2][8][4];
#pragma unroll
        for (int i = 0; i < 2; i++)
#pragma unroll
            for (int j = 0; j < 8; j++) { acc[i][j][0] = acc[i][j][1] = acc[i][j][2] = acc[i][j][3] = 0.f; }
        float mrun = -INFINITY, lrun = 0.f;
        const int head = tid >> 3, kq = tid & 7;
        float* alpha = reinterpret_cast<float*>(smem + M_ALPHA);
        for (int n = BS_CKV; n < BS_PART; n++) {
            b_wait(n, sbase);
            const uint32_t slot = sbase + (n % BRING) * SLOT;
            float sc[4][4][4];
#pragma unroll
            for (int i = 0; i < 4; i++)
#pragma unroll
                for (int j = 0; j < 4; j++) { sc[i][j][0] = sc[i][j][1] = sc[i][j][2] = sc[i][j][3] = 0.f; }
#pragma unroll
            for (int j = 0; j < 4; j++)
#pragma unroll
                for (int sp = 0; sp < 2; sp++) {
                    uint32_t bf[4];
                    ldsm4(bf, slot + warp * 4096 + (8 * j + (lane & 7)) * 128 + (((4 * sp + (lane >> 3)) ^ (lane & 7)) * 16));
#pragma unroll
                    for (int i = 0; i < 4; i++) {
                        mma16816(sc[i][j], qf[i][2 * sp], bf[0], bf[1]);
                        mma16816(sc[i][j], qf[i][2 * sp + 1], bf[2], bf[3]);
                    }
                }
#pragma unroll
            for (int i = 0; i < 4; i++)
#pragma unroll
                for (int j = 0; j < 4; j++)
                    *reinterpret_cast<float2*>(red + warp * 1024 + (8 * i + g) * 32 + ((8 * j) ^ (8 * (g & 3))) + 2 * t) =
                        make_float2(sc[i][j][0] + sc[i][j][2], sc[i][j][1] + sc[i][j][3]);
            __syncthreads();
            if (tid == 0 && n > BS_CKV) b_issue(p, n - 1 + BD, bi, sbase, pol);
            {
                float4 s = make_float4(0.f, 0.f, 0.f, 0.f);
#pragma unroll
                for (int w = 0; w < 8; w++) {
                    const float4 v = *reinterpret_cast<const float4*>(red + w * 1024 + head * 32 + ((4 * kq) ^ (8 * (head & 3))));
                    s.x += v.x; s.y += v.y; s.z += v.z; s.w += v.w;
                }
                const uint32_t r0 = pack_bf16(s.x, s.y), r1 = pack_bf16(s.z, s.w);
                const uint32_t s0 = pack_bf16(bf_lo(r0) * SCALE, bf_hi(r0) * SCALE);
                const uint32_t s1 = pack_bf16(bf_lo(r1) * SCALE, bf_hi(r1) * SCALE);
                const float f0 = bf_lo(s0), f1 = bf_hi(s0), f2 = bf_lo(s1), f3 = bf_hi(s1);
                float mx = fmaxf(fmaxf(f0, f1), fmaxf(f2, f3));
                mx = fmaxf(mx, __shfl_xor_sync(~0u, mx, 1));
                mx = fmaxf(mx, __shfl_xor_sync(~0u, mx, 2));
                mx = fmaxf(mx, __shfl_xor_sync(~0u, mx, 4));
                const float mnew = fmaxf(mrun, mx);
                const float al = expsub(mrun, mnew);
                const float p0 = expsub(f0, mnew), p1 = expsub(f1, mnew), p2 = expsub(f2, mnew), p3 = expsub(f3, mnew);
                lrun = lrun * al + ((p0 + p1) + (p2 + p3));
                mrun = mnew;
                *reinterpret_cast<uint2*>(smem + M_P + head * 80 + kq * 8) = make_uint2(pack_bf16(p0, p1), pack_bf16(p2, p3));
                if (kq == 0) alpha[head] = al;
            }
            __syncthreads();
            {
                uint32_t pf[2][2][4];
#pragma unroll
                for (int i = 0; i < 2; i++)
#pragma unroll
                    for (int ks = 0; ks < 2; ks++)
                        ldsm4(pf[i][ks], sbase + M_P + (16 * i + (lane & 15)) * 80 + (16 * ks + 8 * (lane >> 4)) * 2);
#pragma unroll
                for (int i = 0; i < 2; i++) {
                    const float a0 = alpha[16 * i + g], a1 = alpha[16 * i + 8 + g];
#pragma unroll
                    for (int j = 0; j < 8; j++) { acc[i][j][0] *= a0; acc[i][j][1] *= a0; acc[i][j][2] *= a1; acc[i][j][3] *= a1; }
                }
#pragma unroll
                for (int j = 0; j < 8; j++) {
                    uint32_t bf[4];
                    ldsm4t(bf, slot + warp * 4096 + lane * 128 + ((j ^ (lane & 7)) * 16));
#pragma unroll
                    for (int i = 0; i < 2; i++) {
                        mma16816(acc[i][j], pf[i][0], bf[0], bf[1]);
                        mma16816(acc[i][j], pf[i][1], bf[2], bf[3]);
                    }
                }
            }
        }
        __syncthreads();
        if (tid == 0) b_issue(p, BS_PART - 1 + BD, bi, sbase, pol);
        lrun += __shfl_xor_sync(~0u, lrun, 1);
        lrun += __shfl_xor_sync(~0u, lrun, 2);
        lrun += __shfl_xor_sync(~0u, lrun, 4);
        if (kq == 0) g_bml[head * NBCTA + bi] = make_float2(mrun, lrun);
#pragma unroll
        for (int i = 0; i < 2; i++)
#pragma unroll
            for (int j = 0; j < 8; j++) {
                g_bpart[((16 * i + g) * NBCTA + bi) * 256 + warp * 32 + j * 4 + t] = make_float2(acc[i][j][0], acc[i][j][1]);
                g_bpart[((16 * i + 8 + g) * NBCTA + bi) * 256 + warp * 32 + j * 4 + t] = make_float2(acc[i][j][2], acc[i][j][3]);
            }
    }
    if (!CLU) {
#pragma unroll 1
        for (int i = tid; i < NH * 36; i += 256) g_outb[bi * NH * 36 + i] = make_uint4(0u, epoch, 0u, epoch);
    }
    b_exchange(&ctl[C_BBAR + 1][0], BS_PART, &g_bpart[bi * NBCTA * 256], sbase, pol);
    {
        float* omega = reinterpret_cast<float*>(smem + M_OMEGA);
        if (warp == 0) {
            __syncwarp();
            const uint2 ml = ld_relaxed8(&g_bml[bi * NBCTA + lane]);
            const float ms = __uint_as_float(ml.x);
            float m = ms;
            m = fmaxf(m, __shfl_xor_sync(~0u, m, 1));
            m = fmaxf(m, __shfl_xor_sync(~0u, m, 2));
            m = fmaxf(m, __shfl_xor_sync(~0u, m, 4));
            const float w = expsub(ms, m);
            float l = w * __uint_as_float(ml.y);
            l += __shfl_xor_sync(~0u, l, 1);
            l += __shfl_xor_sync(~0u, l, 2);
            l += __shfl_xor_sync(~0u, l, 4);
            omega[lane] = w / l;
        }
        __syncthreads();
        b_wait(BS_PART, sbase);
        b_wait(BS_PART + 1, sbase);
#pragma unroll 1
        for (int b = 0; b < 4; b++) {
            const float2* ps = reinterpret_cast<const float2*>(smem + ((BS_PART + (b >> 1)) % BRING) * SLOT) + (b & 1) * 2048 + tid;
            float c0 = 0.f, c1 = 0.f;
#pragma unroll
            for (int s = 0; s < 8; s++) {
                const float w = omega[b * 8 + s];
                const float2 v = ps[s * 256];
                c0 = fmaf(w, v.x, c0);
                c1 = fmaf(w, v.y, c1);
            }
            const uint32_t hi = pack_bf16(c0, c1);
            *reinterpret_cast<uint32_t*>(smem + M_CH + b * CP + tid * 4) = hi;
            *reinterpret_cast<uint32_t*>(smem + M_CL + b * CP + tid * 4) = pack_bf16(c0 - bf_lo(hi), c1 - bf_hi(hi));
        }
        __syncthreads();
        if (tid == 0) { b_issue(p, BS_PART + BD, bi, sbase, pol); b_issue(p, BS_PART + 1 + BD, bi, sbase, pol); }
    }
    b_gemm(p, sbase, BS_WUV, BS_END, 512, sbase + M_CH, sbase + M_CL, CP, bi, pol);
    TS(12);
    if (CLU) {
        if (warp < 4) {
            const unsigned short* c = reinterpret_cast<const unsigned short*>(smem + M_QB + warp * QP) + 16 * t + g;
            g_octx[(bi * 4 + warp) * 32 + lane] = make_float4(bf_lo(c[0]), bf_lo(c[8]), bf_lo(c[64]), bf_lo(c[72]));
        }
        __syncthreads();
        if (tid == 0) asm volatile("st.release.gpu.global.u32 [%0], %1;" ::"l"(&g_cdone[bi][0]), "r"(epoch + 1) : "memory");
        return;
    }
    if (tid == 0) {
#pragma unroll 1
        for (int i = 0; i < 4; i++) {
            mbar_expect_tx(sbase + M_BAR + i * 8, 36864);
            tma3d(sbase + i * 36864, &p.tm_wo, 0, bi * 128 + i * 32, 0, sbase + M_BAR + i * 8, pol);
        }
    }
    TS(8);
    {
        float acc[9][4];
#pragma unroll
        for (int j = 0; j < 9; j++) { acc[j][0] = acc[j][1] = acc[j][2] = acc[j][3] = 0.f; }
#pragma unroll 1
        for (int i = 0; i < 4; i++) {
            const uint32_t xo = sbase + M_QB + (g & 3) * QP + i * 64 + t * 4;
            const uint32_t a0[4] = {lds32(xo), 0u, lds32(xo + 16), 0u}, a1[4] = {lds32(xo + 32), 0u, lds32(xo + 48), 0u};
            mbar_wait(sbase + M_BAR + i * 8, 0);
#pragma unroll
            for (int j = 0; j < 9; j++) {
                const int nt = warp * 9 + j;
                uint32_t w[4];
                ldsm4t(w, sbase + i * 36864 + (nt >> 3) * 4096 + lane * 128 + (((nt & 7) ^ (lane & 7)) * 16));
                mma16816(acc[j], a0, w[0], w[1]);
                mma16816(acc[j], a1, w[2], w[3]);
            }
        }
        if (g < 4) {
#pragma unroll
            for (int j = 0; j < 9; j++) {
                const int c2 = (warp * 9 + j) * 4 + t;
                st_tagged2(&g_outb[((c2 / 9) * NH + bi) * 36 + g * 9 + c2 % 9], acc[j][0], acc[j][1], epoch + 1);
            }
        }
    }
    TS(9);
    {
        const uint4* src = g_outb + (bi * NH + (tid >> 3)) * 36 + (tid & 7);
        float2* part = reinterpret_cast<float2*>(red);
        unsigned n = 0;
        while (true) {
            ulonglong2 v[5];
            bool ok = true;
#pragma unroll
            for (int i = 0; i < 5; i++)
                if (i < 4 || (tid & 7) < 4) v[i] = ld_tagged2(src + i * 8);
#pragma unroll
            for (int i = 0; i < 5; i++)
                if (i < 4 || (tid & 7) < 4) {
                    ok = ok && (unsigned)(v[i].x >> 32) == epoch + 1 && (unsigned)(v[i].y >> 32) == epoch + 1;
                    part[(tid >> 3) * 36 + (tid & 7) + i * 8] = make_float2(__uint_as_float((unsigned)v[i].x), __uint_as_float((unsigned)v[i].y));
                }
            if (ok) break;
            __nanosleep(400);
            if (++n > SPIN_LIMIT) __trap();
        }
        __syncthreads();
        if (tid < 36) {
            float s0 = 0.f, s1 = 0.f;
#pragma unroll 8
            for (int h = 0; h < NH; h++) { const float2 v = part[h * 36 + tid]; s0 += v.x; s1 += v.y; }
            *reinterpret_cast<uint32_t*>(p.out + (tid / 9) * 2 * DM + DM + bi * 18 + (tid % 9) * 2) = pack_bf16(s0, s1);
        }
    }
    TS(10);
}

template <bool CLU>
__global__ void __launch_bounds__(256, 1) fused_decode_kernel(const __grid_constant__ Params p) {
    asm volatile("{\n.reg .pred p;\n.reg .u32 a;\n.reg .u64 b;\nsub.u32 a, %1, %4;\nsetp.lt.u32 p, a, %3;\nmad.lo.u32 a, %2, %6, %1;\n"
                 "mad.wide.u32 b, a, %5, %0;\n"
                 "@p prefetch.global.L2 [b];\n}"
                 ::"l"(p.pf), "r"(threadIdx.x), "r"(blockIdx.x), "n"(PFN), "n"(PF0), "n"(PFS), "n"(PFC) : "memory");
    extern __shared__ __align__(1024) char smem_raw[];
    const uint32_t sbase = (smem_u32(smem_raw) + 1023u) & ~1023u;
    if (CLU && threadIdx.x < 32 && blockIdx.x >= NBCTA) {
        const unsigned u0 = blockIdx.x - NBCTA, u1 = u0 + 8 * MINCL - NBCTA;
        asm volatile("{\n.reg .pred p;\nelect.sync _|p, 0xffffffff;\n"
                     "@p mbarrier.init.shared::cta.b64 [%0], 1;\n"
                     "@p mbarrier.init.shared::cta.b64 [%0+8], 1;\n"
                     "@p fence.mbarrier_init.release.cluster;\n"
                     "@p mbarrier.arrive.expect_tx.shared::cta.b64 _, [%0], 32768;\n"
                     "@p cp.async.bulk.shared::cluster.global.mbarrier::complete_tx::bytes.L2::cache_hint [%1], [%2], 32768, [%0], %4;\n"
                     "@p mbarrier.arrive.expect_tx.shared::cta.b64 _, [%0+8], 32768;\n"
                     "@p cp.async.bulk.shared::cluster.global.mbarrier::complete_tx::bytes.L2::cache_hint [%1+32768], [%3], 32768, [%0+8], %4;\n}"
                     ::"r"(sbase + M_BAR), "r"(sbase), "l"(reinterpret_cast<const char*>(p.kc) + (size_t)u0 * TILE_BYTES),
                       "l"(reinterpret_cast<const char*>(p.kc) + (size_t)((u1 >> 7) * 1024 + (u1 & 127)) * TILE_BYTES), "l"(0x12F0000000000000ull) : "memory");
    }
    char* smem = smem_raw + (sbase - smem_u32(smem_raw));
    const int tid = threadIdx.x, warp = tid >> 5, lane = tid & 31;
    const int blk = blockIdx.x;
    const bool isB = CLU ? blk < NBCTA : (blk & 3) == 0 && (blk >> 2) < NBCTA;
    const int bi = CLU ? blk : blk >> 2;
    const int nb = CLU ? blk - NBCTA : blk - min(NBCTA, (blk + 3) >> 2);
    const int nblk = CLU ? 8 * MINCL : gridDim.x, nnb = nblk - NBCTA;
    const int nstatic = nnb * (NW + XW);
    uint64_t pol;
    asm volatile("createpolicy.fractional.L2::evict_first.b64 %0, 1.0;" : "=l"(pol));
    const uint32_t wbar = sbase + M_BAR + warp * 8, wslot = sbase + warp * SLOT;
    const int u0 = warp * nnb + nb;
    const bool hold = ((blk >> 2) >> KMIN << KMIN) * 4 * UPP < nstatic;
    const uint32_t jbar = sbase + M_BAR + (NSLOT + BRING) * 8;
    if (warp == 7) {
        if (lane == 0 && blk < 128) {
            mbar_init(jbar, 1);
            asm volatile("fence.mbarrier_init.release.cluster;" ::: "memory");
            uint64_t poln;
            asm volatile("createpolicy.fractional.L2::evict_normal.b64 %0, 1.0;" : "=l"(poln));
            mbar_expect_tx(jbar, 36864 + 4 * 1152);
            tma3d(sbase + J0W, &p.tm_j0, blk * 32, 0, 0, jbar, poln);
            bulk_load(sbase + M_XA, p.xa, 4608, jbar, poln);
        }
        if (lane < 8) reinterpret_cast<unsigned*>(smem + M_HELP)[lane] = 0;
        __syncwarp();
        if (!isB) asm volatile("bar.arrive 2, %0;" ::"n"(32 * (NW + XW + 1)) : "memory");
    }
    if (warp < 4 && lane == 0 && (!CLU || isB || warp >= 2)) {
        mbar_init(wbar, 1);

        asm volatile("fence.mbarrier_init.release.cluster;" ::: "memory");
        if (warp < NEARLY && !isB && !hold) {
            mbar_expect_tx(wbar, TILE_BYTES);
            bulk_load(wslot, block_src(p.kc, unit_block<CLU>(u0)), TILE_BYTES, wbar, pol);
        }
    }
    unsigned epoch = 0;
    if (lane == 0) epoch = ld_relaxed4(&g_epoch);
    TS(0);
    if (CLU) {
        if (warp == 6) {
            if (lane < 8 + 8 * PH && lane != 1) mbar_init(sbase + F_BAR + lane * 8, 1);
            if ((lane >> 1) == 1) mbar_expect_tx(sbase + F_BAR + lane * 8, 1024);
            asm volatile("fence.mbarrier_init.release.cluster;" ::: "memory");
        }
        asm volatile("barrier.cluster.arrive.relaxed.aligned;" ::: "memory");
    }
    if ((warp >> 1) == 2 && blk < 128) st_relaxed64(&g_qll[((tid - 128) >> 4) * 2048 + blk * 16 + (tid & 15)], 0ull);
    if (isB || warp >= NW + XW) epoch = __shfl_sync(~0u, epoch, 0);
    if (isB && warp == 3) asm volatile("bar.sync 1, 160;" ::: "memory");
    if (isB && tid == 96) {
#pragma unroll 1
        for (int i = 0; i < BRING; i++) mbar_init(sbase + M_BAR + (NSLOT + i) * 8, 1);
        asm volatile("fence.mbarrier_init.release.cluster;" ::: "memory");
        if (hold) { unsigned n = 0; while (ld_acquire_cta_shared(sbase + M_HELP + 24) < 2) { if (++n > (SPIN_LIMIT << 4)) __trap(); } }
#pragma unroll 1
        for (int b = 0; b < 4; b++) bulk_load(sbase + M_XB + b * XP, p.xb + b * DM, 1152, sbase + M_BAR + NSLOT * 8, pol);
#pragma unroll 1
        for (int n = 0; n < BD; n++) b_issue(p, n, bi, sbase, pol);
    }
    if (warp >= 4 && blk < 128) {
        const int g = lane >> 2, t = lane & 3, j = tid - 128;
        asm volatile("bar.sync 1, %0;" ::"r"(isB ? 160 : 128) : "memory");
#pragma unroll 1
        for (int sl = blk, ph = 0;; sl += 128 - nblk, ph = 1) {
        mbar_wait(jbar, ph);
        TS(13);
        float acc[4][4];
#pragma unroll
        for (int i = 0; i < 16; i++) acc[i >> 2][i & 3] = 0.f;
        const uint32_t wa = sbase + J0W + ((warp - 4) * 144 + (lane & 15)) * 64;
        const uint32_t sw = (lane >> 1) & 3, xa = sbase + M_XA + (g & 3) * 1152 + (warp - 4) * 288 + t * 4;
#pragma unroll 3
        for (int s = 0; s < 9; s++) {
            const uint32_t a[4] = {lds32(xa + s * 32), 0u, lds32(xa + s * 32 + 16), 0u};
            uint32_t w0[4], w1[4];
            ldsm4t(w0, wa + s * 1024 + (((lane >> 4) ^ sw) * 16));
            ldsm4t(w1, wa + s * 1024 + (((2 + (lane >> 4)) ^ sw) * 16));
            mma16816(acc[0], a, w0[0], w0[1]);
            mma16816(acc[1], a, w0[2], w0[3]);
            mma16816(acc[2], a, w1[0], w1[1]);
            mma16816(acc[3], a, w1[2], w1[3]);
        }
        float2* j0 = reinterpret_cast<float2*>(smem + M_J0);
        if (g < 4) {
#pragma unroll
            for (int i = 0; i < 4; i++) j0[(warp - 4) * 64 + g * 16 + i * 4 + t] = make_float2(acc[i][0], acc[i][1]);
        }
        asm volatile("bar.sync 1, 128;" ::: "memory");
        const bool again = sl == blk && blk + 128 - nblk >= nblk;
        if (again && tid == 224) {
            mbar_expect_tx(jbar, 36864);
            tma3d(sbase + J0W, &p.tm_j0, (blk + 128 - nblk) * 32, 0, 0, jbar, pol);
        }
        if (warp < 6) {
            const float2 v0 = j0[j], v1 = j0[64 + j], v2 = j0[128 + j], v3 = j0[192 + j];
            st_relaxed64(&g_qll[(j >> 4) * 2048 + sl * 16 + (j & 15)],
                         (unsigned long long)pack_bf16((v0.x + v1.x) + (v2.x + v3.x), (v0.y + v1.y) + (v2.y + v3.y)) |
                             ((unsigned long long)(epoch + 1) << 32));
            __syncwarp();
            if (lane == 0) asm volatile("red.relaxed.cta.shared::cta.add.u32 [%0], 1;" ::"r"(sbase + M_HELP + 24) : "memory");
        } else if (warp == 7) {
            if (blk < C_LINES) g_ctl[(epoch & 1) ^ 1][blk][lane] = 0;
        }
        TS(1);
        if (!again) break;
        asm volatile("bar.sync 1, 128;" ::: "memory");
        }
    }
    if (isB) {
        b_chain<CLU>(p, smem, sbase, bi, epoch, pol);
        if (CLU) b_final(p, sbase, blk, epoch, pol);
        return;
    }
    const int sl = nb >> 3, rank = blk & 7;
    if (warp < NW + XW) {
        a_worker<CLU>(p, u0, warp >= NW + ((nb & 3) < (CLU ? X3C : X3) ? 1 : 0), warp < NEARLY && !hold, hold, nstatic, wslot, wbar, sbase + M_HELP,
                      epoch, pol);
        const bool two = sl < 9 && rank == 7;
        if (CLU && (warp == 3 || (warp == 2 && two)) && sl < 10) {
            epoch = __shfl_sync(~0u, epoch, 0);
            unsigned n = 0;
            while (ld_acquire_cta_shared(sbase + M_HELP + 12) == 0) { __nanosleep(1000); if (++n > SPIN_LIMIT) __trap(); }
            asm volatile("barrier.cluster.wait.acquire.aligned;" ::: "memory");
            f_collect((sl < 9 ? g_vdone : g_cdone) + 4 * rank, sl < 9 ? 4 * UPP : epoch + 1, (sl < 9 ? g_oacc : g_octx) + 4 * rank * 128,
                      two ? (warp == 2 ? CM2 : 15 - CM2) : 15, sbase);
            if (warp == 2) return;
            mbar_wait(sbase + F_BAR, 0);
#pragma unroll 1
            for (int i = 0; i < 2; i++) f_receive(p.out + (sl < 9 ? sl * 64 : DM + 512) + rank * 8, 0, i == 0, sbase);
        }
        return;
    }
    if (warp == 7) {
#pragma unroll 1
        for (int i = nb; i < 4 * NH; i += nnb) g_oacc[i * 32 + lane] = make_float4(0.f, 0.f, 0.f, 0.f);
        if (nb < NREP * NH) g_vdone[nb][lane] = 0;
        __syncwarp();
        k_helper(sbase + M_HELP, epoch);
        if (nb == 0 && lane == 0) g_epoch = epoch + 1;
        __syncwarp();
    }
    if (CLU) {
        if (sl < 10) {
            const CUtensorMap* tm = sl < 9 ? &p.tm_fa : &p.tm_fb;
            asm volatile("barrier.cluster.wait.acquire.aligned;" ::: "memory");
            f_project(tm, min(sl, 8), rank, 0, warp & 3, A0 + (warp & 3) * AJ + rank * AR - max(0, (warp & 3) * 8 + rank - AK) * AC, AJ / PH, epoch + 1, sbase, pol);
        }
    } else if (warp == 6 && nb < NFIN) {
        finisher(p, sbase, nb);
        TS(4);
    } else if (warp != 7 && warp >= 6 - NPOLL && nb < NFIN) {
        v_poller(sbase, nb, warp - (6 - NPOLL));
    }
}

}

typedef CUresult (*EncodeFn)(CUtensorMap*, CUtensorMapDataType, cuuint32_t, void*, const cuuint64_t*, const cuuint64_t*,
                             const cuuint32_t*, const cuuint32_t*, CUtensorMapInterleave, CUtensorMapSwizzle,
                             CUtensorMapL2promotion, CUtensorMapFloatOOBfill);

extern "C" void kernel_launch(void* const* d_in, const int* in_sizes, int n_in, void* d_out, int out_size) {
    (void)in_sizes; (void)n_in; (void)out_size;
    static int nsm = 0, ncl = 0;
    static EncodeFn encode = nullptr;
    cudaLaunchConfig_t cfg = {};
    cudaLaunchAttribute at[1];
    at[0].id = cudaLaunchAttributeClusterDimension;
    at[0].val.clusterDim.x = 8; at[0].val.clusterDim.y = 1; at[0].val.clusterDim.z = 1;
    cfg.blockDim = dim3(256); cfg.dynamicSmemBytes = SMEM_BYTES; cfg.stream = cudaStreamPerThread; cfg.attrs = at; cfg.numAttrs = 1;
    if (nsm == 0) {
        int dev = 0;
        cudaGetDevice(&dev);
        cudaDeviceGetAttribute(&nsm, cudaDevAttrMultiProcessorCount, dev);
        cudaFuncSetAttribute(fused_decode_kernel<false>, cudaFuncAttributeMaxDynamicSharedMemorySize, SMEM_BYTES);
        cudaFuncSetAttribute(fused_decode_kernel<true>, cudaFuncAttributeMaxDynamicSharedMemorySize, SMEM_BYTES);
        cfg.gridDim = dim3(128);
        if (cudaOccupancyMaxActiveClusters(&ncl, fused_decode_kernel<true>, &cfg) != cudaSuccess) { ncl = 0; (void)cudaGetLastError(); }
        if (ncl > MINCL) ncl = MINCL;
        void* fn = nullptr;
        cudaDriverEntryPointQueryResult qr;
        cudaGetDriverEntryPoint("cuTensorMapEncodeTiled", &fn, cudaEnableDefault, &qr);
        encode = (EncodeFn)fn;
    }
    Params p;
    auto panels = [&](CUtensorMap* tm, void* ptr, int rows, int cols, int box_rows, int box_panels,
                      CUtensorMapL2promotion promo = CU_TENSOR_MAP_L2_PROMOTION_L2_256B) {
        const cuuint64_t gd[3] = {64, (cuuint64_t)rows, (cuuint64_t)(cols / 64)}, gs[2] = {(cuuint64_t)cols * 2, 128};
        const cuuint32_t box[3] = {64, (cuuint32_t)box_rows, (cuuint32_t)box_panels}, es[3] = {1, 1, 1};
        encode(tm, CU_TENSOR_MAP_DATA_TYPE_BFLOAT16, 3, ptr, gd, gs, box, es, CU_TENSOR_MAP_INTERLEAVE_NONE,
               CU_TENSOR_MAP_SWIZZLE_128B, promo, CU_TENSOR_MAP_FLOAT_OOB_FILL_NONE);
    };
    panels(&p.tm_wq, d_in[7], DM, 4096, 128, 2);
    panels(&p.tm_wuk, d_in[8], 512, 4096, 128, 2);
    panels(&p.tm_wuv, d_in[9], 512, 4096, 128, 2);
    panels(&p.tm_wo, d_in[10], 4096, DM, 32, 9);
    panels(&p.tm_ckv, d_in[6], 4 * SK, 512, 32, 8);
    panels(&p.tm_fa, d_in[4], 4096, DM, 128 / PH, 1, CU_TENSOR_MAP_L2_PROMOTION_L2_128B);
    panels(&p.tm_fb, d_in[10], 4096, DM, 128 / PH, 1, CU_TENSOR_MAP_L2_PROMOTION_L2_128B);
    {
        const cuuint64_t gd[3] = {4096, 192, 3}, gs[2] = {8192, 192 * 8192};
        const cuuint32_t box[3] = {32, 192, 3}, es[3] = {1, 1, 1};
        encode(&p.tm_j0, CU_TENSOR_MAP_DATA_TYPE_BFLOAT16, 3, d_in[3], gd, gs, box, es, CU_TENSOR_MAP_INTERLEAVE_NONE,
               CU_TENSOR_MAP_SWIZZLE_64B, CU_TENSOR_MAP_L2_PROMOTION_L2_128B, CU_TENSOR_MAP_FLOAT_OOB_FILL_NONE);
    }
    p.xa = (const __nv_bfloat16*)d_in[0];
    p.kc = (const __nv_bfloat16*)d_in[1];
    p.vc = (const __nv_bfloat16*)d_in[2];
    p.pf = (const char*)d_in[1] + (size_t)PFOFF * TILE_BYTES - PF0 * PFS;
    p.wo = (const __nv_bfloat16*)d_in[4];
    p.xb = (const __nv_bfloat16*)d_in[5];
    p.out = (__nv_bfloat16*)d_out;
    if (ncl >= MINCL) {
        cfg.gridDim = dim3(8 * ncl);
        cudaLaunchKernelEx(&cfg, fused_decode_kernel<true>, p);
    } else {
        fused_decode_kernel<false><<<nsm, 256, SMEM_BYTES, cudaStreamPerThread>>>(p);
    }
}
```

```cpp
#include <cuda_runtime.h>
#include <cuda.h>
#include <cuda_bf16.h>
#include <stdint.h>

namespace {

constexpr int NH = 32, SK = 4096, DM = 576;
constexpr int KEYS = 128;
constexpr int UPP = SK / KEYS;
constexpr int NUK = 4 * NH * UPP;
constexpr int TILE_BYTES = KEYS * 256;
#define NWORK 2
constexpr int NW = NWORK;
constexpr int NBCTA = 32;
constexpr int MINCL = 15;
constexpr int NFIN = 72;
constexpr int SLOT = 32768;
constexpr int NSLOT = 6;
constexpr int BRING = 5;
constexpr int J0W = 5 * SLOT;
constexpr int MISC = NSLOT * SLOT + 4096;
constexpr int XP = 1168, CP = 1040, QP = 272;
constexpr int M_XA = MISC;
constexpr int M_XB = M_XA + 4 * XP;
constexpr int M_CH = M_XB + 4 * XP;
constexpr int M_CL = M_CH + 4 * CP;
constexpr int M_QB = M_CL + 4 * CP;
constexpr int M_QA = M_CH;
constexpr int M_J0 = M_QB + 4 * QP;
constexpr int M_P = M_J0 + 2048;
constexpr int M_ALPHA = M_P + 2560;
constexpr int M_OMEGA = M_ALPHA + 128;
constexpr int M_BAR = M_OMEGA + 128;
constexpr int M_HELP = M_BAR + 128;
#define PH 1
constexpr int F_W = 4 * SLOT;
constexpr int F_BF = (M_HELP + 128 + 255) / 256 * 256;
constexpr int F_RX = F_BF + 4096;
constexpr int F_BAR = F_RX + 2048;
constexpr int SMEM_BYTES = F_BAR + 64 + 64 * PH + 1024;
static_assert(SMEM_BYTES <= 232448 && M_BAR % 8 == 0 && M_QA % 16 == 0 && M_P % 16 == 0, "smem layout");
#define XW 2
#define X3 1
#define X3C 3
#define NEARLY 3
#define BD 5
#define FPF 3
#define FSLEEP 800
#define VS0 24
#define EARLY 100
#define ELOG 5
#define TPU 159
#define A0 3000
#define AJ 700
#define AR (AJ / 8 / PH)
#define ASTEP (AJ / PH)
#define BSTEP (BJ / PH)
#define PFN 96
#define PFS 128
#define PFC PFN
#define PFLD 0
#define PF0 128
#define PFOFF 0
#define CM2 10
#define AK 24
#define AC 0
#define BK 24
#define BC 0
#define B0 2500
#define BJ 700
#define BS (300 / PH)
#define BR (BJ / 8 / PH)
#define NPOLL 2
#define PGAP 200
static_assert(X3C <= 3 && NW == 2, "warp 2 of rank 7 is free");
static_assert(NW + XW <= 4 && NEARLY <= NW + XW && BD <= BRING, "slots 4 and 5 hold the finisher weights");
#define KMAX 4
#define VMAX 4
constexpr int KMIN = 2, VMIN = 0;
constexpr float SCALE = 0.08838834764831845f;
constexpr float LOG2E = 1.4426950408889634f;
constexpr unsigned SPIN_LIMIT = 1u << 24;

#define NREP 2
#define NREPC 1
constexpr int C_QUEUE = 0, C_KDONE = 1, C_BBAR = 3, C_LINES = 5;

struct Params {
    const char* pf;
    const __nv_bfloat16 *kc, *xa, *vc, *wo, *xb;
    __nv_bfloat16* out;
    CUtensorMap tm_j0;
    CUtensorMap tm_wq, tm_wuk, tm_ckv, tm_wuv, tm_wo;
    CUtensorMap tm_fa, tm_fb;
};

__device__ unsigned g_epoch;
__device__ unsigned g_ctl[2][C_LINES][32];
__device__ uint2 g_qll[4 * 2048];
__device__ uint2 g_scores[128 * SK / 4];
__device__ float2 g_stats[128 * UPP];
__device__ float4 g_oacc[128 * 32];
__device__ unsigned g_vdone[NREP * NH][32];
__device__ float4 g_octx[128 * 32];
__device__ unsigned g_cdone[NH][32];
__device__ unsigned long long g_dry[16][16];
__device__ uint4 g_qabs[4 * 8 * 4 * 4 * 32];
__device__ float2 g_bpart[NBCTA * NH * 256];
__device__ float2 g_bml[NBCTA * NH];
__device__ uint4 g_outb[NBCTA * NH * 36];

#define TS(i)
#define TSV(i, v)
#define LAND(i)
#define CLK(x)
#define ACC(a, x, y)

__device__ __forceinline__ uint32_t smem_u32(const void* p) { return (uint32_t)__cvta_generic_to_shared(p); }
__device__ __forceinline__ void mbar_init(uint32_t bar, uint32_t cnt) {
    asm volatile("mbarrier.init.shared::cta.b64 [%0], %1;" ::"r"(bar), "r"(cnt) : "memory");
}
__device__ __forceinline__ void mbar_expect_tx(uint32_t bar, uint32_t bytes) {
    asm volatile("mbarrier.arrive.expect_tx.shared::cta.b64 _, [%0], %1;" ::"r"(bar), "r"(bytes) : "memory");
}
__device__ __forceinline__ bool mbar_try(uint32_t bar, uint32_t parity) {
    uint32_t ok;
    asm volatile("{\n.reg .pred p;\nmbarrier.try_wait.parity.shared::cta.b64 p, [%1], %2;\nselp.u32 %0, 1, 0, p;\n}\n"
                 : "=r"(ok) : "r"(bar), "r"(parity) : "memory");
    return ok;
}
__device__ __forceinline__ void mbar_wait(uint32_t bar, uint32_t parity) {
    unsigned n = 0;
    while (!mbar_try(bar, parity)) { if (++n > SPIN_LIMIT) __trap(); }
}
__device__ __forceinline__ void mbar_spin(uint32_t bar) {
    asm volatile("{\n.reg .pred p;\n.reg .u32 n;\nmov.u32 n, 0;\nSPIN:\nmbarrier.test_wait.parity.shared::cta.b64 p, [%0], 0;\n@p bra.uni DONE;\n"
                 "add.u32 n, n, 1;\nsetp.lt.u32 p, n, 0x4000000;\n@p bra.uni SPIN;\ntrap;\nDONE:\n}" ::"r"(bar) : "memory");
}
__device__ __forceinline__ void bulk_load(uint32_t dst, const void* src, uint32_t bytes, uint32_t bar, uint64_t pol) {
    asm volatile("cp.async.bulk.shared::cluster.global.mbarrier::complete_tx::bytes.L2::cache_hint [%0], [%1], %2, [%3], %4;"
                 ::"r"(dst), "l"(src), "r"(bytes), "r"(bar), "l"(pol) : "memory");
}
__device__ __forceinline__ void tma3d(uint32_t dst, const CUtensorMap* tm, int c0, int c1, int c2, uint32_t bar, uint64_t pol) {
    asm volatile("cp.async.bulk.tensor.3d.shared::cluster.global.mbarrier::complete_tx::bytes.L2::cache_hint [%0], [%1, {%3,%4,%5}], [%2], %6;"
                 ::"r"(dst), "l"(tm), "r"(bar), "r"(c0), "r"(c1), "r"(c2), "l"(pol) : "memory");
}
__device__ __forceinline__ void l2_prefetch(const void* src, uint32_t bytes) {
    asm volatile("cp.async.bulk.prefetch.L2.global [%0], %1;" ::"l"(src), "r"(bytes) : "memory");
}
__device__ __forceinline__ void ldsm4(uint32_t (&r)[4], uint32_t addr) {
    asm volatile("ldmatrix.sync.aligned.m8n8.x4.shared.b16 {%0,%1,%2,%3}, [%4];"
                 : "=r"(r[0]), "=r"(r[1]), "=r"(r[2]), "=r"(r[3]) : "r"(addr));
}
__device__ __forceinline__ void ldsm4t(uint32_t (&r)[4], uint32_t addr) {
    asm volatile("ldmatrix.sync.aligned.m8n8.x4.trans.shared.b16 {%0,%1,%2,%3}, [%4];"
                 : "=r"(r[0]), "=r"(r[1]), "=r"(r[2]), "=r"(r[3]) : "r"(addr));
}
__device__ __forceinline__ void mma16816(float (&d)[4], const uint32_t (&a)[4], uint32_t b0, uint32_t b1) {
    asm("mma.sync.aligned.m16n8k16.row.col.f32.bf16.bf16.f32 {%0,%1,%2,%3}, {%4,%5,%6,%7}, {%8,%9}, {%0,%1,%2,%3};"
        : "+f"(d[0]), "+f"(d[1]), "+f"(d[2]), "+f"(d[3])
        : "r"(a[0]), "r"(a[1]), "r"(a[2]), "r"(a[3]), "r"(b0), "r"(b1));
}
__device__ __forceinline__ uint32_t lds32(uint32_t a) {
    uint32_t v;
    asm volatile("ld.shared.u32 %0, [%1];" : "=r"(v) : "r"(a));
    return v;
}
__device__ __forceinline__ unsigned ld_acquire(const unsigned* p) {
    unsigned v;
    asm volatile("ld.acquire.gpu.global.u32 %0, [%1];" : "=r"(v) : "l"(p) : "memory");
    return v;
}
__device__ __forceinline__ uint2 ld_relaxed8(const void* p) {
    uint2 v;
    asm volatile("ld.relaxed.gpu.global.v2.u32 {%0,%1}, [%2];" : "=r"(v.x), "=r"(v.y) : "l"(p) : "memory");
    return v;
}
__device__ __forceinline__ unsigned ld_relaxed4(const void* p) {
    unsigned v;
    asm volatile("ld.relaxed.gpu.global.u32 %0, [%1];" : "=r"(v) : "l"(p) : "memory");
    return v;
}
__device__ __forceinline__ unsigned atom_inc(unsigned* p) {
    unsigned v;
    asm volatile("atom.relaxed.gpu.global.inc.u32 %0, [%1], 0x7fffffff;" : "=r"(v) : "l"(p) : "memory");
    return v;
}
__device__ __forceinline__ unsigned long long ld_relaxed64(const void* p) {
    unsigned long long v;
    asm volatile("ld.relaxed.gpu.global.u64 %0, [%1];" : "=l"(v) : "l"(p) : "memory");
    return v;
}
__device__ __forceinline__ void st_relaxed64(void* p, unsigned long long v) {
    asm volatile("st.relaxed.gpu.global.u64 [%0], %1;" ::"l"(p), "l"(v) : "memory");
}
__device__ __forceinline__ float4 ld_relaxed16(const void* p) {
    float4 v;
    asm volatile("ld.relaxed.gpu.global.v4.f32 {%0,%1,%2,%3}, [%4];" : "=f"(v.x), "=f"(v.y), "=f"(v.z), "=f"(v.w) : "l"(p) : "memory");
    return v;
}
__device__ __forceinline__ uint32_t mapa(uint32_t a, uint32_t rank) {
    uint32_t r;
    asm("mapa.shared::cluster.u32 %0, %1, %2;" : "=r"(r) : "r"(a), "r"(rank));
    return r;
}
__device__ __forceinline__ uint32_t time_ns() { uint32_t t; asm volatile("mov.u32 %0, %globaltimer_lo;" : "=r"(t)); return t; }
__device__ __forceinline__ void fence_gpu() { asm volatile("fence.acq_rel.gpu;" ::: "memory"); }
__device__ __forceinline__ void red_add_u32(unsigned* p, unsigned v) {
    asm volatile("red.relaxed.gpu.global.add.u32 [%0], %1;" ::"l"(p), "r"(v) : "memory");
}
__device__ __forceinline__ void st_tagged2(void* p, float a, float b, unsigned tag) {
    const unsigned long long hi = (unsigned long long)tag << 32;
    asm volatile("st.relaxed.gpu.global.v2.b64 [%0], {%1,%2};" ::"l"(p), "l"(hi | __float_as_uint(a)), "l"(hi | __float_as_uint(b)) : "memory");
}
__device__ __forceinline__ ulonglong2 ld_tagged2(const void* p) {
    ulonglong2 v;
    asm volatile("ld.relaxed.gpu.global.v2.b64 {%0,%1}, [%2];" : "=l"(v.x), "=l"(v.y) : "l"(p) : "memory");
    return v;
}
__device__ __forceinline__ float4 atom_add_f4(void* p, float a, float b, float c, float d) {
    float4 r;
    asm volatile("atom.relaxed.gpu.global.add.v4.f32 {%0,%1,%2,%3}, [%4], {%5,%6,%7,%8};"
                 : "=f"(r.x), "=f"(r.y), "=f"(r.z), "=f"(r.w) : "l"(p), "f"(a), "f"(b), "f"(c), "f"(d) : "memory");
    return r;
}
__device__ __forceinline__ void red_release_cta_shared(uint32_t a, unsigned v) {
    asm volatile("red.release.cta.shared::cta.add.u32 [%0], %1;" ::"r"(a), "r"(v) : "memory");
}
__device__ __forceinline__ unsigned ld_acquire_cta_shared(uint32_t a) {
    unsigned v;
    asm volatile("ld.acquire.cta.shared::cta.u32 %0, [%1];" : "=r"(v) : "r"(a) : "memory");
    return v;
}
__device__ __forceinline__ void st_release_cta_shared(uint32_t a, unsigned v) {
    asm volatile("st.release.cta.shared::cta.u32 [%0], %1;" ::"r"(a), "r"(v) : "memory");
}
__device__ __forceinline__ void wait_count(const unsigned* p, unsigned target) {
    unsigned n = 0;
    while (ld_acquire(p) < target) { if (++n > SPIN_LIMIT) __trap(); }
}
__device__ __forceinline__ uint32_t pack_bf16(float lo, float hi) {
    uint32_t r;
    asm("cvt.rn.bf16x2.f32 %0, %1, %2;" : "=r"(r) : "f"(hi), "f"(lo));
    return r;
}
__device__ __forceinline__ float bf_lo(uint32_t v) { return __uint_as_float(v << 16); }
__device__ __forceinline__ float bf_hi(uint32_t v) { return __uint_as_float(v & 0xffff0000u); }
__device__ __forceinline__ float ex2(float x) { float y; asm("ex2.approx.ftz.f32 %0, %1;" : "=f"(y) : "f"(x)); return y; }
__device__ __forceinline__ float expsub(float a, float b) { return ex2((a - b) * LOG2E); }
__device__ __forceinline__ float warp_max(float v) {
#pragma unroll
    for (int m = 16; m; m >>= 1) v = fmaxf(v, __shfl_xor_sync(~0u, v, m));
    return v;
}
__device__ __forceinline__ float warp_sum(float v) {
#pragma unroll
    for (int m = 16; m; m >>= 1) v += __shfl_xor_sync(~0u, v, m);
    return v;
}
template <bool CLU>
__device__ __forceinline__ unsigned unit_block(int u) {
    const unsigned x = ((unsigned)u & (NUK - 1)) / UPP;
    const int lg = u < NUK ? min(KMAX, max(KMIN, 29 - __clz(x | 1))) : (CLU && (int)x >= 4 * VS0 ? 0 : min(VMAX, max(VMIN, 29 - __clz((127 - x) | 1))));
    const unsigned r = x & ((4u << lg) - 1);
    return ((x - r + (r & ((1u << lg) - 1)) * 4 + (r >> lg)) * UPP) | ((unsigned)u & (UPP - 1));
}
__device__ __forceinline__ const char* block_src(const void* base, unsigned blk) {
    const unsigned po = blk / UPP;
    return reinterpret_cast<const char*>(base) + (size_t)(((po & 3) * NH + (po >> 2)) * UPP + blk % UPP) * TILE_BYTES;
}

template <bool CLU>
__device__ __forceinline__ void a_worker(const Params& p, int un, bool once, bool pre, bool hold, int nstatic, uint32_t slot, uint32_t bar,
                                         uint32_t help, unsigned epoch, uint64_t pol) {
    constexpr int NU = 2 * NUK, NR = CLU ? NREPC : NREP;
    const int lane = threadIdx.x & 31, g = lane >> 2, t = lane & 3;
    const int li = lane & 7;
    uint32_t kaddr[4], vaddr[8];
    {
        const int e = (lane >> 3) & 1, kk = lane >> 4;
#pragma unroll
        for (int s = 0; s < 4; s++) kaddr[s] = slot + (16 * li + e) * 256 + ((2 * s + kk + li) & 7) * 16;
        const int vrow = 4 * (li >> 1) + (li & 1) + 2 * kk;
#pragma unroll
        for (int c = 0; c < 8; c++) vaddr[c] = slot + vrow * 256 + e * 128 + ((c + li) & 7) * 16;
#pragma unroll
        for (int c = 0; c < 8; c++) asm volatile("" : "+r"(vaddr[c]));
    }
    const uint32_t vmask = (g >> 1) != t ? 0u : ((g & 1) ? 0xffff0000u : 0xffffu);
    int kseen = -1;
    unsigned long long H0 = 0, H1 = 0;
    auto header = [&](int v, unsigned vb) {
        if (v >= NU) return;
        const void *a0, *a1;
        if (v < NUK) {
            const unsigned po = vb / UPP;
            a0 = g_qll + (po & 3) * 2048 + (po >> 2) * 64 + lane;
            a1 = reinterpret_cast<const uint2*>(a0) + 32;
        } else {
            const int half = vb / (NUK / 2);
            if (half > kseen) {
                unsigned n = 0;
                while (ld_acquire_cta_shared(help + 12 + 4 * half) == 0) { if (++n > (SPIN_LIMIT << 4)) __trap(); }
                kseen = half;
            }
            a0 = &g_scores[vb * (KEYS / 4) + lane];
            a1 = &g_stats[(vb / UPP) * UPP + lane];
        }
        H0 = ld_relaxed64(a0);
        H1 = ld_relaxed64(a1);
    };
    asm volatile("bar.sync 2, %0;" ::"n"(32 * (NW + XW + 1)) : "memory");
    epoch = __shfl_sync(~0u, epoch, 0);
    if (hold) { unsigned n = 0; while (ld_acquire_cta_shared(help + 24) < 2) { if (++n > (SPIN_LIMIT << 4)) __trap(); } }
    unsigned (*ctl)[32] = g_ctl[epoch & 1];
    const unsigned tag = epoch + 1;
    unsigned nxt = once ? NU : 0;
    int u = -1;
    unsigned bu = 0, bn = unit_block<CLU>(un);
    bool have = false;
    uint32_t phase = 0;
    unsigned kpend = 0;
    const unsigned zero = gridDim.x >> 24;
    uint32_t Q[16];
    float4 oret = make_float4(0.f, 0.f, 0.f, 0.f);
    while (true) {
        const char* nsrc = block_src(un < NUK ? p.kc : p.vc, bn);
        float4* odst = &g_oacc[(bu / UPP) * 32 + lane];
        unsigned* vdst = &g_vdone[(lane & (NR - 1)) * NH + bu / (4 * UPP)][0];
        float d[8][4];
        CLK(c1);
        asm volatile("" : "+l"(odst));
        if (u >= NUK) {
#pragma unroll
            for (int j = 0; j < 8; j++) { d[j][0] = d[j][1] = d[j][2] = d[j][3] = 0.f; }
            mbar_wait(bar, phase);
            LAND(NUK + bu);
            uint32_t a[2][8][4];
#pragma unroll
            for (int c = 0; c < 8; c++) ldsm4t(a[0][c], vaddr[c]);
#pragma unroll
            for (int j = 0; j < 8; j++) {
                if (j < 7) {
#pragma unroll
                    for (int c = 0; c < 8; c++) ldsm4t(a[(j + 1) & 1][c], vaddr[c] + (j + 1) * 4096);
                }
#pragma unroll
                for (int c = 0; c < 8; c++) mma16816(d[c], a[j & 1][c], Q[2 * j], Q[2 * j + 1]);
            }
            float o[4];
#pragma unroll
            for (int r = 0; r < 2; r++) {
                o[2 * r] = d[0][2 * r] + d[7][2 * r + 1];
                o[2 * r + 1] = d[0][2 * r + 1] + d[1][2 * r];
#pragma unroll
                for (int k = 1; k < 4; k++) {
                    const int src = (lane & 28) | ((t - k) & 3);
                    o[2 * r] += __shfl_sync(~0u, d[2 * k][2 * r] + d[2 * k - 1][2 * r + 1], src);
                    o[2 * r + 1] += __shfl_sync(~0u, d[2 * k][2 * r + 1] + d[2 * k + 1][2 * r], src);
                }
            }
            oret = atom_add_f4(odst, o[0], o[1], o[2], o[3]);
        } else if (u >= 0) {
#pragma unroll
            for (int j = 0; j < 8; j++) { d[j][0] = d[j][1] = d[j][2] = d[j][3] = 0.f; }
            mbar_wait(bar, phase);
            LAND(bu);
            uint32_t a[2][8][4];
#pragma unroll
            for (int j = 0; j < 8; j++) ldsm4(a[0][j], kaddr[0] + (4 * (j & 3) + 2 * (j >> 2)) * 256);
#pragma unroll
            for (int s = 0; s < 8; s++) {
                if (s < 7) {
#pragma unroll
                    for (int j = 0; j < 8; j++)
                        ldsm4(a[(s + 1) & 1][j], kaddr[(s + 1) & 3] + (4 * (j & 3) + 2 * (j >> 2)) * 256 + ((s + 1) >> 2) * 128);
                }
#pragma unroll
                for (int j = 0; j < 8; j++)
                    mma16816(d[j], a[s & 1][j], Q[(s & 4) * 2 + ((2 * s - 2 * j) & 7)], Q[(s & 4) * 2 + ((2 * s + 1 - 2 * j) & 7)]);
            }
        }
        if (u >= 0) phase ^= 1;
        CLK(c2b);
        if (un < NU && lane == 0) {
            if (!once) nxt = atom_inc(&ctl[C_QUEUE][0]);
            if (u >= 0 || !pre) {
                mbar_expect_tx(bar, TILE_BYTES);
                bulk_load(slot, nsrc, TILE_BYTES, bar, pol);
            }
        }
        const uint32_t tk = clock();
        CLK(c3);
        if ((unsigned)u < (unsigned)NUK) {
            const int j0 = (t - (g >> 1)) & 3;
            float v[4];
#pragma unroll
            for (int q = 0; q < 4; q++) {
                const int jq = (q >> 1) * 4, e = (q & 1) * 2;
                const float x0 = (g & 1) ? d[jq + 0][e + 1] : d[jq + 0][e];
                const float x1 = (g & 1) ? d[jq + 1][e + 1] : d[jq + 1][e];
                const float x2 = (g & 1) ? d[jq + 2][e + 1] : d[jq + 2][e];
                const float x3 = (g & 1) ? d[jq + 3][e + 1] : d[jq + 3][e];
                const float y0 = (j0 & 1) ? x1 : x0, y1 = (j0 & 1) ? x3 : x2;
                v[q] = (j0 & 2) ? y1 : y0;
            }
            const uint32_t r0 = pack_bf16(v[0], v[1]), r1 = pack_bf16(v[2], v[3]);
            const uint32_t s0 = pack_bf16(bf_lo(r0) * SCALE, bf_hi(r0) * SCALE);
            const uint32_t s1 = pack_bf16(bf_lo(r1) * SCALE, bf_hi(r1) * SCALE);
            g_scores[bu * (KEYS / 4) + 4 * g + j0] = make_uint2(s0, s1);
            const float f0 = bf_lo(s0), f1 = bf_hi(s0), f2 = bf_lo(s1), f3 = bf_hi(s1);
            const float m = warp_max(fmaxf(fmaxf(f0, f1), fmaxf(f2, f3)));
            const float l = warp_sum((expsub(f0, m) + expsub(f1, m)) + (expsub(f2, m) + expsub(f3, m)));
            if (lane == 0) g_stats[bu] = make_float2(m, l);
            kpend++;
            if (un / (NUK / 2) != u / (NUK / 2)) {
                __syncwarp();
                if (lane == 0) {
                    red_release_cta_shared(help + 4 * (u / (NUK / 2)), kpend);
                    if (un >= NUK) red_release_cta_shared(help + 8, 1u);
                }
                kpend = 0;
            }
        }
        CLK(c4);
        int unn = NU;
        if (un < NU) {
            unsigned n = 0;
            while (true) {
                if (!have) header(un, bn);
                if (un >= NUK || __all_sync(~0u, (uint32_t)(H0 >> 32) == tag && (uint32_t)(H1 >> 32) == tag)) break;
                if (++n > SPIN_LIMIT) __trap();
                have = false;
            }
            if (un >= NUK) {
                const uint32_t s0 = (uint32_t)H0, s1 = (uint32_t)(H0 >> 32);
                const float mu = __uint_as_float((uint32_t)H1);
                const float m = warp_max(mu);
                const float l = warp_sum(__uint_as_float((uint32_t)(H1 >> 32)) * expsub(mu, m));
                const float inv = 1.0f / l;
                const uint32_t w0 = pack_bf16(expsub(bf_lo(s0), m) * inv, expsub(bf_hi(s0), m) * inv);
                const uint32_t w1 = pack_bf16(expsub(bf_lo(s1), m) * inv, expsub(bf_hi(s1), m) * inv);
#pragma unroll
                for (int j = 0; j < 8; j++) {
                    Q[2 * j] = __shfl_sync(~0u, w0, 4 * j + t) & vmask;
                    Q[2 * j + 1] = __shfl_sync(~0u, w1, 4 * j + t) & vmask;
                }
            } else {
#pragma unroll
                for (int j = 0; j < 8; j++) {
                    const int src = (((j + g) & 7) << 2) + t;
                    Q[j] = __shfl_sync(~0u, (uint32_t)H0, src);
                    Q[8 + j] = __shfl_sync(~0u, (uint32_t)H1, src);
                }
            }
            unn = nstatic + (int)__shfl_sync(~0u, nxt, 0);
            if (CLU && ((NU - EARLY - unn) & ~(7 << ELOG)) == 0 && lane < MINCL)
                st_relaxed64(&g_dry[lane][(NU - EARLY - unn) >> ELOG],
                             (time_ns() - (((uint32_t)clock() - tk) >> 1) + (NU - unn) * TPU / 16) | (unsigned long long)tag << 32);
        }
        if (u >= NUK && lane < NR)
            red_add_u32(vdst,
                        1u + ((__float_as_uint(oret.x) | __float_as_uint(oret.y) | __float_as_uint(oret.z) | __float_as_uint(oret.w)) & zero));
        if (un >= NU) break;
        bu = bn;
        have = !(un < NUK && unn >= NUK && !(un >= NUK / 2 && unn < NUK + NUK / 2));
        bn = unit_block<CLU>(unn);
        if (have) header(unn, bn);
        u = un;
        un = unn;
    }
}

__device__ __forceinline__ void k_helper(uint32_t help, unsigned epoch) {
    if ((threadIdx.x & 31) != 0) return;
    unsigned (*ctl)[32] = g_ctl[epoch & 1];
    unsigned sent0 = 0, sent1 = 0, n = 0;
    int seen = 0;
    bool fin = false;
    while (!fin || seen < 2) {
        if (!fin) {
            fin = ld_acquire_cta_shared(help + 8) == NW + XW;
            const unsigned c0 = ld_acquire_cta_shared(help), c1 = ld_acquire_cta_shared(help + 4);
            if (c0 != sent0 || c1 != sent1) {
                fence_gpu();
                if (c0 != sent0) red_add_u32(&ctl[C_KDONE][0], c0 - sent0);
                if (c1 != sent1) red_add_u32(&ctl[C_KDONE + 1][0], c1 - sent1);
                sent0 = c0; sent1 = c1;
            }
        }
        if (seen < 2 && ld_acquire(&ctl[C_KDONE + seen][0]) >= NUK / 2) {
            st_release_cta_shared(help + 12 + 4 * seen, 1u);
            seen++;
        } else {
            __nanosleep(300);
        }
        if (++n > SPIN_LIMIT) __trap();
    }
}

__device__ __forceinline__ void v_poller(uint32_t sbase, int f, int w) {
    constexpr int HL = NH;
    const int lane = threadIdx.x & 31;
    const unsigned (*cp)[32] = &g_vdone[((f * NPOLL + w) % NREP) * NH];
    unsigned n = 0;
    while (ld_acquire_cta_shared(sbase + M_HELP + 12) == 0) { __nanosleep(1000); if (++n > SPIN_LIMIT) __trap(); }
    int h = 0;
    bool fast = false;
    while (h < HL) {
        const unsigned r = __ballot_sync(~0u, ld_acquire(&cp[min(h + (lane & 3), HL - 1)][0]) >= 4 * UPP) & 15u;
        if (r & 1) {
            h = min(HL, h + __ffs(~r) - 1);
            __syncwarp();
            if (lane == 0) asm volatile("red.release.cta.shared::cta.max.u32 [%0], %1;" ::"r"(sbase + M_HELP + 20), "r"(h) : "memory");
        }
        if (h < HL - 4) {
            __nanosleep(h ? 300 : 1000);
        } else if (!fast) {
            fast = true;
            const long long t0 = clock64();
            while (clock64() - t0 < w * PGAP) {}
        }
        if (++n > SPIN_LIMIT) __trap();
    }
}
__device__ __forceinline__ void finisher(const Params& p, uint32_t sbase, int f) {
    constexpr int HL = NH;
    const int lane = threadIdx.x & 31;
    {
        const char* wg = reinterpret_cast<const char*>(p.wo);
        const uint32_t dst = sbase + 4 * SLOT + (16 * (lane & 7) + (lane >> 3)) * 16;
#pragma unroll 1
        for (int h = -FPF - 4; h < HL; h++) {
            if (lane == 0 && (unsigned)(h + FPF) < (unsigned)HL) l2_prefetch(wg + (size_t)(h + FPF) * 147456 + f * 2048, 2048);
            if (h >= 0) {
#pragma unroll
                for (int r = 0; r < 4; r++)
                    asm volatile("cp.async.cg.shared.global [%0], [%1], 16;" ::"r"(dst + h * 2048 + ((r & 1) * 4 + (r >> 1) * 8) * 16),
                                 "l"(wg + (size_t)(h * 128 + r * 32 + lane) * (DM * 2) + f * 16) : "memory");
            }
            __nanosleep(FSLEEP);
        }
        asm volatile("cp.async.wait_all;" ::: "memory");
        __syncwarp();
    }
    TS(11);
    const float4* vec = g_oacc + ((lane >> 2) & 3) * 32 + (lane >> 4) * 16 + (lane & 3);
    float acc[2][2][4];
#pragma unroll
    for (int i = 0; i < 16; i++) acc[i >> 3][(i >> 2) & 1][i & 3] = 0.f;
    uint32_t* outp = reinterpret_cast<uint32_t*>(p.out + (lane >> 2) * (2 * DM) + f * 8 + (lane & 3) * 2);
    uint32_t wa = sbase + 4 * SLOT + lane * 16;
    auto project = [&](const float4 (&x)[4], const uint32_t (&w)[4][4]) {
#pragma unroll
        for (int s = 0; s < 4; s++) {
            const uint32_t a[4] = {pack_bf16(x[s].x, x[s].y), 0u, pack_bf16(x[s].z, x[s].w), 0u};
            mma16816(acc[0][s & 1], a, w[s >> 1][(s & 1) * 2], w[s >> 1][(s & 1) * 2 + 1]);
            mma16816(acc[1][s & 1], a, w[2 + (s >> 1)][(s & 1) * 2], w[2 + (s >> 1)][(s & 1) * 2 + 1]);
        }
    };
    int h = 0;
    unsigned n = 0;
    while (h < HL) {
        uint32_t w[4][4];
#pragma unroll
        for (int q = 0; q < 4; q++) ldsm4t(w[q], wa + q * 512);
        int ready;
        while ((ready = ld_acquire_cta_shared(sbase + M_HELP + 20)) <= h) {
            if (h < HL - 3) __nanosleep(100);
            if (++n > (SPIN_LIMIT << 4)) __trap();
        }
        float4 x[4], y[4];
#pragma unroll
        for (int s = 0; s < 4; s++) x[s] = ld_relaxed16(vec + s * 4);
        const bool two = ready > h + 1;
        if (two) {
#pragma unroll
            for (int s = 0; s < 4; s++) y[s] = ld_relaxed16(vec + 128 + s * 4);
        }
        project(x, w);
        if (two) {
#pragma unroll
            for (int q = 0; q < 4; q++) ldsm4t(w[q], wa + 2048 + q * 512);
            project(y, w);
        }
        const int nr = two ? 2 : 1;
        h += nr;
        vec += nr * 128;
        wa += nr * 2048;
        const float o0 = acc[0][0][0] + acc[0][1][0] + __shfl_down_sync(~0u, acc[1][0][0] + acc[1][1][0], 16);
        const float o1 = acc[0][0][1] + acc[0][1][1] + __shfl_down_sync(~0u, acc[1][0][1] + acc[1][1][1], 16);
        asm volatile("{\n.reg .pred p;\nsetp.ne.u32 p, %2, 0;\n@p st.global.u32 [%0], %1;\n}" ::"l"(outp), "r"(pack_bf16(o0, o1)),
                     "r"((uint32_t)(lane < 16 && h == NH)) : "memory");
    }
}

__device__ __noinline__ void f_collect(const unsigned (*flag)[32], unsigned full, const float4* src, unsigned todo, uint32_t sbase) {
    const int lane = threadIdx.x & 31, g = lane >> 2, t = lane & 3;
    const bool last = todo != 15;
    unsigned n = 0;
    while (todo) {
        const unsigned v = ld_acquire(&flag[t][0]);
        unsigned m = __ballot_sync(~0u, v == full) & todo;
        if (m == 0) {
            if (!last || __shfl_sync(~0u, v, 0) == 0) __nanosleep(200);
            if (++n > SPIN_LIMIT) __trap();
            continue;
        }
        __syncwarp();
        todo ^= m;
        if (last) TS(16);
        do {
            const int h0 = __ffs(m) - 1, h1 = 31 - __clz(m);
            m &= ~((1u << h0) | (1u << h1));
            float4 x[8];
#pragma unroll
            for (int b = 0; b < 8; b++) x[b] = ld_relaxed16(src + ((b & 4) ? h1 : h0) * 128 + (b & 3) * 32 + lane);
#pragma unroll
            for (int b = 0; b < 8; b++) {
                const uint32_t lo = pack_bf16(x[b].x, x[b].y), hi = pack_bf16(x[b].z, x[b].w);
                const uint32_t o = __shfl_xor_sync(~0u, (g & 1) ? lo : hi, 4);
                const uint32_t e0 = (g & 1) ? o : lo, e1 = (g & 1) ? hi : o;
                asm volatile("st.shared.v2.u32 [%0], {%1,%2};"
                             ::"r"(sbase + F_BF + ((b & 4) ? h1 : h0) * 1024 + t * 256 + ((b ^ t) & 3) * 64 + g * 8),
                               "r"(__byte_perm(e0, e1, 0x5410)), "r"(__byte_perm(e0, e1, 0x7632)) : "memory");
            }
            __syncwarp();
            if (lane < (h0 == h1 ? 1 : 2))
                asm volatile("mbarrier.arrive.shared::cta.b64 _, [%0];" ::"r"(sbase + F_BAR + 32 + (lane ? h1 : h0) * 8) : "memory");
        } while (m);
    }
    if (last) TS(17);
}

__device__ __noinline__ void f_project(const CUtensorMap* tm, int panel, int rank, int sl, int j, int delay, int step, unsigned tag, uint32_t sbase, uint64_t pol) {
    const int lane = threadIdx.x & 31, g = lane >> 2, t = lane & 3;
    const uint32_t wb = sbase + F_W - sl * 2 * SLOT, bars = sbase + F_BAR + 64 + sl * 32 * PH;
    const uint32_t wa = wb + ((lane & 7) + (lane >> 4) * 8) * 128 + (((2 * j + ((lane >> 3) & 1)) ^ (lane & 7)) * 16);
    const uint32_t ba = sbase + F_BF + (g & 3) * 64 + t * 16;
    const uint32_t rdst = mapa(sbase + F_RX + sl * 1024 + rank * 128 + g * 16 + (t & 1) * 8, 2 * j + (t >> 1));
    const uint32_t rbar = mapa(sbase + F_BAR + 16 + sl * 8, 2 * j + (t >> 1));
    unsigned n = 0;
    if (threadIdx.x >= 224) {
        if (lane == 0) asm volatile("prefetch.tensormap [%0];" ::"l"(tm) : "memory");
        unsigned long long v;
        while (!__all_sync(~0u, (v = ld_relaxed64(&g_dry[blockIdx.x >> 3][g])) >> 32 == tag)) {
            __nanosleep(200);
            if (++n > SPIN_LIMIT) __trap();
        }
        const uint32_t t0 = __shfl_sync(~0u, (uint32_t)v, 0);
        const uint32_t t1 = t0 + (__reduce_add_sync(~0u, (int)((uint32_t)v - t0)) >> 5);
        if (lane == 0) asm volatile("st.shared.u32 [%0+8], %1;\nmbarrier.arrive.shared::cta.b64 _, [%0];" ::"r"(sbase + F_BAR), "r"(t1) : "memory");
        TS(22);
    }
    mbar_wait(sbase + F_BAR, 0);
    if (lane == 0) {
        uint32_t due = lds32(sbase + F_BAR + 8) + delay;
#pragma unroll 1
        for (int q = j * PH; q < (j + 1) * PH; q++, due += step) {
            mbar_expect_tx(bars + q * 8, 16384 / PH);
            while ((int)(time_ns() - due) < 0) {}
            tma3d(wb + q * (16384 / PH), tm, 0, rank * 512 + q * (128 / PH), panel, bars + q * 8, pol);
        }
    }
    __syncwarp();
    TS(18);
#define NCH 2
    float acc[4][4];
#pragma unroll
    for (int i = 0; i < 16; i++) acc[i >> 2][i & 3] = 0.f;
    const bool up = t & 2;
#pragma unroll 1
    for (int h = 0; h < 4; h++) {
        uint32_t wp = wa + h * 16384, bar = bars + h * PH * 8, last = h == 3;
        mbar_spin(sbase + F_BAR + 32 + h * 8);
        uint32_t bf[4][4];
#pragma unroll
        for (int s = 0; s < 4; s++)
            asm volatile("ld.shared.v4.u32 {%0,%1,%2,%3}, [%4];" : "=r"(bf[s][0]), "=r"(bf[s][1]), "=r"(bf[s][2]), "=r"(bf[s][3])
                         : "r"(((ba + h * 1024) ^ (s * 64)) + s * 256) : "memory");
        asm volatile("" : "+r"(wp), "+r"(bar), "+r"(last));
#pragma unroll
        for (int q = 0; q < PH; q++) {
            mbar_spin(bar + q * 8);
            if (h == 3 && q == PH - 1) TS(19);
            uint32_t a[8 / PH][4];
#pragma unroll
            for (int s = 0; s < 8 / PH; s++) ldsm4t(a[s], wp + (q * (8 / PH) + s) * 2048);
#pragma unroll
            for (int s = 0; s < 8 / PH; s++) {
                const int k = q * (8 / PH) + s;
                mma16816(acc[s & (NCH - 1)], a[s], bf[k & 3][(k >> 2) * 2], bf[k & 3][(k >> 2) * 2 + 1]);
            }
        }
        float v0 = up ? acc[0][2] + acc[1][2] : acc[0][0] + acc[1][0], v1 = up ? acc[0][3] + acc[1][3] : acc[0][1] + acc[1][1];
        if (NCH == 4) {
            v0 = (v0 + (up ? acc[2][2] : acc[2][0])) + (up ? acc[3][2] : acc[3][0]);
            v1 = (v1 + (up ? acc[2][3] : acc[2][1])) + (up ? acc[3][3] : acc[3][1]);
        }
        asm volatile("{\n.reg .pred p;\nsetp.ne.u32 p, %4, 0;\n"
                     "@p st.async.weak.shared::cluster.mbarrier::complete_tx::bytes.v2.b32 [%0], {%1,%2}, [%3];\n}"
                     ::"r"(rdst), "r"(__float_as_uint(v0)), "r"(__float_as_uint(v1)), "r"(rbar), "r"(last) : "memory");
    }
    TS(20);
}

__device__ __noinline__ void f_receive(__nv_bfloat16* out, int sl, bool dry, uint32_t sbase) {
    const int lane = threadIdx.x & 31;
    out += (lane & 3) * (2 * DM) + (lane >> 2);
    uint32_t src = sbase + F_RX + sl * 1024 + lane * 4;
    asm volatile("" : "+l"(out), "+r"(src));
    asm volatile("{\n.reg .pred p;\n.reg .u32 n;\nmov.u32 n, 0;\nSPIN:\nmbarrier.test_wait.parity.acquire.cluster.shared::cta.b64 p, [%0], 0;\n"
                 "@p bra.uni DONE;\nadd.u32 n, n, 1;\nsetp.lt.u32 p, n, 0x4000000;\n@p bra.uni SPIN;\ntrap;\nDONE:\n}"
                 ::"r"(sbase + F_BAR + (dry ? 0 : 16 + sl * 8)) : "memory");
    float v[8];
#pragma unroll
    for (int r = 0; r < 8; r++) asm volatile("ld.shared.f32 %0, [%1];" : "=f"(v[r]) : "r"(src + r * 128) : "memory");
    const float o = ((v[0] + v[1]) + (v[2] + v[3])) + ((v[4] + v[5]) + (v[6] + v[7]));
    asm volatile("{\n.reg .pred p;\nsetp.eq.u32 p, %2, 0;\n@p st.global.u16 [%0], %1;\n}"
                 ::"l"(out), "h"((unsigned short)pack_bf16(o, 0.f)), "r"((uint32_t)dry) : "memory");
    TS(15);
}

__device__ __forceinline__ void b_final(const Params& p, uint32_t sbase, int blk, unsigned epoch, uint64_t pol) {
    const int warp = threadIdx.x >> 5;
    const int rank = blk & 7, sl = warp >> 2, panel = (blk >> 3) * 2 + sl;
    asm volatile("barrier.cluster.wait.acquire.aligned;" ::: "memory");
    if (warp == 0) f_collect(&g_cdone[4 * rank], epoch + 1, &g_octx[4 * rank * 128], 15, sbase);
    if ((warp & 3) == 0) {
        mbar_wait(sbase + F_BAR, 0);
        f_receive(p.out, sl, true, sbase);
    }
    f_project(&p.tm_fb, panel, rank, sl, warp & 3, B0 + (warp & 3) * BJ + sl * BS + rank * BR - max(0, (warp & 3) * 8 + rank - BK) * BC, BSTEP, epoch + 1, sbase, pol);
    if ((warp & 3) == 0) f_receive(p.out + DM + panel * 64 + rank * 8, sl, false, sbase);
}

constexpr int BS_WUK = 5, BS_Q = 9, BS_CKV = 11, BS_PART = 27, BS_WUV = 29, BS_END = 33;

__device__ __noinline__ void b_issue(const Params& p, int n, int bi, uint32_t sbase, uint64_t pol) {
    if (n >= BS_END || (n >= BS_Q && n < BS_CKV) || (n >= BS_PART && n < BS_WUV)) return;
    const uint32_t bar = sbase + M_BAR + (NSLOT + n % BRING) * 8;
    const CUtensorMap* tm;
    int row, panel = 2 * bi;
    if (n < BS_WUK) { tm = &p.tm_wq; row = n * 128; }
    else if (n < BS_Q) { tm = &p.tm_wuk; row = (n - BS_WUK) * 128; }
    else if (n < BS_PART) {
        tm = &p.tm_ckv; panel = 0;
        row = (bi >> 3) * SK + ((n - BS_CKV) * 8 + (bi & 7)) * 32;
    }
    else { tm = &p.tm_wuv; row = (n - BS_WUV) * 128; }
    mbar_expect_tx(bar, n == 0 ? 32768 + 4 * 1152 : 32768);
    tma3d(sbase + (n % BRING) * SLOT, tm, 0, row, panel, bar, pol);
}
__device__ __forceinline__ void b_issue_xchg(int n, const void* src, uint32_t sbase, uint64_t pol) {
    asm volatile("fence.proxy.async;" ::: "memory");
#pragma unroll
    for (int i = 0; i < 2; i++) {
        const uint32_t bar = sbase + M_BAR + (NSLOT + (n + i) % BRING) * 8;
        mbar_expect_tx(bar, 32768);
        bulk_load(sbase + ((n + i) % BRING) * SLOT, reinterpret_cast<const char*>(src) + i * 32768, 32768, bar, pol);
    }
}
__device__ __forceinline__ void b_wait(int n, uint32_t sbase) {
    mbar_wait(sbase + M_BAR + (NSLOT + n % BRING) * 8, (n / BRING) & 1);
}

__device__ __noinline__ void b_gemm(const Params& p, uint32_t sbase, int n0, int n1, int ktot, uint32_t xh, uint32_t xl, int pitch,
                                    int bi, uint64_t pol) {
    const int tid = threadIdx.x, warp = tid >> 5, lane = tid & 31, g = lane >> 2, t = lane & 3;
    const uint32_t woff = (warp >> 2) * 16384 + (lane & 15) * 128 + ((((warp & 3) * 2 + (lane >> 4)) ^ (lane & 7)) * 16);
    const uint32_t xoff = (g & 3) * pitch + t * 4;
    float acc[2][4];
#pragma unroll
    for (int i = 0; i < 8; i++) acc[i >> 2][i & 3] = 0.f;
#pragma unroll 1
    for (int n = n0; n < n1; n++) {
        b_wait(n, sbase);
        const uint32_t slot = sbase + (n % BRING) * SLOT + woff;
        const int k0 = (n - n0) * 128;
        const int ns = min(8, (ktot - k0) >> 4);
#pragma unroll 2
        for (int s = 0; s < ns; s++) {
            uint32_t a[4], w[4];
            const uint32_t xo = xoff + (k0 + 16 * s) * 2;
            a[0] = lds32(xh + xo); a[2] = lds32(xh + xo + 16);
            a[1] = xl ? lds32(xl + xo) : 0u; a[3] = xl ? lds32(xl + xo + 16) : 0u;
            ldsm4t(w, slot + s * 2048);
            mma16816(acc[0], a, w[0], w[1]);
            mma16816(acc[1], a, w[2], w[3]);
        }
        __syncthreads();
        if (tid == 0) b_issue(p, n + BD, bi, sbase, pol);
    }
    if (g < 4) {
#pragma unroll
        for (int j = 0; j < 2; j++)
            asm volatile("st.shared.u32 [%0], %1;" ::"r"(sbase + M_QB + g * QP + (warp * 16 + j * 8 + t * 2) * 2),
                         "r"(pack_bf16(acc[j][0] + acc[j][2], acc[j][1] + acc[j][3])) : "memory");
    }
    __syncthreads();
}

__device__ __forceinline__ void b_exchange(unsigned* c, int n, const void* src, uint32_t sbase, uint64_t pol) {
    TS(n == BS_Q ? 24 : 28);
    __syncthreads();
    if (threadIdx.x == 0) {
        TS(n == BS_Q ? 25 : 29);
        fence_gpu();
        TS(n == BS_Q ? 26 : 30);
        red_add_u32(c, 1u);
        wait_count(c, NBCTA);
        TS(n == BS_Q ? 27 : 31);
        b_issue_xchg(n, src, sbase, pol);
    }
}

template <bool CLU>
__device__ __noinline__ void b_chain(const Params& p, char* smem, uint32_t sbase, int bi, unsigned epoch, uint64_t pol) {
    const int tid = threadIdx.x, warp = tid >> 5, lane = tid & 31, g = lane >> 2, t = lane & 3;
    unsigned (*ctl)[32] = g_ctl[epoch & 1];
    float* red = reinterpret_cast<float*>(smem + 5 * SLOT);
    __syncthreads();
    b_gemm(p, sbase, 0, BS_WUK, DM, sbase + M_XB, 0, XP, bi, pol);
    TS(6);
    {
        uint32_t Q[16];
#pragma unroll
        for (int c = 0; c < 16; c++) Q[c] = lds32(sbase + M_QB + (g & 3) * QP + c * 16 + t * 4);
        float* qa = reinterpret_cast<float*>(smem + M_QA);
#pragma unroll 1
        for (int n = BS_WUK; n < BS_Q; n++) {
            b_wait(n, sbase);
            const uint32_t base = sbase + (n % BRING) * SLOT + (warp * 16 + (lane & 15)) * 128;
            float d[2][4];
#pragma unroll
            for (int i = 0; i < 8; i++) d[i >> 2][i & 3] = 0.f;
#pragma unroll
            for (int s = 0; s < 8; s++) {
                uint32_t a[4];
                ldsm4(a, base + (s >> 2) * 16384 + (((2 * (s & 3) + (lane >> 4)) ^ (lane & 7)) * 16));
                mma16816(d[s & 1], a, Q[2 * s], Q[2 * s + 1]);
            }
            const int c = (n - BS_WUK) * 128 + warp * 16 + g + 8 * (t >> 1);
            qa[(2 * (t & 1)) * 512 + c] = (t & 2) ? d[0][2] + d[1][2] : d[0][0] + d[1][0];
            qa[(2 * (t & 1) + 1) * 512 + c] = (t & 2) ? d[0][3] + d[1][3] : d[0][1] + d[1][1];
            __syncthreads();
            if (tid == 0) b_issue(p, n + BD, bi, sbase, pol);
        }
#pragma unroll 1
        for (int r = 0; r < 2; r++) {
            const int id = tid + r * 256;
            const int b = id >> 7, c0 = ((id >> 2) & 31) * 16 + (id & 3) * 2;
            const float2 u0 = *reinterpret_cast<const float2*>(qa + b * 512 + c0);
            const float2 u1 = *reinterpret_cast<const float2*>(qa + b * 512 + c0 + 8);
            const uint32_t h0 = pack_bf16(u0.x, u0.y), h1 = pack_bf16(u1.x, u1.y);
            const uint32_t l0 = pack_bf16(u0.x - bf_lo(h0), u0.y - bf_hi(h0)), l1 = pack_bf16(u1.x - bf_lo(h1), u1.y - bf_hi(h1));
            g_qabs[((id >> 2) * 4 + (bi >> 3)) * 32 + (bi & 7) * 4 + (id & 3)] = make_uint4(h0, l0, h1, l1);
        }
    }
    b_exchange(&ctl[C_BBAR][0], BS_Q, &g_qabs[(bi >> 3) * 4096], sbase, pol);
    {
        uint32_t qf[4][4][4];
        b_wait(BS_Q + (warp >> 2), sbase);
        TS(7);
        {
            const uint4* qs = reinterpret_cast<const uint4*>(smem + ((BS_Q + (warp >> 2)) % BRING) * SLOT) + (warp & 3) * 512 + lane;
#pragma unroll
            for (int s = 0; s < 4; s++)
#pragma unroll
                for (int i = 0; i < 4; i++) {
                    const uint4 v = qs[(s * 4 + i) * 32];
                    qf[i][s][0] = v.x; qf[i][s][1] = v.y; qf[i][s][2] = v.z; qf[i][s][3] = v.w;
                }
        }
        __syncthreads();
        if (tid == 0) { b_issue(p, BS_Q + BD, bi, sbase, pol); b_issue(p, BS_Q + 1 + BD, bi, sbase, pol); }
        float acc[2][8][4];
#pragma unroll
        for (int i = 0; i < 2; i++)
#pragma unroll
            for (int j = 0; j < 8; j++) { acc[i][j][0] = acc[i][j][1] = acc[i][j][2] = acc[i][j][3] = 0.f; }
        float mrun = -INFINITY, lrun = 0.f;
        const int head = tid >> 3, kq = tid & 7;
        float* alpha = reinterpret_cast<float*>(smem + M_ALPHA);
        for (int n = BS_CKV; n < BS_PART; n++) {
            b_wait(n, sbase);
            const uint32_t slot = sbase + (n % BRING) * SLOT;
            float sc[4][4][4];
#pragma unroll
            for (int i = 0; i < 4; i++)
#pragma unroll
                for (int j = 0; j < 4; j++) { sc[i][j][0] = sc[i][j][1] = sc[i][j][2] = sc[i][j][3] = 0.f; }
#pragma unroll
            for (int j = 0; j < 4; j++)
#pragma unroll
                for (int sp = 0; sp < 2; sp++) {
                    uint32_t bf[4];
                    ldsm4(bf, slot + warp * 4096 + (8 * j + (lane & 7)) * 128 + (((4 * sp + (lane >> 3)) ^ (lane & 7)) * 16));
#pragma unroll
                    for (int i = 0; i < 4; i++) {
                        mma16816(sc[i][j], qf[i][2 * sp], bf[0], bf[1]);
                        mma16816(sc[i][j], qf[i][2 * sp + 1], bf[2], bf[3]);
                    }
                }
#pragma unroll
            for (int i = 0; i < 4; i++)
#pragma unroll
                for (int j = 0; j < 4; j++)
                    *reinterpret_cast<float2*>(red + warp * 1024 + (8 * i + g) * 32 + ((8 * j) ^ (8 * (g & 3))) + 2 * t) =
                        make_float2(sc[i][j][0] + sc[i][j][2], sc[i][j][1] + sc[i][j][3]);
            __syncthreads();
            if (tid == 0 && n > BS_CKV) b_issue(p, n - 1 + BD, bi, sbase, pol);
            {
                float4 s = make_float4(0.f, 0.f, 0.f, 0.f);
#pragma unroll
                for (int w = 0; w < 8; w++) {
                    const float4 v = *reinterpret_cast<const float4*>(red + w * 1024 + head * 32 + ((4 * kq) ^ (8 * (head & 3))));
                    s.x += v.x; s.y += v.y; s.z += v.z; s.w += v.w;
                }
                const uint32_t r0 = pack_bf16(s.x, s.y), r1 = pack_bf16(s.z, s.w);
                const uint32_t s0 = pack_bf16(bf_lo(r0) * SCALE, bf_hi(r0) * SCALE);
                const uint32_t s1 = pack_bf16(bf_lo(r1) * SCALE, bf_hi(r1) * SCALE);
                const float f0 = bf_lo(s0), f1 = bf_hi(s0), f2 = bf_lo(s1), f3 = bf_hi(s1);
                float mx = fmaxf(fmaxf(f0, f1), fmaxf(f2, f3));
                mx = fmaxf(mx, __shfl_xor_sync(~0u, mx, 1));
                mx = fmaxf(mx, __shfl_xor_sync(~0u, mx, 2));
                mx = fmaxf(mx, __shfl_xor_sync(~0u, mx, 4));
                const float mnew = fmaxf(mrun, mx);
                const float al = expsub(mrun, mnew);
                const float p0 = expsub(f0, mnew), p1 = expsub(f1, mnew), p2 = expsub(f2, mnew), p3 = expsub(f3, mnew);
                lrun = lrun * al + ((p0 + p1) + (p2 + p3));
                mrun = mnew;
                *reinterpret_cast<uint2*>(smem + M_P + head * 80 + kq * 8) = make_uint2(pack_bf16(p0, p1), pack_bf16(p2, p3));
                if (kq == 0) alpha[head] = al;
            }
            __syncthreads();
            {
                uint32_t pf[2][2][4];
#pragma unroll
                for (int i = 0; i < 2; i++)
#pragma unroll
                    for (int ks = 0; ks < 2; ks++)
                        ldsm4(pf[i][ks], sbase + M_P + (16 * i + (lane & 15)) * 80 + (16 * ks + 8 * (lane >> 4)) * 2);
#pragma unroll
                for (int i = 0; i < 2; i++) {
                    const float a0 = alpha[16 * i + g], a1 = alpha[16 * i + 8 + g];
#pragma unroll
                    for (int j = 0; j < 8; j++) { acc[i][j][0] *= a0; acc[i][j][1] *= a0; acc[i][j][2] *= a1; acc[i][j][3] *= a1; }
                }
#pragma unroll
                for (int j = 0; j < 8; j++) {
                    uint32_t bf[4];
                    ldsm4t(bf, slot + warp * 4096 + lane * 128 + ((j ^ (lane & 7)) * 16));
#pragma unroll
                    for (int i = 0; i < 2; i++) {
                        mma16816(acc[i][j], pf[i][0], bf[0], bf[1]);
                        mma16816(acc[i][j], pf[i][1], bf[2], bf[3]);
                    }
                }
            }
        }
        __syncthreads();
        if (tid == 0) b_issue(p, BS_PART - 1 + BD, bi, sbase, pol);
        lrun += __shfl_xor_sync(~0u, lrun, 1);
        lrun += __shfl_xor_sync(~0u, lrun, 2);
        lrun += __shfl_xor_sync(~0u, lrun, 4);
        if (kq == 0) g_bml[head * NBCTA + bi] = make_float2(mrun, lrun);
#pragma unroll
        for (int i = 0; i < 2; i++)
#pragma unroll
            for (int j = 0; j < 8; j++) {
                g_bpart[((16 * i + g) * NBCTA + bi) * 256 + warp * 32 + j * 4 + t] = make_float2(acc[i][j][0], acc[i][j][1]);
                g_bpart[((16 * i + 8 + g) * NBCTA + bi) * 256 + warp * 32 + j * 4 + t] = make_float2(acc[i][j][2], acc[i][j][3]);
            }
    }
    if (!CLU) {
#pragma unroll 1
        for (int i = tid; i < NH * 36; i += 256) g_outb[bi * NH * 36 + i] = make_uint4(0u, epoch, 0u, epoch);
    }
    b_exchange(&ctl[C_BBAR + 1][0], BS_PART, &g_bpart[bi * NBCTA * 256], sbase, pol);
    {
        float* omega = reinterpret_cast<float*>(smem + M_OMEGA);
        if (warp == 0) {
            __syncwarp();
            const uint2 ml = ld_relaxed8(&g_bml[bi * NBCTA + lane]);
            const float ms = __uint_as_float(ml.x);
            float m = ms;
            m = fmaxf(m, __shfl_xor_sync(~0u, m, 1));
            m = fmaxf(m, __shfl_xor_sync(~0u, m, 2));
            m = fmaxf(m, __shfl_xor_sync(~0u, m, 4));
            const float w = expsub(ms, m);
            float l = w * __uint_as_float(ml.y);
            l += __shfl_xor_sync(~0u, l, 1);
            l += __shfl_xor_sync(~0u, l, 2);
            l += __shfl_xor_sync(~0u, l, 4);
            omega[lane] = w / l;
        }
        __syncthreads();
        b_wait(BS_PART, sbase);
        b_wait(BS_PART + 1, sbase);
#pragma unroll 1
        for (int b = 0; b < 4; b++) {
            const float2* ps = reinterpret_cast<const float2*>(smem + ((BS_PART + (b >> 1)) % BRING) * SLOT) + (b & 1) * 2048 + tid;
            float c0 = 0.f, c1 = 0.f;
#pragma unroll
            for (int s = 0; s < 8; s++) {
                const float w = omega[b * 8 + s];
                const float2 v = ps[s * 256];
                c0 = fmaf(w, v.x, c0);
                c1 = fmaf(w, v.y, c1);
            }
            const uint32_t hi = pack_bf16(c0, c1);
            *reinterpret_cast<uint32_t*>(smem + M_CH + b * CP + tid * 4) = hi;
            *reinterpret_cast<uint32_t*>(smem + M_CL + b * CP + tid * 4) = pack_bf16(c0 - bf_lo(hi), c1 - bf_hi(hi));
        }
        __syncthreads();
        if (tid == 0) { b_issue(p, BS_PART + BD, bi, sbase, pol); b_issue(p, BS_PART + 1 + BD, bi, sbase, pol); }
    }
    b_gemm(p, sbase, BS_WUV, BS_END, 512, sbase + M_CH, sbase + M_CL, CP, bi, pol);
    TS(12);
    if (CLU) {
        if (warp < 4) {
            const unsigned short* c = reinterpret_cast<const unsigned short*>(smem + M_QB + warp * QP) + 16 * t + g;
            g_octx[(bi * 4 + warp) * 32 + lane] = make_float4(bf_lo(c[0]), bf_lo(c[8]), bf_lo(c[64]), bf_lo(c[72]));
        }
        __syncthreads();
        if (tid == 0) asm volatile("st.release.gpu.global.u32 [%0], %1;" ::"l"(&g_cdone[bi][0]), "r"(epoch + 1) : "memory");
        return;
    }
    if (tid == 0) {
#pragma unroll 1
        for (int i = 0; i < 4; i++) {
            mbar_expect_tx(sbase + M_BAR + i * 8, 36864);
            tma3d(sbase + i * 36864, &p.tm_wo, 0, bi * 128 + i * 32, 0, sbase + M_BAR + i * 8, pol);
        }
    }
    TS(8);
    {
        float acc[9][4];
#pragma unroll
        for (int j = 0; j < 9; j++) { acc[j][0] = acc[j][1] = acc[j][2] = acc[j][3] = 0.f; }
#pragma unroll 1
        for (int i = 0; i < 4; i++) {
            const uint32_t xo = sbase + M_QB + (g & 3) * QP + i * 64 + t * 4;
            const uint32_t a0[4] = {lds32(xo), 0u, lds32(xo + 16), 0u}, a1[4] = {lds32(xo + 32), 0u, lds32(xo + 48), 0u};
            mbar_wait(sbase + M_BAR + i * 8, 0);
#pragma unroll
            for (int j = 0; j < 9; j++) {
                const int nt = warp * 9 + j;
                uint32_t w[4];
                ldsm4t(w, sbase + i * 36864 + (nt >> 3) * 4096 + lane * 128 + (((nt & 7) ^ (lane & 7)) * 16));
                mma16816(acc[j], a0, w[0], w[1]);
                mma16816(acc[j], a1, w[2], w[3]);
            }
        }
        if (g < 4) {
#pragma unroll
            for (int j = 0; j < 9; j++) {
                const int c2 = (warp * 9 + j) * 4 + t;
                st_tagged2(&g_outb[((c2 / 9) * NH + bi) * 36 + g * 9 + c2 % 9], acc[j][0], acc[j][1], epoch + 1);
            }
        }
    }
    TS(9);
    {
        const uint4* src = g_outb + (bi * NH + (tid >> 3)) * 36 + (tid & 7);
        float2* part = reinterpret_cast<float2*>(red);
        unsigned n = 0;
        while (true) {
            ulonglong2 v[5];
            bool ok = true;
#pragma unroll
            for (int i = 0; i < 5; i++)
                if (i < 4 || (tid & 7) < 4) v[i] = ld_tagged2(src + i * 8);
#pragma unroll
            for (int i = 0; i < 5; i++)
                if (i < 4 || (tid & 7) < 4) {
                    ok = ok && (unsigned)(v[i].x >> 32) == epoch + 1 && (unsigned)(v[i].y >> 32) == epoch + 1;
                    part[(tid >> 3) * 36 + (tid & 7) + i * 8] = make_float2(__uint_as_float((unsigned)v[i].x), __uint_as_float((unsigned)v[i].y));
                }
            if (ok) break;
            __nanosleep(400);
            if (++n > SPIN_LIMIT) __trap();
        }
        __syncthreads();
        if (tid < 36) {
            float s0 = 0.f, s1 = 0.f;
#pragma unroll 8
            for (int h = 0; h < NH; h++) { const float2 v = part[h * 36 + tid]; s0 += v.x; s1 += v.y; }
            *reinterpret_cast<uint32_t*>(p.out + (tid / 9) * 2 * DM + DM + bi * 18 + (tid % 9) * 2) = pack_bf16(s0, s1);
        }
    }
    TS(10);
}

template <bool CLU>
__global__ void __launch_bounds__(256, 1) fused_decode_kernel(const __grid_constant__ Params p) {
    asm volatile("{\n.reg .pred p;\n.reg .u32 a;\n.reg .u64 b;\nsub.u32 a, %1, %4;\nsetp.lt.u32 p, a, %3;\nmad.lo.u32 a, %2, %6, %1;\n"
                 "mad.wide.u32 b, a, %5, %0;\n"
                 "@p prefetch.global.L2 [b];\n}"
                 ::"l"(p.pf), "r"(threadIdx.x), "r"(blockIdx.x), "n"(PFN), "n"(PF0), "n"(PFS), "n"(PFC) : "memory");
    extern __shared__ __align__(1024) char smem_raw[];
    const uint32_t sbase = (smem_u32(smem_raw) + 1023u) & ~1023u;
    if (CLU && threadIdx.x < 32 && blockIdx.x >= NBCTA) {
        const unsigned u0 = blockIdx.x - NBCTA, u1 = u0 + 8 * MINCL - NBCTA;
        asm volatile("{\n.reg .pred p;\nelect.sync _|p, 0xffffffff;\n"
                     "@p mbarrier.init.shared::cta.b64 [%0], 1;\n"
                     "@p mbarrier.init.shared::cta.b64 [%0+8], 1;\n"
                     "@p fence.mbarrier_init.release.cluster;\n"
                     "@p mbarrier.arrive.expect_tx.shared::cta.b64 _, [%0], 32768;\n"
                     "@p cp.async.bulk.shared::cluster.global.mbarrier::complete_tx::bytes.L2::cache_hint [%1], [%2], 32768, [%0], %4;\n"
                     "@p mbarrier.arrive.expect_tx.shared::cta.b64 _, [%0+8], 32768;\n"
                     "@p cp.async.bulk.shared::cluster.global.mbarrier::complete_tx::bytes.L2::cache_hint [%1+32768], [%3], 32768, [%0+8], %4;\n}"
                     ::"r"(sbase + M_BAR), "r"(sbase), "l"(reinterpret_cast<const char*>(p.kc) + (size_t)u0 * TILE_BYTES),
                       "l"(reinterpret_cast<const char*>(p.kc) + (size_t)((u1 >> 7) * 1024 + (u1 & 127)) * TILE_BYTES), "l"(0x12F0000000000000ull) : "memory");
    }
    char* smem = smem_raw + (sbase - smem_u32(smem_raw));
    const int tid = threadIdx.x, warp = tid >> 5, lane = tid & 31;
    const int blk = blockIdx.x;
    const bool isB = CLU ? blk < NBCTA : (blk & 3) == 0 && (blk >> 2) < NBCTA;
    const int bi = CLU ? blk : blk >> 2;
    const int nb = CLU ? blk - NBCTA : blk - min(NBCTA, (blk + 3) >> 2);
    const int nblk = CLU ? 8 * MINCL : gridDim.x, nnb = nblk - NBCTA;
    const int nstatic = nnb * (NW + XW);
    uint64_t pol;
    asm volatile("createpolicy.fractional.L2::evict_first.b64 %0, 1.0;" : "=l"(pol));
    const uint32_t wbar = sbase + M_BAR + warp * 8, wslot = sbase + warp * SLOT;
    const int u0 = warp * nnb + nb;
    const bool hold = ((blk >> 2) >> KMIN << KMIN) * 4 * UPP < nstatic;
    const uint32_t jbar = sbase + M_BAR + (NSLOT + BRING) * 8;
    if (warp == 7) {
        if (lane == 0 && blk < 128) {
            mbar_init(jbar, 1);
            asm volatile("fence.mbarrier_init.release.cluster;" ::: "memory");
            uint64_t poln;
            asm volatile("createpolicy.fractional.L2::evict_normal.b64 %0, 1.0;" : "=l"(poln));
            mbar_expect_tx(jbar, 36864 + 4 * 1152);
            tma3d(sbase + J0W, &p.tm_j0, blk * 32, 0, 0, jbar, poln);
            bulk_load(sbase + M_XA, p.xa, 4608, jbar, poln);
        }
        if (lane < 8) reinterpret_cast<unsigned*>(smem + M_HELP)[lane] = 0;
        __syncwarp();
        if (!isB) asm volatile("bar.arrive 2, %0;" ::"n"(32 * (NW + XW + 1)) : "memory");
    }
    if (warp < 4 && lane == 0 && (!CLU || isB || warp >= 2)) {
        mbar_init(wbar, 1);

        asm volatile("fence.mbarrier_init.release.cluster;" ::: "memory");
        if (warp < NEARLY && !isB && !hold) {
            mbar_expect_tx(wbar, TILE_BYTES);
            bulk_load(wslot, block_src(p.kc, unit_block<CLU>(u0)), TILE_BYTES, wbar, pol);
        }
    }
    unsigned epoch = 0;
    if (lane == 0) epoch = ld_relaxed4(&g_epoch);
    TS(0);
    if (CLU) {
        if (warp == 6) {
            if (lane < 8 + 8 * PH && lane != 1) mbar_init(sbase + F_BAR + lane * 8, 1);
            if ((lane >> 1) == 1) mbar_expect_tx(sbase + F_BAR + lane * 8, 1024);
            asm volatile("fence.mbarrier_init.release.cluster;" ::: "memory");
        }
        asm volatile("barrier.cluster.arrive.relaxed.aligned;" ::: "memory");
    }
    if ((warp >> 1) == 2 && blk < 128) st_relaxed64(&g_qll[((tid - 128) >> 4) * 2048 + blk * 16 + (tid & 15)], 0ull);
    if (isB || warp >= NW + XW) epoch = __shfl_sync(~0u, epoch, 0);
    if (isB && warp == 3) asm volatile("bar.sync 1, 160;" ::: "memory");
    if (isB && tid == 96) {
#pragma unroll 1
        for (int i = 0; i < BRING; i++) mbar_init(sbase + M_BAR + (NSLOT + i) * 8, 1);
        asm volatile("fence.mbarrier_init.release.cluster;" ::: "memory");
        if (hold) { unsigned n = 0; while (ld_acquire_cta_shared(sbase + M_HELP + 24) < 2) { if (++n > (SPIN_LIMIT << 4)) __trap(); } }
#pragma unroll 1
        for (int b = 0; b < 4; b++) bulk_load(sbase + M_XB + b * XP, p.xb + b * DM, 1152, sbase + M_BAR + NSLOT * 8, pol);
#pragma unroll 1
        for (int n = 0; n < BD; n++) b_issue(p, n, bi, sbase, pol);
    }
    if (warp >= 4 && blk < 128) {
        const int g = lane >> 2, t = lane & 3, j = tid - 128;
        asm volatile("bar.sync 1, %0;" ::"r"(isB ? 160 : 128) : "memory");
#pragma unroll 1
        for (int sl = blk, ph = 0;; sl += 128 - nblk, ph = 1) {
        mbar_wait(jbar, ph);
        TS(13);
        float acc[4][4];
#pragma unroll
        for (int i = 0; i < 16; i++) acc[i >> 2][i & 3] = 0.f;
        const uint32_t wa = sbase + J0W + ((warp - 4) * 144 + (lane & 15)) * 64;
        const uint32_t sw = (lane >> 1) & 3, xa = sbase + M_XA + (g & 3) * 1152 + (warp - 4) * 288 + t * 4;
#pragma unroll 3
        for (int s = 0; s < 9; s++) {
            const uint32_t a[4] = {lds32(xa + s * 32), 0u, lds32(xa + s * 32 + 16), 0u};
            uint32_t w0[4], w1[4];
            ldsm4t(w0, wa + s * 1024 + (((lane >> 4) ^ sw) * 16));
            ldsm4t(w1, wa + s * 1024 + (((2 + (lane >> 4)) ^ sw) * 16));
            mma16816(acc[0], a, w0[0], w0[1]);
            mma16816(acc[1], a, w0[2], w0[3]);
            mma16816(acc[2], a, w1[0], w1[1]);
            mma16816(acc[3], a, w1[2], w1[3]);
        }
        float2* j0 = reinterpret_cast<float2*>(smem + M_J0);
        if (g < 4) {
#pragma unroll
            for (int i = 0; i < 4; i++) j0[(warp - 4) * 64 + g * 16 + i * 4 + t] = make_float2(acc[i][0], acc[i][1]);
        }
        asm volatile("bar.sync 1, 128;" ::: "memory");
        const bool again = sl == blk && blk + 128 - nblk >= nblk;
        if (again && tid == 224) {
            mbar_expect_tx(jbar, 36864);
            tma3d(sbase + J0W, &p.tm_j0, (blk + 128 - nblk) * 32, 0, 0, jbar, pol);
        }
        if (warp < 6) {
            const float2 v0 = j0[j], v1 = j0[64 + j], v2 = j0[128 + j], v3 = j0[192 + j];
            st_relaxed64(&g_qll[(j >> 4) * 2048 + sl * 16 + (j & 15)],
                         (unsigned long long)pack_bf16((v0.x + v1.x) + (v2.x + v3.x), (v0.y + v1.y) + (v2.y + v3.y)) |
                             ((unsigned long long)(epoch + 1) << 32));
            __syncwarp();
            if (lane == 0) asm volatile("red.relaxed.cta.shared::cta.add.u32 [%0], 1;" ::"r"(sbase + M_HELP + 24) : "memory");
        } else if (warp == 7) {
            if (blk < C_LINES) g_ctl[(epoch & 1) ^ 1][blk][lane] = 0;
        }
        TS(1);
        if (!again) break;
        asm volatile("bar.sync 1, 128;" ::: "memory");
        }
    }
    if (isB) {
        b_chain<CLU>(p, smem, sbase, bi, epoch, pol);
        if (CLU) b_final(p, sbase, blk, epoch, pol);
        return;
    }
    const int sl = nb >> 3, rank = blk & 7;
    if (warp < NW + XW) {
        a_worker<CLU>(p, u0, warp >= NW + ((nb & 3) < (CLU ? X3C : X3) ? 1 : 0), warp < NEARLY && !hold, hold, nstatic, wslot, wbar, sbase + M_HELP,
                      epoch, pol);
        const bool two = sl < 9 && rank == 7;
        if (CLU && (warp == 3 || (warp == 2 && two)) && sl < 10) {
            epoch = __shfl_sync(~0u, epoch, 0);
            unsigned n = 0;
            while (ld_acquire_cta_shared(sbase + M_HELP + 12) == 0) { __nanosleep(1000); if (++n > SPIN_LIMIT) __trap(); }
            asm volatile("barrier.cluster.wait.acquire.aligned;" ::: "memory");
            f_collect((sl < 9 ? g_vdone : g_cdone) + 4 * rank, sl < 9 ? 4 * UPP : epoch + 1, (sl < 9 ? g_oacc : g_octx) + 4 * rank * 128,
                      two ? (warp == 2 ? CM2 : 15 - CM2) : 15, sbase);
            if (warp == 2) return;
            mbar_wait(sbase + F_BAR, 0);
#pragma unroll 1
            for (int i = 0; i < 2; i++) f_receive(p.out + (sl < 9 ? sl * 64 : DM + 512) + rank * 8, 0, i == 0, sbase);
        }
        return;
    }
    if (warp == 7) {
#pragma unroll 1
        for (int i = nb; i < 4 * NH; i += nnb) g_oacc[i * 32 + lane] = make_float4(0.f, 0.f, 0.f, 0.f);
        if (nb < NREP * NH) g_vdone[nb][lane] = 0;
        __syncwarp();
        k_helper(sbase + M_HELP, epoch);
        if (nb == 0 && lane == 0) g_epoch = epoch + 1;
        __syncwarp();
    }
    if (CLU) {
        if (sl < 10) {
            const CUtensorMap* tm = sl < 9 ? &p.tm_fa : &p.tm_fb;
            asm volatile("barrier.cluster.wait.acquire.aligned;" ::: "memory");
            f_project(tm, min(sl, 8), rank, 0, warp & 3, A0 + (warp & 3) * AJ + rank * AR - max(0, (warp & 3) * 8 + rank - AK) * AC, ASTEP, epoch + 1, sbase, pol);
        }
    } else if (warp == 6 && nb < NFIN) {
        finisher(p, sbase, nb);
        TS(4);
    } else if (warp != 7 && warp >= 6 - NPOLL && nb < NFIN) {
        v_poller(sbase, nb, warp - (6 - NPOLL));
    }
}

}

typedef CUresult (*EncodeFn)(CUtensorMap*, CUtensorMapDataType, cuuint32_t, void*, const cuuint64_t*, const cuuint64_t*,
                             const cuuint32_t*, const cuuint32_t*, CUtensorMapInterleave, CUtensorMapSwizzle,
                             CUtensorMapL2promotion, CUtensorMapFloatOOBfill);

extern "C" void kernel_launch(void* const* d_in, const int* in_sizes, int n_in, void* d_out, int out_size) {
    (void)in_sizes; (void)n_in; (void)out_size;
    static int nsm = 0, ncl = 0;
    static EncodeFn encode = nullptr;
    cudaLaunchConfig_t cfg = {};
    cudaLaunchAttribute at[1];
    at[0].id = cudaLaunchAttributeClusterDimension;
    at[0].val.clusterDim.x = 8; at[0].val.clusterDim.y = 1; at[0].val.clusterDim.z = 1;
    cfg.blockDim = dim3(256); cfg.dynamicSmemBytes = SMEM_BYTES; cfg.stream = cudaStreamPerThread; cfg.attrs = at; cfg.numAttrs = 1;
    if (nsm == 0) {
        int dev = 0;
        cudaGetDevice(&dev);
        cudaDeviceGetAttribute(&nsm, cudaDevAttrMultiProcessorCount, dev);
        cudaFuncSetAttribute(fused_decode_kernel<false>, cudaFuncAttributeMaxDynamicSharedMemorySize, SMEM_BYTES);
        cudaFuncSetAttribute(fused_decode_kernel<true>, cudaFuncAttributeMaxDynamicSharedMemorySize, SMEM_BYTES);
        cfg.gridDim = dim3(128);
        if (cudaOccupancyMaxActiveClusters(&ncl, fused_decode_kernel<true>, &cfg) != cudaSuccess) { ncl = 0; (void)cudaGetLastError(); }
        if (ncl > MINCL) ncl = MINCL;
        void* fn = nullptr;
        cudaDriverEntryPointQueryResult qr;
        cudaGetDriverEntryPoint("cuTensorMapEncodeTiled", &fn, cudaEnableDefault, &qr);
        encode = (EncodeFn)fn;
    }
    Params p;
    auto panels = [&](CUtensorMap* tm, void* ptr, int rows, int cols, int box_rows, int box_panels,
                      CUtensorMapL2promotion promo = CU_TENSOR_MAP_L2_PROMOTION_L2_256B) {
        const cuuint64_t gd[3] = {64, (cuuint64_t)rows, (cuuint64_t)(cols / 64)}, gs[2] = {(cuuint64_t)cols * 2, 128};
        const cuuint32_t box[3] = {64, (cuuint32_t)box_rows, (cuuint32_t)box_panels}, es[3] = {1, 1, 1};
        encode(tm, CU_TENSOR_MAP_DATA_TYPE_BFLOAT16, 3, ptr, gd, gs, box, es, CU_TENSOR_MAP_INTERLEAVE_NONE,
               CU_TENSOR_MAP_SWIZZLE_128B, promo, CU_TENSOR_MAP_FLOAT_OOB_FILL_NONE);
    };
    panels(&p.tm_wq, d_in[7], DM, 4096, 128, 2);
    panels(&p.tm_wuk, d_in[8], 512, 4096, 128, 2);
    panels(&p.tm_wuv, d_in[9], 512, 4096, 128, 2);
    panels(&p.tm_wo, d_in[10], 4096, DM, 32, 9);
    panels(&p.tm_ckv, d_in[6], 4 * SK, 512, 32, 8);
    panels(&p.tm_fa, d_in[4], 4096, DM, 128 / PH, 1, CU_TENSOR_MAP_L2_PROMOTION_L2_128B);
    panels(&p.tm_fb, d_in[10], 4096, DM, 128 / PH, 1, CU_TENSOR_MAP_L2_PROMOTION_L2_128B);
    {
        const cuuint64_t gd[3] = {4096, 192, 3}, gs[2] = {8192, 192 * 8192};
        const cuuint32_t box[3] = {32, 192, 3}, es[3] = {1, 1, 1};
        encode(&p.tm_j0, CU_TENSOR_MAP_DATA_TYPE_BFLOAT16, 3, d_in[3], gd, gs, box, es, CU_TENSOR_MAP_INTERLEAVE_NONE,
               CU_TENSOR_MAP_SWIZZLE_64B, CU_TENSOR_MAP_L2_PROMOTION_L2_128B, CU_TENSOR_MAP_FLOAT_OOB_FILL_NONE);
    }
    p.xa = (const __nv_bfloat16*)d_in[0];
    p.kc = (const __nv_bfloat16*)d_in[1];
    p.vc = (const __nv_bfloat16*)d_in[2];
    p.pf = (const char*)d_in[1] + (size_t)PFOFF * TILE_BYTES - PF0 * PFS;
    p.wo = (const __nv_bfloat16*)d_in[4];
    p.xb = (const __nv_bfloat16*)d_in[5];
    p.out = (__nv_bfloat16*)d_out;
    if (ncl >= MINCL) {
        cfg.gridDim = dim3(8 * ncl);
        cudaLaunchKernelEx(&cfg, fused_decode_kernel<true>, p);
    } else {
        fused_decode_kernel<false><<<nsm, 256, SMEM_BYTES, cudaStreamPerThread>>>(p);
    }
}
```

```cpp
#include <cuda_runtime.h>
#include <cuda.h>
#include <cuda_bf16.h>
#include <stdint.h>

namespace {

constexpr int NH = 32, SK = 4096, DM = 576;
constexpr int KEYS = 128;
constexpr int UPP = SK / KEYS;
constexpr int NUK = 4 * NH * UPP;
constexpr int TILE_BYTES = KEYS * 256;
#define NWORK 2
constexpr int NW = NWORK;
constexpr int NBCTA = 32;
constexpr int MINCL = 15;
constexpr int NFIN = 72;
constexpr int SLOT = 32768;
constexpr int NSLOT = 6;
constexpr int BRING = 5;
constexpr int J0W = 5 * SLOT;
constexpr int MISC = NSLOT * SLOT + 4096;
constexpr int XP = 1168, CP = 1040, QP = 272;
constexpr int M_XA = MISC;
constexpr int M_XB = M_XA + 4 * XP;
constexpr int M_CH = M_XB + 4 * XP;
constexpr int M_CL = M_CH + 4 * CP;
constexpr int M_QB = M_CL + 4 * CP;
constexpr int M_QA = M_CH;
constexpr int M_J0 = M_QB + 4 * QP;
constexpr int M_P = M_J0 + 2048;
constexpr int M_ALPHA = M_P + 2560;
constexpr int M_OMEGA = M_ALPHA + 128;
constexpr int M_BAR = M_OMEGA + 128;
constexpr int M_HELP = M_BAR + 128;
#define PH 1
constexpr int F_W = 4 * SLOT;
constexpr int F_BF = (M_HELP + 128 + 255) / 256 * 256;
constexpr int F_RX = F_BF + 4096;
constexpr int F_BAR = F_RX + 2048;
constexpr int SMEM_BYTES = F_BAR + 64 + 64 * PH + 1024;
static_assert(SMEM_BYTES <= 232448 && M_BAR % 8 == 0 && M_QA % 16 == 0 && M_P % 16 == 0, "smem layout");
#define XW 2
#define X3 1
#define X3C 3
#define NEARLY 3
#define BD 5
#define FPF 3
#define FSLEEP 800
#define VS0 24
#define EARLY 100
#define ELOG 5
#define TPU 159
#define A0 3000
#define AJ 700
#define AR (AJ / 8 / PH)
#define ASTEP (AJ / PH)
#define BSTEP (BJ / PH)
#define PFN 96
#define PFS 128
#define PFC PFN
#define PFLD 0
#define PF0 128
#define PFOFF 0
#define CM2 10
#define AK 24
#define AC 0
#define BK 24
#define BC 0
#define B0 2500
#define BJ 700
#define BS (300 / PH)
#define BR (BJ / 8 / PH)
#define NPOLL 2
#define PGAP 200
static_assert(X3C <= 3 && NW == 2, "warp 2 of rank 7 is free");
static_assert(NW + XW <= 4 && NEARLY <= NW + XW && BD <= BRING, "slots 4 and 5 hold the finisher weights");
#define KMAX 4
#define VMAX 4
constexpr int KMIN = 2, VMIN = 0;
constexpr float SCALE = 0.08838834764831845f;
constexpr float LOG2E = 1.4426950408889634f;
constexpr unsigned SPIN_LIMIT = 1u << 24;

#define NREP 2
#define NREPC 1
constexpr int C_QUEUE = 0, C_KDONE = 1, C_BBAR = 3, C_LINES = 5;

struct Params {
    const char* pf;
    const __nv_bfloat16 *kc, *xa, *vc, *wo, *xb;
    __nv_bfloat16* out;
    CUtensorMap tm_j0;
    CUtensorMap tm_wq, tm_wuk, tm_ckv, tm_wuv, tm_wo;
    CUtensorMap tm_fa, tm_fb;
};

__device__ unsigned g_epoch;
__device__ unsigned g_ctl[2][C_LINES][32];
__device__ uint2 g_qll[4 * 2048];
__device__ uint2 g_scores[128 * SK / 4];
__device__ float2 g_stats[128 * UPP];
__device__ float4 g_oacc[128 * 32];
__device__ unsigned g_vdone[NREP * NH][32];
__device__ float4 g_octx[128 * 32];
__device__ unsigned g_cdone[NH][32];
__device__ unsigned long long g_dry[16][16];
__device__ uint4 g_qabs[4 * 8 * 4 * 4 * 32];
__device__ float2 g_bpart[NBCTA * NH * 256];
__device__ float2 g_bml[NBCTA * NH];
__device__ uint4 g_outb[NBCTA * NH * 36];

#define TS(i)
#define TSV(i, v)
#define LAND(i)
#define CLK(x)
#define ACC(a, x, y)

__device__ __forceinline__ uint32_t smem_u32(const void* p) { return (uint32_t)__cvta_generic_to_shared(p); }
__device__ __forceinline__ void mbar_init(uint32_t bar, uint32_t cnt) {
    asm volatile("mbarrier.init.shared::cta.b64 [%0], %1;" ::"r"(bar), "r"(cnt) : "memory");
}
__device__ __forceinline__ void mbar_expect_tx(uint32_t bar, uint32_t bytes) {
    asm volatile("mbarrier.arrive.expect_tx.shared::cta.b64 _, [%0], %1;" ::"r"(bar), "r"(bytes) : "memory");
}
__device__ __forceinline__ bool mbar_try(uint32_t bar, uint32_t parity) {
    uint32_t ok;
    asm volatile("{\n.reg .pred p;\nmbarrier.try_wait.parity.shared::cta.b64 p, [%1], %2;\nselp.u32 %0, 1, 0, p;\n}\n"
                 : "=r"(ok) : "r"(bar), "r"(parity) : "memory");
    return ok;
}
__device__ __forceinline__ void mbar_wait(uint32_t bar, uint32_t parity) {
    unsigned n = 0;
    while (!mbar_try(bar, parity)) { if (++n > SPIN_LIMIT) __trap(); }
}
#define WAIT1 "try_wait"
#define WAIT2 "try_wait"
__device__ __forceinline__ void mbar_spin(uint32_t bar) {
    asm volatile("{\n.reg .pred p;\n.reg .u32 n;\nmov.u32 n, 0;\nSPIN:\nmbarrier." WAIT1 ".parity.shared::cta.b64 p, [%0], 0;\n@p bra.uni DONE;\n"
                 "add.u32 n, n, 1;\nsetp.lt.u32 p, n, 0x4000000;\n@p bra.uni SPIN;\ntrap;\nDONE:\n}" ::"r"(bar) : "memory");
}
__device__ __forceinline__ void bulk_load(uint32_t dst, const void* src, uint32_t bytes, uint32_t bar, uint64_t pol) {
    asm volatile("cp.async.bulk.shared::cluster.global.mbarrier::complete_tx::bytes.L2::cache_hint [%0], [%1], %2, [%3], %4;"
                 ::"r"(dst), "l"(src), "r"(bytes), "r"(bar), "l"(pol) : "memory");
}
__device__ __forceinline__ void tma3d(uint32_t dst, const CUtensorMap* tm, int c0, int c1, int c2, uint32_t bar, uint64_t pol) {
    asm volatile("cp.async.bulk.tensor.3d.shared::cluster.global.mbarrier::complete_tx::bytes.L2::cache_hint [%0], [%1, {%3,%4,%5}], [%2], %6;"
                 ::"r"(dst), "l"(tm), "r"(bar), "r"(c0), "r"(c1), "r"(c2), "l"(pol) : "memory");
}
__device__ __forceinline__ void l2_prefetch(const void* src, uint32_t bytes) {
    asm volatile("cp.async.bulk.prefetch.L2.global [%0], %1;" ::"l"(src), "r"(bytes) : "memory");
}
__device__ __forceinline__ void ldsm4(uint32_t (&r)[4], uint32_t addr) {
    asm volatile("ldmatrix.sync.aligned.m8n8.x4.shared.b16 {%0,%1,%2,%3}, [%4];"
                 : "=r"(r[0]), "=r"(r[1]), "=r"(r[2]), "=r"(r[3]) : "r"(addr));
}
__device__ __forceinline__ void ldsm4t(uint32_t (&r)[4], uint32_t addr) {
    asm volatile("ldmatrix.sync.aligned.m8n8.x4.trans.shared.b16 {%0,%1,%2,%3}, [%4];"
                 : "=r"(r[0]), "=r"(r[1]), "=r"(r[2]), "=r"(r[3]) : "r"(addr));
}
__device__ __forceinline__ void mma16816(float (&d)[4], const uint32_t (&a)[4], uint32_t b0, uint32_t b1) {
    asm("mma.sync.aligned.m16n8k16.row.col.f32.bf16.bf16.f32 {%0,%1,%2,%3}, {%4,%5,%6,%7}, {%8,%9}, {%0,%1,%2,%3};"
        : "+f"(d[0]), "+f"(d[1]), "+f"(d[2]), "+f"(d[3])
        : "r"(a[0]), "r"(a[1]), "r"(a[2]), "r"(a[3]), "r"(b0), "r"(b1));
}
__device__ __forceinline__ uint32_t lds32(uint32_t a) {
    uint32_t v;
    asm volatile("ld.shared.u32 %0, [%1];" : "=r"(v) : "r"(a));
    return v;
}
__device__ __forceinline__ unsigned ld_acquire(const unsigned* p) {
    unsigned v;
    asm volatile("ld.acquire.gpu.global.u32 %0, [%1];" : "=r"(v) : "l"(p) : "memory");
    return v;
}
__device__ __forceinline__ uint2 ld_relaxed8(const void* p) {
    uint2 v;
    asm volatile("ld.relaxed.gpu.global.v2.u32 {%0,%1}, [%2];" : "=r"(v.x), "=r"(v.y) : "l"(p) : "memory");
    return v;
}
__device__ __forceinline__ unsigned ld_relaxed4(const void* p) {
    unsigned v;
    asm volatile("ld.relaxed.gpu.global.u32 %0, [%1];" : "=r"(v) : "l"(p) : "memory");
    return v;
}
__device__ __forceinline__ unsigned atom_inc(unsigned* p) {
    unsigned v;
    asm volatile("atom.relaxed.gpu.global.inc.u32 %0, [%1], 0x7fffffff;" : "=r"(v) : "l"(p) : "memory");
    return v;
}
__device__ __forceinline__ unsigned long long ld_relaxed64(const void* p) {
    unsigned long long v;
    asm volatile("ld.relaxed.gpu.global.u64 %0, [%1];" : "=l"(v) : "l"(p) : "memory");
    return v;
}
__device__ __forceinline__ void st_relaxed64(void* p, unsigned long long v) {
    asm volatile("st.relaxed.gpu.global.u64 [%0], %1;" ::"l"(p), "l"(v) : "memory");
}
__device__ __forceinline__ float4 ld_relaxed16(const void* p) {
    float4 v;
    asm volatile("ld.relaxed.gpu.global.v4.f32 {%0,%1,%2,%3}, [%4];" : "=f"(v.x), "=f"(v.y), "=f"(v.z), "=f"(v.w) : "l"(p) : "memory");
    return v;
}
__device__ __forceinline__ uint32_t mapa(uint32_t a, uint32_t rank) {
    uint32_t r;
    asm("mapa.shared::cluster.u32 %0, %1, %2;" : "=r"(r) : "r"(a), "r"(rank));
    return r;
}
__device__ __forceinline__ uint32_t time_ns() { uint32_t t; asm volatile("mov.u32 %0, %globaltimer_lo;" : "=r"(t)); return t; }
__device__ __forceinline__ void fence_gpu() { asm volatile("fence.acq_rel.gpu;" ::: "memory"); }
__device__ __forceinline__ void red_add_u32(unsigned* p, unsigned v) {
    asm volatile("red.relaxed.gpu.global.add.u32 [%0], %1;" ::"l"(p), "r"(v) : "memory");
}
__device__ __forceinline__ void st_tagged2(void* p, float a, float b, unsigned tag) {
    const unsigned long long hi = (unsigned long long)tag << 32;
    asm volatile("st.relaxed.gpu.global.v2.b64 [%0], {%1,%2};" ::"l"(p), "l"(hi | __float_as_uint(a)), "l"(hi | __float_as_uint(b)) : "memory");
}
__device__ __forceinline__ ulonglong2 ld_tagged2(const void* p) {
    ulonglong2 v;
    asm volatile("ld.relaxed.gpu.global.v2.b64 {%0,%1}, [%2];" : "=l"(v.x), "=l"(v.y) : "l"(p) : "memory");
    return v;
}
__device__ __forceinline__ float4 atom_add_f4(void* p, float a, float b, float c, float d) {
    float4 r;
    asm volatile("atom.relaxed.gpu.global.add.v4.f32 {%0,%1,%2,%3}, [%4], {%5,%6,%7,%8};"
                 : "=f"(r.x), "=f"(r.y), "=f"(r.z), "=f"(r.w) : "l"(p), "f"(a), "f"(b), "f"(c), "f"(d) : "memory");
    return r;
}
__device__ __forceinline__ void red_release_cta_shared(uint32_t a, unsigned v) {
    asm volatile("red.release.cta.shared::cta.add.u32 [%0], %1;" ::"r"(a), "r"(v) : "memory");
}
__device__ __forceinline__ unsigned ld_acquire_cta_shared(uint32_t a) {
    unsigned v;
    asm volatile("ld.acquire.cta.shared::cta.u32 %0, [%1];" : "=r"(v) : "r"(a) : "memory");
    return v;
}
__device__ __forceinline__ void st_release_cta_shared(uint32_t a, unsigned v) {
    asm volatile("st.release.cta.shared::cta.u32 [%0], %1;" ::"r"(a), "r"(v) : "memory");
}
__device__ __forceinline__ void wait_count(const unsigned* p, unsigned target) {
    unsigned n = 0;
    while (ld_acquire(p) < target) { if (++n > SPIN_LIMIT) __trap(); }
}
__device__ __forceinline__ uint32_t pack_bf16(float lo, float hi) {
    uint32_t r;
    asm("cvt.rn.bf16x2.f32 %0, %1, %2;" : "=r"(r) : "f"(hi), "f"(lo));
    return r;
}
__device__ __forceinline__ float bf_lo(uint32_t v) { return __uint_as_float(v << 16); }
__device__ __forceinline__ float bf_hi(uint32_t v) { return __uint_as_float(v & 0xffff0000u); }
__device__ __forceinline__ float ex2(float x) { float y; asm("ex2.approx.ftz.f32 %0, %1;" : "=f"(y) : "f"(x)); return y; }
__device__ __forceinline__ float expsub(float a, float b) { return ex2((a - b) * LOG2E); }
__device__ __forceinline__ float warp_max(float v) {
#pragma unroll
    for (int m = 16; m; m >>= 1) v = fmaxf(v, __shfl_xor_sync(~0u, v, m));
    return v;
}
__device__ __forceinline__ float warp_sum(float v) {
#pragma unroll
    for (int m = 16; m; m >>= 1) v += __shfl_xor_sync(~0u, v, m);
    return v;
}
template <bool CLU>
__device__ __forceinline__ unsigned unit_block(int u) {
    const unsigned x = ((unsigned)u & (NUK - 1)) / UPP;
    const int lg = u < NUK ? min(KMAX, max(KMIN, 29 - __clz(x | 1))) : (CLU && (int)x >= 4 * VS0 ? 0 : min(VMAX, max(VMIN, 29 - __clz((127 - x) | 1))));
    const unsigned r = x & ((4u << lg) - 1);
    return ((x - r + (r & ((1u << lg) - 1)) * 4 + (r >> lg)) * UPP) | ((unsigned)u & (UPP - 1));
}
__device__ __forceinline__ const char* block_src(const void* base, unsigned blk) {
    const unsigned po = blk / UPP;
    return reinterpret_cast<const char*>(base) + (size_t)(((po & 3) * NH + (po >> 2)) * UPP + blk % UPP) * TILE_BYTES;
}

template <bool CLU>
__device__ __forceinline__ void a_worker(const Params& p, int un, bool once, bool pre, bool hold, int nstatic, uint32_t slot, uint32_t bar,
                                         uint32_t help, unsigned epoch, uint64_t pol) {
    constexpr int NU = 2 * NUK, NR = CLU ? NREPC : NREP;
    const int lane = threadIdx.x & 31, g = lane >> 2, t = lane & 3;
    const int li = lane & 7;
    uint32_t kaddr[4], vaddr[8];
    {
        const int e = (lane >> 3) & 1, kk = lane >> 4;
#pragma unroll
        for (int s = 0; s < 4; s++) kaddr[s] = slot + (16 * li + e) * 256 + ((2 * s + kk + li) & 7) * 16;
        const int vrow = 4 * (li >> 1) + (li & 1) + 2 * kk;
#pragma unroll
        for (int c = 0; c < 8; c++) vaddr[c] = slot + vrow * 256 + e * 128 + ((c + li) & 7) * 16;
#pragma unroll
        for (int c = 0; c < 8; c++) asm volatile("" : "+r"(vaddr[c]));
    }
    const uint32_t vmask = (g >> 1) != t ? 0u : ((g & 1) ? 0xffff0000u : 0xffffu);
    int kseen = -1;
    unsigned long long H0 = 0, H1 = 0;
    auto header = [&](int v, unsigned vb) {
        if (v >= NU) return;
        const void *a0, *a1;
        if (v < NUK) {
            const unsigned po = vb / UPP;
            a0 = g_qll + (po & 3) * 2048 + (po >> 2) * 64 + lane;
            a1 = reinterpret_cast<const uint2*>(a0) + 32;
        } else {
            const int half = vb / (NUK / 2);
            if (half > kseen) {
                unsigned n = 0;
                while (ld_acquire_cta_shared(help + 12 + 4 * half) == 0) { if (++n > (SPIN_LIMIT << 4)) __trap(); }
                kseen = half;
            }
            a0 = &g_scores[vb * (KEYS / 4) + lane];
            a1 = &g_stats[(vb / UPP) * UPP + lane];
        }
        H0 = ld_relaxed64(a0);
        H1 = ld_relaxed64(a1);
    };
    asm volatile("bar.sync 2, %0;" ::"n"(32 * (NW + XW + 1)) : "memory");
    epoch = __shfl_sync(~0u, epoch, 0);
    if (hold) { unsigned n = 0; while (ld_acquire_cta_shared(help + 24) < 2) { if (++n > (SPIN_LIMIT << 4)) __trap(); } }
    unsigned (*ctl)[32] = g_ctl[epoch & 1];
    const unsigned tag = epoch + 1;
    unsigned nxt = once ? NU : 0;
    int u = -1;
    unsigned bu = 0, bn = unit_block<CLU>(un);
    bool have = false;
    uint32_t phase = 0;
    unsigned kpend = 0;
    const unsigned zero = gridDim.x >> 24;
    uint32_t Q[16];
    float4 oret = make_float4(0.f, 0.f, 0.f, 0.f);
    while (true) {
        const char* nsrc = block_src(un < NUK ? p.kc : p.vc, bn);
        float4* odst = &g_oacc[(bu / UPP) * 32 + lane];
        unsigned* vdst = &g_vdone[(lane & (NR - 1)) * NH + bu / (4 * UPP)][0];
        float d[8][4];
        CLK(c1);
        asm volatile("" : "+l"(odst));
        if (u >= NUK) {
#pragma unroll
            for (int j = 0; j < 8; j++) { d[j][0] = d[j][1] = d[j][2] = d[j][3] = 0.f; }
            mbar_wait(bar, phase);
            LAND(NUK + bu);
            uint32_t a[2][8][4];
#pragma unroll
            for (int c = 0; c < 8; c++) ldsm4t(a[0][c], vaddr[c]);
#pragma unroll
            for (int j = 0; j < 8; j++) {
                if (j < 7) {
#pragma unroll
                    for (int c = 0; c < 8; c++) ldsm4t(a[(j + 1) & 1][c], vaddr[c] + (j + 1) * 4096);
                }
#pragma unroll
                for (int c = 0; c < 8; c++) mma16816(d[c], a[j & 1][c], Q[2 * j], Q[2 * j + 1]);
            }
            float o[4];
#pragma unroll
            for (int r = 0; r < 2; r++) {
                o[2 * r] = d[0][2 * r] + d[7][2 * r + 1];
                o[2 * r + 1] = d[0][2 * r + 1] + d[1][2 * r];
#pragma unroll
                for (int k = 1; k < 4; k++) {
                    const int src = (lane & 28) | ((t - k) & 3);
                    o[2 * r] += __shfl_sync(~0u, d[2 * k][2 * r] + d[2 * k - 1][2 * r + 1], src);
                    o[2 * r + 1] += __shfl_sync(~0u, d[2 * k][2 * r + 1] + d[2 * k + 1][2 * r], src);
                }
            }
            oret = atom_add_f4(odst, o[0], o[1], o[2], o[3]);
        } else if (u >= 0) {
#pragma unroll
            for (int j = 0; j < 8; j++) { d[j][0] = d[j][1] = d[j][2] = d[j][3] = 0.f; }
            mbar_wait(bar, phase);
            LAND(bu);
            uint32_t a[2][8][4];
#pragma unroll
            for (int j = 0; j < 8; j++) ldsm4(a[0][j], kaddr[0] + (4 * (j & 3) + 2 * (j >> 2)) * 256);
#pragma unroll
            for (int s = 0; s < 8; s++) {
                if (s < 7) {
#pragma unroll
                    for (int j = 0; j < 8; j++)
                        ldsm4(a[(s + 1) & 1][j], kaddr[(s + 1) & 3] + (4 * (j & 3) + 2 * (j >> 2)) * 256 + ((s + 1) >> 2) * 128);
                }
#pragma unroll
                for (int j = 0; j < 8; j++)
                    mma16816(d[j], a[s & 1][j], Q[(s & 4) * 2 + ((2 * s - 2 * j) & 7)], Q[(s & 4) * 2 + ((2 * s + 1 - 2 * j) & 7)]);
            }
        }
        if (u >= 0) phase ^= 1;
        CLK(c2b);
        if (un < NU && lane == 0) {
            if (!once) nxt = atom_inc(&ctl[C_QUEUE][0]);
            if (u >= 0 || !pre) {
                mbar_expect_tx(bar, TILE_BYTES);
                bulk_load(slot, nsrc, TILE_BYTES, bar, pol);
            }
        }
        const uint32_t tk = clock();
        CLK(c3);
        if ((unsigned)u < (unsigned)NUK) {
            const int j0 = (t - (g >> 1)) & 3;
            float v[4];
#pragma unroll
            for (int q = 0; q < 4; q++) {
                const int jq = (q >> 1) * 4, e = (q & 1) * 2;
                const float x0 = (g & 1) ? d[jq + 0][e + 1] : d[jq + 0][e];
                const float x1 = (g & 1) ? d[jq + 1][e + 1] : d[jq + 1][e];
                const float x2 = (g & 1) ? d[jq + 2][e + 1] : d[jq + 2][e];
                const float x3 = (g & 1) ? d[jq + 3][e + 1] : d[jq + 3][e];
                const float y0 = (j0 & 1) ? x1 : x0, y1 = (j0 & 1) ? x3 : x2;
                v[q] = (j0 & 2) ? y1 : y0;
            }
            const uint32_t r0 = pack_bf16(v[0], v[1]), r1 = pack_bf16(v[2], v[3]);
            const uint32_t s0 = pack_bf16(bf_lo(r0) * SCALE, bf_hi(r0) * SCALE);
            const uint32_t s1 = pack_bf16(bf_lo(r1) * SCALE, bf_hi(r1) * SCALE);
            g_scores[bu * (KEYS / 4) + 4 * g + j0] = make_uint2(s0, s1);
            const float f0 = bf_lo(s0), f1 = bf_hi(s0), f2 = bf_lo(s1), f3 = bf_hi(s1);
            const float m = warp_max(fmaxf(fmaxf(f0, f1), fmaxf(f2, f3)));
            const float l = warp_sum((expsub(f0, m) + expsub(f1, m)) + (expsub(f2, m) + expsub(f3, m)));
            if (lane == 0) g_stats[bu] = make_float2(m, l);
            kpend++;
            if (un / (NUK / 2) != u / (NUK / 2)) {
                __syncwarp();
                if (lane == 0) {
                    red_release_cta_shared(help + 4 * (u / (NUK / 2)), kpend);
                    if (un >= NUK) red_release_cta_shared(help + 8, 1u);
                }
                kpend = 0;
            }
        }
        CLK(c4);
        int unn = NU;
        if (un < NU) {
            unsigned n = 0;
            while (true) {
                if (!have) header(un, bn);
                if (un >= NUK || __all_sync(~0u, (uint32_t)(H0 >> 32) == tag && (uint32_t)(H1 >> 32) == tag)) break;
                if (++n > SPIN_LIMIT) __trap();
                have = false;
            }
            if (un >= NUK) {
                const uint32_t s0 = (uint32_t)H0, s1 = (uint32_t)(H0 >> 32);
                const float mu = __uint_as_float((uint32_t)H1);
                const float m = warp_max(mu);
                const float l = warp_sum(__uint_as_float((uint32_t)(H1 >> 32)) * expsub(mu, m));
                const float inv = 1.0f / l;
                const uint32_t w0 = pack_bf16(expsub(bf_lo(s0), m) * inv, expsub(bf_hi(s0), m) * inv);
                const uint32_t w1 = pack_bf16(expsub(bf_lo(s1), m) * inv, expsub(bf_hi(s1), m) * inv);
#pragma unroll
                for (int j = 0; j < 8; j++) {
                    Q[2 * j] = __shfl_sync(~0u, w0, 4 * j + t) & vmask;
                    Q[2 * j + 1] = __shfl_sync(~0u, w1, 4 * j + t) & vmask;
                }
            } else {
#pragma unroll
                for (int j = 0; j < 8; j++) {
                    const int src = (((j + g) & 7) << 2) + t;
                    Q[j] = __shfl_sync(~0u, (uint32_t)H0, src);
                    Q[8 + j] = __shfl_sync(~0u, (uint32_t)H1, src);
                }
            }
            unn = nstatic + (int)__shfl_sync(~0u, nxt, 0);
            if (CLU && ((NU - EARLY - unn) & ~(7 << ELOG)) == 0 && lane < MINCL)
                st_relaxed64(&g_dry[lane][(NU - EARLY - unn) >> ELOG],
                             (time_ns() - (((uint32_t)clock() - tk) >> 1) + (NU - unn) * TPU / 16) | (unsigned long long)tag << 32);
        }
        if (u >= NUK && lane < NR)
            red_add_u32(vdst,
                        1u + ((__float_as_uint(oret.x) | __float_as_uint(oret.y) | __float_as_uint(oret.z) | __float_as_uint(oret.w)) & zero));
        if (un >= NU) break;
        bu = bn;
        have = !(un < NUK && unn >= NUK && !(un >= NUK / 2 && unn < NUK + NUK / 2));
        bn = unit_block<CLU>(unn);
        if (have) header(unn, bn);
        u = un;
        un = unn;
    }
}

__device__ __forceinline__ void k_helper(uint32_t help, unsigned epoch) {
    if ((threadIdx.x & 31) != 0) return;
    unsigned (*ctl)[32] = g_ctl[epoch & 1];
    unsigned sent0 = 0, sent1 = 0, n = 0;
    int seen = 0;
    bool fin = false;
    while (!fin || seen < 2) {
        if (!fin) {
            fin = ld_acquire_cta_shared(help + 8) == NW + XW;
            const unsigned c0 = ld_acquire_cta_shared(help), c1 = ld_acquire_cta_shared(help + 4);
            if (c0 != sent0 || c1 != sent1) {
                fence_gpu();
                if (c0 != sent0) red_add_u32(&ctl[C_KDONE][0], c0 - sent0);
                if (c1 != sent1) red_add_u32(&ctl[C_KDONE + 1][0], c1 - sent1);
                sent0 = c0; sent1 = c1;
            }
        }
        if (seen < 2 && ld_acquire(&ctl[C_KDONE + seen][0]) >= NUK / 2) {
            st_release_cta_shared(help + 12 + 4 * seen, 1u);
            seen++;
        } else {
            __nanosleep(300);
        }
        if (++n > SPIN_LIMIT) __trap();
    }
}

__device__ __forceinline__ void v_poller(uint32_t sbase, int f, int w) {
    constexpr int HL = NH;
    const int lane = threadIdx.x & 31;
    const unsigned (*cp)[32] = &g_vdone[((f * NPOLL + w) % NREP) * NH];
    unsigned n = 0;
    while (ld_acquire_cta_shared(sbase + M_HELP + 12) == 0) { __nanosleep(1000); if (++n > SPIN_LIMIT) __trap(); }
    int h = 0;
    bool fast = false;
    while (h < HL) {
        const unsigned r = __ballot_sync(~0u, ld_acquire(&cp[min(h + (lane & 3), HL - 1)][0]) >= 4 * UPP) & 15u;
        if (r & 1) {
            h = min(HL, h + __ffs(~r) - 1);
            __syncwarp();
            if (lane == 0) asm volatile("red.release.cta.shared::cta.max.u32 [%0], %1;" ::"r"(sbase + M_HELP + 20), "r"(h) : "memory");
        }
        if (h < HL - 4) {
            __nanosleep(h ? 300 : 1000);
        } else if (!fast) {
            fast = true;
            const long long t0 = clock64();
            while (clock64() - t0 < w * PGAP) {}
        }
        if (++n > SPIN_LIMIT) __trap();
    }
}
__device__ __forceinline__ void finisher(const Params& p, uint32_t sbase, int f) {
    constexpr int HL = NH;
    const int lane = threadIdx.x & 31;
    {
        const char* wg = reinterpret_cast<const char*>(p.wo);
        const uint32_t dst = sbase + 4 * SLOT + (16 * (lane & 7) + (lane >> 3)) * 16;
#pragma unroll 1
        for (int h = -FPF - 4; h < HL; h++) {
            if (lane == 0 && (unsigned)(h + FPF) < (unsigned)HL) l2_prefetch(wg + (size_t)(h + FPF) * 147456 + f * 2048, 2048);
            if (h >= 0) {
#pragma unroll
                for (int r = 0; r < 4; r++)
                    asm volatile("cp.async.cg.shared.global [%0], [%1], 16;" ::"r"(dst + h * 2048 + ((r & 1) * 4 + (r >> 1) * 8) * 16),
                                 "l"(wg + (size_t)(h * 128 + r * 32 + lane) * (DM * 2) + f * 16) : "memory");
            }
            __nanosleep(FSLEEP);
        }
        asm volatile("cp.async.wait_all;" ::: "memory");
        __syncwarp();
    }
    TS(11);
    const float4* vec = g_oacc + ((lane >> 2) & 3) * 32 + (lane >> 4) * 16 + (lane & 3);
    float acc[2][2][4];
#pragma unroll
    for (int i = 0; i < 16; i++) acc[i >> 3][(i >> 2) & 1][i & 3] = 0.f;
    uint32_t* outp = reinterpret_cast<uint32_t*>(p.out + (lane >> 2) * (2 * DM) + f * 8 + (lane & 3) * 2);
    uint32_t wa = sbase + 4 * SLOT + lane * 16;
    auto project = [&](const float4 (&x)[4], const uint32_t (&w)[4][4]) {
#pragma unroll
        for (int s = 0; s < 4; s++) {
            const uint32_t a[4] = {pack_bf16(x[s].x, x[s].y), 0u, pack_bf16(x[s].z, x[s].w), 0u};
            mma16816(acc[0][s & 1], a, w[s >> 1][(s & 1) * 2], w[s >> 1][(s & 1) * 2 + 1]);
            mma16816(acc[1][s & 1], a, w[2 + (s >> 1)][(s & 1) * 2], w[2 + (s >> 1)][(s & 1) * 2 + 1]);
        }
    };
    int h = 0;
    unsigned n = 0;
    while (h < HL) {
        uint32_t w[4][4];
#pragma unroll
        for (int q = 0; q < 4; q++) ldsm4t(w[q], wa + q * 512);
        int ready;
        while ((ready = ld_acquire_cta_shared(sbase + M_HELP + 20)) <= h) {
            if (h < HL - 3) __nanosleep(100);
            if (++n > (SPIN_LIMIT << 4)) __trap();
        }
        float4 x[4], y[4];
#pragma unroll
        for (int s = 0; s < 4; s++) x[s] = ld_relaxed16(vec + s * 4);
        const bool two = ready > h + 1;
        if (two) {
#pragma unroll
            for (int s = 0; s < 4; s++) y[s] = ld_relaxed16(vec + 128 + s * 4);
        }
        project(x, w);
        if (two) {
#pragma unroll
            for (int q = 0; q < 4; q++) ldsm4t(w[q], wa + 2048 + q * 512);
            project(y, w);
        }
        const int nr = two ? 2 : 1;
        h += nr;
        vec += nr * 128;
        wa += nr * 2048;
        const float o0 = acc[0][0][0] + acc[0][1][0] + __shfl_down_sync(~0u, acc[1][0][0] + acc[1][1][0], 16);
        const float o1 = acc[0][0][1] + acc[0][1][1] + __shfl_down_sync(~0u, acc[1][0][1] + acc[1][1][1], 16);
        asm volatile("{\n.reg .pred p;\nsetp.ne.u32 p, %2, 0;\n@p st.global.u32 [%0], %1;\n}" ::"l"(outp), "r"(pack_bf16(o0, o1)),
                     "r"((uint32_t)(lane < 16 && h == NH)) : "memory");
    }
}

__device__ __noinline__ void f_collect(const unsigned (*flag)[32], unsigned full, const float4* src, unsigned todo, uint32_t sbase) {
    const int lane = threadIdx.x & 31, g = lane >> 2, t = lane & 3;
    const bool last = todo != 15;
    unsigned n = 0;
    while (todo) {
        const unsigned v = ld_acquire(&flag[t][0]);
        unsigned m = __ballot_sync(~0u, v == full) & todo;
        if (m == 0) {
            if (!last || __shfl_sync(~0u, v, 0) == 0) __nanosleep(200);
            if (++n > SPIN_LIMIT) __trap();
            continue;
        }
        __syncwarp();
        todo ^= m;
        if (last) TS(16);
        do {
            const int h0 = __ffs(m) - 1, h1 = 31 - __clz(m);
            m &= ~((1u << h0) | (1u << h1));
            float4 x[8];
#pragma unroll
            for (int b = 0; b < 8; b++) x[b] = ld_relaxed16(src + ((b & 4) ? h1 : h0) * 128 + (b & 3) * 32 + lane);
#pragma unroll
            for (int b = 0; b < 8; b++) {
                const uint32_t lo = pack_bf16(x[b].x, x[b].y), hi = pack_bf16(x[b].z, x[b].w);
                const uint32_t o = __shfl_xor_sync(~0u, (g & 1) ? lo : hi, 4);
                const uint32_t e0 = (g & 1) ? o : lo, e1 = (g & 1) ? hi : o;
                asm volatile("st.shared.v2.u32 [%0], {%1,%2};"
                             ::"r"(sbase + F_BF + ((b & 4) ? h1 : h0) * 1024 + t * 256 + ((b ^ t) & 3) * 64 + g * 8),
                               "r"(__byte_perm(e0, e1, 0x5410)), "r"(__byte_perm(e0, e1, 0x7632)) : "memory");
            }
            __syncwarp();
            if (lane < (h0 == h1 ? 1 : 2))
                asm volatile("mbarrier.arrive.shared::cta.b64 _, [%0];" ::"r"(sbase + F_BAR + 32 + (lane ? h1 : h0) * 8) : "memory");
        } while (m);
    }
    if (last) TS(17);
}

__device__ __noinline__ void f_project(const CUtensorMap* tm, int panel, int rank, int sl, int j, int delay, int step, unsigned tag, uint32_t sbase, uint64_t pol) {
    const int lane = threadIdx.x & 31, g = lane >> 2, t = lane & 3;
    const uint32_t wb = sbase + F_W - sl * 2 * SLOT, bars = sbase + F_BAR + 64 + sl * 32 * PH;
    const uint32_t wa = wb + ((lane & 7) + (lane >> 4) * 8) * 128 + (((2 * j + ((lane >> 3) & 1)) ^ (lane & 7)) * 16);
    const uint32_t ba = sbase + F_BF + (g & 3) * 64 + t * 16;
    const uint32_t rdst = mapa(sbase + F_RX + sl * 1024 + rank * 128 + g * 16 + (t & 1) * 8, 2 * j + (t >> 1));
    const uint32_t rbar = mapa(sbase + F_BAR + 16 + sl * 8, 2 * j + (t >> 1));
    unsigned n = 0;
    if (threadIdx.x >= 224) {
        if (lane == 0) asm volatile("prefetch.tensormap [%0];" ::"l"(tm) : "memory");
        unsigned long long v;
        while (!__all_sync(~0u, (v = ld_relaxed64(&g_dry[blockIdx.x >> 3][g])) >> 32 == tag)) {
            __nanosleep(200);
            if (++n > SPIN_LIMIT) __trap();
        }
        const uint32_t t0 = __shfl_sync(~0u, (uint32_t)v, 0);
        const uint32_t t1 = t0 + (__reduce_add_sync(~0u, (int)((uint32_t)v - t0)) >> 5);
        if (lane == 0) asm volatile("st.shared.u32 [%0+8], %1;\nmbarrier.arrive.shared::cta.b64 _, [%0];" ::"r"(sbase + F_BAR), "r"(t1) : "memory");
        TS(22);
    }
    mbar_wait(sbase + F_BAR, 0);
    if (lane == 0) {
        uint32_t due = lds32(sbase + F_BAR + 8) + delay;
#pragma unroll 1
        for (int q = j * PH; q < (j + 1) * PH; q++, due += step) {
            mbar_expect_tx(bars + q * 8, 16384 / PH);
            while ((int)(time_ns() - due) < 0) {}
            tma3d(wb + q * (16384 / PH), tm, 0, rank * 512 + q * (128 / PH), panel, bars + q * 8, pol);
        }
    }
    __syncwarp();
    TS(18);
#define NCH 2
    float acc[4][4];
#pragma unroll
    for (int i = 0; i < 16; i++) acc[i >> 2][i & 3] = 0.f;
    const bool up = t & 2;
#pragma unroll 1
    for (int h = 0; h < 4; h++) {
        uint32_t wp = wa + h * 16384, bar = bars + h * PH * 8, last = h == 3;
        mbar_spin(sbase + F_BAR + 32 + h * 8);
        uint32_t bf[4][4];
#pragma unroll
        for (int s = 0; s < 4; s++)
            asm volatile("ld.shared.v4.u32 {%0,%1,%2,%3}, [%4];" : "=r"(bf[s][0]), "=r"(bf[s][1]), "=r"(bf[s][2]), "=r"(bf[s][3])
                         : "r"(((ba + h * 1024) ^ (s * 64)) + s * 256) : "memory");
        asm volatile("" : "+r"(wp), "+r"(bar), "+r"(last));
#pragma unroll
        for (int q = 0; q < PH; q++) {
            mbar_spin(bar + q * 8);
            if (h == 3 && q == PH - 1) TS(19);
            uint32_t a[8 / PH][4];
#pragma unroll
            for (int s = 0; s < 8 / PH; s++) ldsm4t(a[s], wp + (q * (8 / PH) + s) * 2048);
#pragma unroll
            for (int s = 0; s < 8 / PH; s++) {
                const int k = q * (8 / PH) + s;
                mma16816(acc[s & (NCH - 1)], a[s], bf[k & 3][(k >> 2) * 2], bf[k & 3][(k >> 2) * 2 + 1]);
            }
        }
        float v0 = up ? acc[0][2] + acc[1][2] : acc[0][0] + acc[1][0], v1 = up ? acc[0][3] + acc[1][3] : acc[0][1] + acc[1][1];
        if (NCH == 4) {
            v0 = (v0 + (up ? acc[2][2] : acc[2][0])) + (up ? acc[3][2] : acc[3][0]);
            v1 = (v1 + (up ? acc[2][3] : acc[2][1])) + (up ? acc[3][3] : acc[3][1]);
        }
        asm volatile("{\n.reg .pred p;\nsetp.ne.u32 p, %4, 0;\n"
                     "@p st.async.weak.shared::cluster.mbarrier::complete_tx::bytes.v2.b32 [%0], {%1,%2}, [%3];\n}"
                     ::"r"(rdst), "r"(__float_as_uint(v0)), "r"(__float_as_uint(v1)), "r"(rbar), "r"(last) : "memory");
    }
    TS(20);
}

__device__ __noinline__ void f_receive(__nv_bfloat16* out, int sl, bool dry, uint32_t sbase) {
    const int lane = threadIdx.x & 31;
    out += (lane & 3) * (2 * DM) + (lane >> 2);
    uint32_t src = sbase + F_RX + sl * 1024 + lane * 4;
    asm volatile("" : "+l"(out), "+r"(src));
    asm volatile("{\n.reg .pred p;\n.reg .u32 n;\nmov.u32 n, 0;\nSPIN:\nmbarrier." WAIT2 ".parity.acquire.cluster.shared::cta.b64 p, [%0], 0;\n"
                 "@p bra.uni DONE;\nadd.u32 n, n, 1;\nsetp.lt.u32 p, n, 0x4000000;\n@p bra.uni SPIN;\ntrap;\nDONE:\n}"
                 ::"r"(sbase + F_BAR + (dry ? 0 : 16 + sl * 8)) : "memory");
    float v[8];
#pragma unroll
    for (int r = 0; r < 8; r++) asm volatile("ld.shared.f32 %0, [%1];" : "=f"(v[r]) : "r"(src + r * 128) : "memory");
    const float o = ((v[0] + v[1]) + (v[2] + v[3])) + ((v[4] + v[5]) + (v[6] + v[7]));
    asm volatile("{\n.reg .pred p;\nsetp.eq.u32 p, %2, 0;\n@p st.global.u16 [%0], %1;\n}"
                 ::"l"(out), "h"((unsigned short)pack_bf16(o, 0.f)), "r"((uint32_t)dry) : "memory");
    TS(15);
}

__device__ __forceinline__ void b_final(const Params& p, uint32_t sbase, int blk, unsigned epoch, uint64_t pol) {
    const int warp = threadIdx.x >> 5;
    const int rank = blk & 7, sl = warp >> 2, panel = (blk >> 3) * 2 + sl;
    asm volatile("barrier.cluster.wait.acquire.aligned;" ::: "memory");
    if (warp == 0) f_collect(&g_cdone[4 * rank], epoch + 1, &g_octx[4 * rank * 128], 15, sbase);
    if ((warp & 3) == 0) {
        mbar_wait(sbase + F_BAR, 0);
        f_receive(p.out, sl, true, sbase);
    }
    f_project(&p.tm_fb, panel, rank, sl, warp & 3, B0 + (warp & 3) * BJ + sl * BS + rank * BR - max(0, (warp & 3) * 8 + rank - BK) * BC, BSTEP, epoch + 1, sbase, pol);
    if ((warp & 3) == 0) f_receive(p.out + DM + panel * 64 + rank * 8, sl, false, sbase);
}

constexpr int BS_WUK = 5, BS_Q = 9, BS_CKV = 11, BS_PART = 27, BS_WUV = 29, BS_END = 33;

__device__ __noinline__ void b_issue(const Params& p, int n, int bi, uint32_t sbase, uint64_t pol) {
    if (n >= BS_END || (n >= BS_Q && n < BS_CKV) || (n >= BS_PART && n < BS_WUV)) return;
    const uint32_t bar = sbase + M_BAR + (NSLOT + n % BRING) * 8;
    const CUtensorMap* tm;
    int row, panel = 2 * bi;
    if (n < BS_WUK) { tm = &p.tm_wq; row = n * 128; }
    else if (n < BS_Q) { tm = &p.tm_wuk; row = (n - BS_WUK) * 128; }
    else if (n < BS_PART) {
        tm = &p.tm_ckv; panel = 0;
        row = (bi >> 3) * SK + ((n - BS_CKV) * 8 + (bi & 7)) * 32;
    }
    else { tm = &p.tm_wuv; row = (n - BS_WUV) * 128; }
    mbar_expect_tx(bar, n == 0 ? 32768 + 4 * 1152 : 32768);
    tma3d(sbase + (n % BRING) * SLOT, tm, 0, row, panel, bar, pol);
}
__device__ __forceinline__ void b_issue_xchg(int n, const void* src, uint32_t sbase, uint64_t pol) {
    asm volatile("fence.proxy.async;" ::: "memory");
#pragma unroll
    for (int i = 0; i < 2; i++) {
        const uint32_t bar = sbase + M_BAR + (NSLOT + (n + i) % BRING) * 8;
        mbar_expect_tx(bar, 32768);
        bulk_load(sbase + ((n + i) % BRING) * SLOT, reinterpret_cast<const char*>(src) + i * 32768, 32768, bar, pol);
    }
}
__device__ __forceinline__ void b_wait(int n, uint32_t sbase) {
    mbar_wait(sbase + M_BAR + (NSLOT + n % BRING) * 8, (n / BRING) & 1);
}

__device__ __noinline__ void b_gemm(const Params& p, uint32_t sbase, int n0, int n1, int ktot, uint32_t xh, uint32_t xl, int pitch,
                                    int bi, uint64_t pol) {
    const int tid = threadIdx.x, warp = tid >> 5, lane = tid & 31, g = lane >> 2, t = lane & 3;
    const uint32_t woff = (warp >> 2) * 16384 + (lane & 15) * 128 + ((((warp & 3) * 2 + (lane >> 4)) ^ (lane & 7)) * 16);
    const uint32_t xoff = (g & 3) * pitch + t * 4;
    float acc[2][4];
#pragma unroll
    for (int i = 0; i < 8; i++) acc[i >> 2][i & 3] = 0.f;
#pragma unroll 1
    for (int n = n0; n < n1; n++) {
        b_wait(n, sbase);
        const uint32_t slot = sbase + (n % BRING) * SLOT + woff;
        const int k0 = (n - n0) * 128;
        const int ns = min(8, (ktot - k0) >> 4);
#pragma unroll 2
        for (int s = 0; s < ns; s++) {
            uint32_t a[4], w[4];
            const uint32_t xo = xoff + (k0 + 16 * s) * 2;
            a[0] = lds32(xh + xo); a[2] = lds32(xh + xo + 16);
            a[1] = xl ? lds32(xl + xo) : 0u; a[3] = xl ? lds32(xl + xo + 16) : 0u;
            ldsm4t(w, slot + s * 2048);
            mma16816(acc[0], a, w[0], w[1]);
            mma16816(acc[1], a, w[2], w[3]);
        }
        __syncthreads();
        if (tid == 0) b_issue(p, n + BD, bi, sbase, pol);
    }
    if (g < 4) {
#pragma unroll
        for (int j = 0; j < 2; j++)
            asm volatile("st.shared.u32 [%0], %1;" ::"r"(sbase + M_QB + g * QP + (warp * 16 + j * 8 + t * 2) * 2),
                         "r"(pack_bf16(acc[j][0] + acc[j][2], acc[j][1] + acc[j][3])) : "memory");
    }
    __syncthreads();
}

__device__ __forceinline__ void b_exchange(unsigned* c, int n, const void* src, uint32_t sbase, uint64_t pol) {
    TS(n == BS_Q ? 24 : 28);
    __syncthreads();
    if (threadIdx.x == 0) {
        TS(n == BS_Q ? 25 : 29);
        fence_gpu();
        TS(n == BS_Q ? 26 : 30);
        red_add_u32(c, 1u);
        wait_count(c, NBCTA);
        TS(n == BS_Q ? 27 : 31);
        b_issue_xchg(n, src, sbase, pol);
    }
}

template <bool CLU>
__device__ __noinline__ void b_chain(const Params& p, char* smem, uint32_t sbase, int bi, unsigned epoch, uint64_t pol) {
    const int tid = threadIdx.x, warp = tid >> 5, lane = tid & 31, g = lane >> 2, t = lane & 3;
    unsigned (*ctl)[32] = g_ctl[epoch & 1];
    float* red = reinterpret_cast<float*>(smem + 5 * SLOT);
    __syncthreads();
    b_gemm(p, sbase, 0, BS_WUK, DM, sbase + M_XB, 0, XP, bi, pol);
    TS(6);
    {
        uint32_t Q[16];
#pragma unroll
        for (int c = 0; c < 16; c++) Q[c] = lds32(sbase + M_QB + (g & 3) * QP + c * 16 + t * 4);
        float* qa = reinterpret_cast<float*>(smem + M_QA);
#pragma unroll 1
        for (int n = BS_WUK; n < BS_Q; n++) {
            b_wait(n, sbase);
            const uint32_t base = sbase + (n % BRING) * SLOT + (warp * 16 + (lane & 15)) * 128;
            float d[2][4];
#pragma unroll
            for (int i = 0; i < 8; i++) d[i >> 2][i & 3] = 0.f;
#pragma unroll
            for (int s = 0; s < 8; s++) {
                uint32_t a[4];
                ldsm4(a, base + (s >> 2) * 16384 + (((2 * (s & 3) + (lane >> 4)) ^ (lane & 7)) * 16));
                mma16816(d[s & 1], a, Q[2 * s], Q[2 * s + 1]);
            }
            const int c = (n - BS_WUK) * 128 + warp * 16 + g + 8 * (t >> 1);
            qa[(2 * (t & 1)) * 512 + c] = (t & 2) ? d[0][2] + d[1][2] : d[0][0] + d[1][0];
            qa[(2 * (t & 1) + 1) * 512 + c] = (t & 2) ? d[0][3] + d[1][3] : d[0][1] + d[1][1];
            __syncthreads();
            if (tid == 0) b_issue(p, n + BD, bi, sbase, pol);
        }
#pragma unroll 1
        for (int r = 0; r < 2; r++) {
            const int id = tid + r * 256;
            const int b = id >> 7, c0 = ((id >> 2) & 31) * 16 + (id & 3) * 2;
            const float2 u0 = *reinterpret_cast<const float2*>(qa + b * 512 + c0);
            const float2 u1 = *reinterpret_cast<const float2*>(qa + b * 512 + c0 + 8);
            const uint32_t h0 = pack_bf16(u0.x, u0.y), h1 = pack_bf16(u1.x, u1.y);
            const uint32_t l0 = pack_bf16(u0.x - bf_lo(h0), u0.y - bf_hi(h0)), l1 = pack_bf16(u1.x - bf_lo(h1), u1.y - bf_hi(h1));
            g_qabs[((id >> 2) * 4 + (bi >> 3)) * 32 + (bi & 7) * 4 + (id & 3)] = make_uint4(h0, l0, h1, l1);
        }
    }
    b_exchange(&ctl[C_BBAR][0], BS_Q, &g_qabs[(bi >> 3) * 4096], sbase, pol);
    {
        uint32_t qf[4][4][4];
        b_wait(BS_Q + (warp >> 2), sbase);
        TS(7);
        {
            const uint4* qs = reinterpret_cast<const uint4*>(smem + ((BS_Q + (warp >> 2)) % BRING) * SLOT) + (warp & 3) * 512 + lane;
#pragma unroll
            for (int s = 0; s < 4; s++)
#pragma unroll
                for (int i = 0; i < 4; i++) {
                    const uint4 v = qs[(s * 4 + i) * 32];
                    qf[i][s][0] = v.x; qf[i][s][1] = v.y; qf[i][s][2] = v.z; qf[i][s][3] = v.w;
                }
        }
        __syncthreads();
        if (tid == 0) { b_issue(p, BS_Q + BD, bi, sbase, pol); b_issue(p, BS_Q + 1 + BD, bi, sbase, pol); }
        float acc[2][8][4];
#pragma unroll
        for (int i = 0; i < 2; i++)
#pragma unroll
            for (int j = 0; j < 8; j++) { acc[i][j][0] = acc[i][j][1] = acc[i][j][2] = acc[i][j][3] = 0.f; }
        float mrun = -INFINITY, lrun = 0.f;
        const int head = tid >> 3, kq = tid & 7;
        float* alpha = reinterpret_cast<float*>(smem + M_ALPHA);
        for (int n = BS_CKV; n < BS_PART; n++) {
            b_wait(n, sbase);
            const uint32_t slot = sbase + (n % BRING) * SLOT;
            float sc[4][4][4];
#pragma unroll
            for (int i = 0; i < 4; i++)
#pragma unroll
                for (int j = 0; j < 4; j++) { sc[i][j][0] = sc[i][j][1] = sc[i][j][2] = sc[i][j][3] = 0.f; }
#pragma unroll
            for (int j = 0; j < 4; j++)
#pragma unroll
                for (int sp = 0; sp < 2; sp++) {
                    uint32_t bf[4];
                    ldsm4(bf, slot + warp * 4096 + (8 * j + (lane & 7)) * 128 + (((4 * sp + (lane >> 3)) ^ (lane & 7)) * 16));
#pragma unroll
                    for (int i = 0; i < 4; i++) {
                        mma16816(sc[i][j], qf[i][2 * sp], bf[0], bf[1]);
                        mma16816(sc[i][j], qf[i][2 * sp + 1], bf[2], bf[3]);
                    }
                }
#pragma unroll
            for (int i = 0; i < 4; i++)
#pragma unroll
                for (int j = 0; j < 4; j++)
                    *reinterpret_cast<float2*>(red + warp * 1024 + (8 * i + g) * 32 + ((8 * j) ^ (8 * (g & 3))) + 2 * t) =
                        make_float2(sc[i][j][0] + sc[i][j][2], sc[i][j][1] + sc[i][j][3]);
            __syncthreads();
            if (tid == 0 && n > BS_CKV) b_issue(p, n - 1 + BD, bi, sbase, pol);
            {
                float4 s = make_float4(0.f, 0.f, 0.f, 0.f);
#pragma unroll
                for (int w = 0; w < 8; w++) {
                    const float4 v = *reinterpret_cast<const float4*>(red + w * 1024 + head * 32 + ((4 * kq) ^ (8 * (head & 3))));
                    s.x += v.x; s.y += v.y; s.z += v.z; s.w += v.w;
                }
                const uint32_t r0 = pack_bf16(s.x, s.y), r1 = pack_bf16(s.z, s.w);
                const uint32_t s0 = pack_bf16(bf_lo(r0) * SCALE, bf_hi(r0) * SCALE);
                const uint32_t s1 = pack_bf16(bf_lo(r1) * SCALE, bf_hi(r1) * SCALE);
                const float f0 = bf_lo(s0), f1 = bf_hi(s0), f2 = bf_lo(s1), f3 = bf_hi(s1);
                float mx = fmaxf(fmaxf(f0, f1), fmaxf(f2, f3));
                mx = fmaxf(mx, __shfl_xor_sync(~0u, mx, 1));
                mx = fmaxf(mx, __shfl_xor_sync(~0u, mx, 2));
                mx = fmaxf(mx, __shfl_xor_sync(~0u, mx, 4));
                const float mnew = fmaxf(mrun, mx);
                const float al = expsub(mrun, mnew);
                const float p0 = expsub(f0, mnew), p1 = expsub(f1, mnew), p2 = expsub(f2, mnew), p3 = expsub(f3, mnew);
                lrun = lrun * al + ((p0 + p1) + (p2 + p3));
                mrun = mnew;
                *reinterpret_cast<uint2*>(smem + M_P + head * 80 + kq * 8) = make_uint2(pack_bf16(p0, p1), pack_bf16(p2, p3));
                if (kq == 0) alpha[head] = al;
            }
            __syncthreads();
            {
                uint32_t pf[2][2][4];
#pragma unroll
                for (int i = 0; i < 2; i++)
#pragma unroll
                    for (int ks = 0; ks < 2; ks++)
                        ldsm4(pf[i][ks], sbase + M_P + (16 * i + (lane & 15)) * 80 + (16 * ks + 8 * (lane >> 4)) * 2);
#pragma unroll
                for (int i = 0; i < 2; i++) {
                    const float a0 = alpha[16 * i + g], a1 = alpha[16 * i + 8 + g];
#pragma unroll
                    for (int j = 0; j < 8; j++) { acc[i][j][0] *= a0; acc[i][j][1] *= a0; acc[i][j][2] *= a1; acc[i][j][3] *= a1; }
                }
#pragma unroll
                for (int j = 0; j < 8; j++) {
                    uint32_t bf[4];
                    ldsm4t(bf, slot + warp * 4096 + lane * 128 + ((j ^ (lane & 7)) * 16));
#pragma unroll
                    for (int i = 0; i < 2; i++) {
                        mma16816(acc[i][j], pf[i][0], bf[0], bf[1]);
                        mma16816(acc[i][j], pf[i][1], bf[2], bf[3]);
                    }
                }
            }
        }
        __syncthreads();
        if (tid == 0) b_issue(p, BS_PART - 1 + BD, bi, sbase, pol);
        lrun += __shfl_xor_sync(~0u, lrun, 1);
        lrun += __shfl_xor_sync(~0u, lrun, 2);
        lrun += __shfl_xor_sync(~0u, lrun, 4);
        if (kq == 0) g_bml[head * NBCTA + bi] = make_float2(mrun, lrun);
#pragma unroll
        for (int i = 0; i < 2; i++)
#pragma unroll
            for (int j = 0; j < 8; j++) {
                g_bpart[((16 * i + g) * NBCTA + bi) * 256 + warp * 32 + j * 4 + t] = make_float2(acc[i][j][0], acc[i][j][1]);
                g_bpart[((16 * i + 8 + g) * NBCTA + bi) * 256 + warp * 32 + j * 4 + t] = make_float2(acc[i][j][2], acc[i][j][3]);
            }
    }
    if (!CLU) {
#pragma unroll 1
        for (int i = tid; i < NH * 36; i += 256) g_outb[bi * NH * 36 + i] = make_uint4(0u, epoch, 0u, epoch);
    }
    b_exchange(&ctl[C_BBAR + 1][0], BS_PART, &g_bpart[bi * NBCTA * 256], sbase, pol);
    {
        float* omega = reinterpret_cast<float*>(smem + M_OMEGA);
        if (warp == 0) {
            __syncwarp();
            const uint2 ml = ld_relaxed8(&g_bml[bi * NBCTA + lane]);
            const float ms = __uint_as_float(ml.x);
            float m = ms;
            m = fmaxf(m, __shfl_xor_sync(~0u, m, 1));
            m = fmaxf(m, __shfl_xor_sync(~0u, m, 2));
            m = fmaxf(m, __shfl_xor_sync(~0u, m, 4));
            const float w = expsub(ms, m);
            float l = w * __uint_as_float(ml.y);
            l += __shfl_xor_sync(~0u, l, 1);
            l += __shfl_xor_sync(~0u, l, 2);
            l += __shfl_xor_sync(~0u, l, 4);
            omega[lane] = w / l;
        }
        __syncthreads();
        b_wait(BS_PART, sbase);
        b_wait(BS_PART + 1, sbase);
#pragma unroll 1
        for (int b = 0; b < 4; b++) {
            const float2* ps = reinterpret_cast<const float2*>(smem + ((BS_PART + (b >> 1)) % BRING) * SLOT) + (b & 1) * 2048 + tid;
            float c0 = 0.f, c1 = 0.f;
#pragma unroll
            for (int s = 0; s < 8; s++) {
                const float w = omega[b * 8 + s];
                const float2 v = ps[s * 256];
                c0 = fmaf(w, v.x, c0);
                c1 = fmaf(w, v.y, c1);
            }
            const uint32_t hi = pack_bf16(c0, c1);
            *reinterpret_cast<uint32_t*>(smem + M_CH + b * CP + tid * 4) = hi;
            *reinterpret_cast<uint32_t*>(smem + M_CL + b * CP + tid * 4) = pack_bf16(c0 - bf_lo(hi), c1 - bf_hi(hi));
        }
        __syncthreads();
        if (tid == 0) { b_issue(p, BS_PART + BD, bi, sbase, pol); b_issue(p, BS_PART + 1 + BD, bi, sbase, pol); }
    }
    b_gemm(p, sbase, BS_WUV, BS_END, 512, sbase + M_CH, sbase + M_CL, CP, bi, pol);
    TS(12);
    if (CLU) {
        if (warp < 4) {
            const unsigned short* c = reinterpret_cast<const unsigned short*>(smem + M_QB + warp * QP) + 16 * t + g;
            g_octx[(bi * 4 + warp) * 32 + lane] = make_float4(bf_lo(c[0]), bf_lo(c[8]), bf_lo(c[64]), bf_lo(c[72]));
        }
        __syncthreads();
        if (tid == 0) asm volatile("st.release.gpu.global.u32 [%0], %1;" ::"l"(&g_cdone[bi][0]), "r"(epoch + 1) : "memory");
        return;
    }
    if (tid == 0) {
#pragma unroll 1
        for (int i = 0; i < 4; i++) {
            mbar_expect_tx(sbase + M_BAR + i * 8, 36864);
            tma3d(sbase + i * 36864, &p.tm_wo, 0, bi * 128 + i * 32, 0, sbase + M_BAR + i * 8, pol);
        }
    }
    TS(8);
    {
        float acc[9][4];
#pragma unroll
        for (int j = 0; j < 9; j++) { acc[j][0] = acc[j][1] = acc[j][2] = acc[j][3] = 0.f; }
#pragma unroll 1
        for (int i = 0; i < 4; i++) {
            const uint32_t xo = sbase + M_QB + (g & 3) * QP + i * 64 + t * 4;
            const uint32_t a0[4] = {lds32(xo), 0u, lds32(xo + 16), 0u}, a1[4] = {lds32(xo + 32), 0u, lds32(xo + 48), 0u};
            mbar_wait(sbase + M_BAR + i * 8, 0);
#pragma unroll
            for (int j = 0; j < 9; j++) {
                const int nt = warp * 9 + j;
                uint32_t w[4];
                ldsm4t(w, sbase + i * 36864 + (nt >> 3) * 4096 + lane * 128 + (((nt & 7) ^ (lane & 7)) * 16));
                mma16816(acc[j], a0, w[0], w[1]);
                mma16816(acc[j], a1, w[2], w[3]);
            }
        }
        if (g < 4) {
#pragma unroll
            for (int j = 0; j < 9; j++) {
                const int c2 = (warp * 9 + j) * 4 + t;
                st_tagged2(&g_outb[((c2 / 9) * NH + bi) * 36 + g * 9 + c2 % 9], acc[j][0], acc[j][1], epoch + 1);
            }
        }
    }
    TS(9);
    {
        const uint4* src = g_outb + (bi * NH + (tid >> 3)) * 36 + (tid & 7);
        float2* part = reinterpret_cast<float2*>(red);
        unsigned n = 0;
        while (true) {
            ulonglong2 v[5];
            bool ok = true;
#pragma unroll
            for (int i = 0; i < 5; i++)
                if (i < 4 || (tid & 7) < 4) v[i] = ld_tagged2(src + i * 8);
#pragma unroll
            for (int i = 0; i < 5; i++)
                if (i < 4 || (tid & 7) < 4) {
                    ok = ok && (unsigned)(v[i].x >> 32) == epoch + 1 && (unsigned)(v[i].y >> 32) == epoch + 1;
                    part[(tid >> 3) * 36 + (tid & 7) + i * 8] = make_float2(__uint_as_float((unsigned)v[i].x), __uint_as_float((unsigned)v[i].y));
                }
            if (ok) break;
            __nanosleep(400);
            if (++n > SPIN_LIMIT) __trap();
        }
        __syncthreads();
        if (tid < 36) {
            float s0 = 0.f, s1 = 0.f;
#pragma unroll 8
            for (int h = 0; h < NH; h++) { const float2 v = part[h * 36 + tid]; s0 += v.x; s1 += v.y; }
            *reinterpret_cast<uint32_t*>(p.out + (tid / 9) * 2 * DM + DM + bi * 18 + (tid % 9) * 2) = pack_bf16(s0, s1);
        }
    }
    TS(10);
}

template <bool CLU>
__global__ void __launch_bounds__(256, 1) fused_decode_kernel(const __grid_constant__ Params p) {
    asm volatile("{\n.reg .pred p;\n.reg .u32 a;\n.reg .u64 b;\nsub.u32 a, %1, %4;\nsetp.lt.u32 p, a, %3;\nmad.lo.u32 a, %2, %6, %1;\n"
                 "mad.wide.u32 b, a, %5, %0;\n"
                 "@p prefetch.global.L2 [b];\n}"
                 ::"l"(p.pf), "r"(threadIdx.x), "r"(blockIdx.x), "n"(PFN), "n"(PF0), "n"(PFS), "n"(PFC) : "memory");
    extern __shared__ __align__(1024) char smem_raw[];
    const uint32_t sbase = (smem_u32(smem_raw) + 1023u) & ~1023u;
    if (CLU && threadIdx.x < 32 && blockIdx.x >= NBCTA) {
        const unsigned u0 = blockIdx.x - NBCTA, u1 = u0 + 8 * MINCL - NBCTA;
        asm volatile("{\n.reg .pred p;\nelect.sync _|p, 0xffffffff;\n"
                     "@p mbarrier.init.shared::cta.b64 [%0], 1;\n"
                     "@p mbarrier.init.shared::cta.b64 [%0+8], 1;\n"
                     "@p fence.mbarrier_init.release.cluster;\n"
                     "@p mbarrier.arrive.expect_tx.shared::cta.b64 _, [%0], 32768;\n"
                     "@p cp.async.bulk.shared::cluster.global.mbarrier::complete_tx::bytes.L2::cache_hint [%1], [%2], 32768, [%0], %4;\n"
                     "@p mbarrier.arrive.expect_tx.shared::cta.b64 _, [%0+8], 32768;\n"
                     "@p cp.async.bulk.shared::cluster.global.mbarrier::complete_tx::bytes.L2::cache_hint [%1+32768], [%3], 32768, [%0+8], %4;\n}"
                     ::"r"(sbase + M_BAR), "r"(sbase), "l"(reinterpret_cast<const char*>(p.kc) + (size_t)u0 * TILE_BYTES),
                       "l"(reinterpret_cast<const char*>(p.kc) + (size_t)((u1 >> 7) * 1024 + (u1 & 127)) * TILE_BYTES), "l"(0x12F0000000000000ull) : "memory");
    }
    char* smem = smem_raw + (sbase - smem_u32(smem_raw));
    const int tid = threadIdx.x, warp = tid >> 5, lane = tid & 31;
    const int blk = blockIdx.x;
    const bool isB = CLU ? blk < NBCTA : (blk & 3) == 0 && (blk >> 2) < NBCTA;
    const int bi = CLU ? blk : blk >> 2;
    const int nb = CLU ? blk - NBCTA : blk - min(NBCTA, (blk + 3) >> 2);
    const int nblk = CLU ? 8 * MINCL : gridDim.x, nnb = nblk - NBCTA;
    const int nstatic = nnb * (NW + XW);
    uint64_t pol;
    asm volatile("createpolicy.fractional.L2::evict_first.b64 %0, 1.0;" : "=l"(pol));
    const uint32_t wbar = sbase + M_BAR + warp * 8, wslot = sbase + warp * SLOT;
    const int u0 = warp * nnb + nb;
    const bool hold = ((blk >> 2) >> KMIN << KMIN) * 4 * UPP < nstatic;
    const uint32_t jbar = sbase + M_BAR + (NSLOT + BRING) * 8;
    if (warp == 7) {
        if (lane == 0 && blk < 128) {
            mbar_init(jbar, 1);
            asm volatile("fence.mbarrier_init.release.cluster;" ::: "memory");
            uint64_t poln;
            asm volatile("createpolicy.fractional.L2::evict_normal.b64 %0, 1.0;" : "=l"(poln));
            mbar_expect_tx(jbar, 36864 + 4 * 1152);
            tma3d(sbase + J0W, &p.tm_j0, blk * 32, 0, 0, jbar, poln);
            bulk_load(sbase + M_XA, p.xa, 4608, jbar, poln);
        }
        if (lane < 8) reinterpret_cast<unsigned*>(smem + M_HELP)[lane] = 0;
        __syncwarp();
        if (!isB) asm volatile("bar.arrive 2, %0;" ::"n"(32 * (NW + XW + 1)) : "memory");
    }
    if (warp < 4 && lane == 0 && (!CLU || isB || warp >= 2)) {
        mbar_init(wbar, 1);

        asm volatile("fence.mbarrier_init.release.cluster;" ::: "memory");
        if (warp < NEARLY && !isB && !hold) {
            mbar_expect_tx(wbar, TILE_BYTES);
            bulk_load(wslot, block_src(p.kc, unit_block<CLU>(u0)), TILE_BYTES, wbar, pol);
        }
    }
    unsigned epoch = 0;
    if (lane == 0) epoch = ld_relaxed4(&g_epoch);
    TS(0);
    if (CLU) {
        if (warp == 6) {
            if (lane < 8 + 8 * PH && lane != 1) mbar_init(sbase + F_BAR + lane * 8, 1);
            if ((lane >> 1) == 1) mbar_expect_tx(sbase + F_BAR + lane * 8, 1024);
            asm volatile("fence.mbarrier_init.release.cluster;" ::: "memory");
        }
        asm volatile("barrier.cluster.arrive.relaxed.aligned;" ::: "memory");
    }
    if ((warp >> 1) == 2 && blk < 128) st_relaxed64(&g_qll[((tid - 128) >> 4) * 2048 + blk * 16 + (tid & 15)], 0ull);
    if (isB || warp >= NW + XW) epoch = __shfl_sync(~0u, epoch, 0);
    if (isB && warp == 3) asm volatile("bar.sync 1, 160;" ::: "memory");
    if (isB && tid == 96) {
#pragma unroll 1
        for (int i = 0; i < BRING; i++) mbar_init(sbase + M_BAR + (NSLOT + i) * 8, 1);
        asm volatile("fence.mbarrier_init.release.cluster;" ::: "memory");
        if (hold) { unsigned n = 0; while (ld_acquire_cta_shared(sbase + M_HELP + 24) < 2) { if (++n > (SPIN_LIMIT << 4)) __trap(); } }
#pragma unroll 1
        for (int b = 0; b < 4; b++) bulk_load(sbase + M_XB + b * XP, p.xb + b * DM, 1152, sbase + M_BAR + NSLOT * 8, pol);
#pragma unroll 1
        for (int n = 0; n < BD; n++) b_issue(p, n, bi, sbase, pol);
    }
    if (warp >= 4 && blk < 128) {
        const int g = lane >> 2, t = lane & 3, j = tid - 128;
        asm volatile("bar.sync 1, %0;" ::"r"(isB ? 160 : 128) : "memory");
#pragma unroll 1
        for (int sl = blk, ph = 0;; sl += 128 - nblk, ph = 1) {
        mbar_wait(jbar, ph);
        TS(13);
        float acc[4][4];
#pragma unroll
        for (int i = 0; i < 16; i++) acc[i >> 2][i & 3] = 0.f;
        const uint32_t wa = sbase + J0W + ((warp - 4) * 144 + (lane & 15)) * 64;
        const uint32_t sw = (lane >> 1) & 3, xa = sbase + M_XA + (g & 3) * 1152 + (warp - 4) * 288 + t * 4;
#pragma unroll 3
        for (int s = 0; s < 9; s++) {
            const uint32_t a[4] = {lds32(xa + s * 32), 0u, lds32(xa + s * 32 + 16), 0u};
            uint32_t w0[4], w1[4];
            ldsm4t(w0, wa + s * 1024 + (((lane >> 4) ^ sw) * 16));
            ldsm4t(w1, wa + s * 1024 + (((2 + (lane >> 4)) ^ sw) * 16));
            mma16816(acc[0], a, w0[0], w0[1]);
            mma16816(acc[1], a, w0[2], w0[3]);
            mma16816(acc[2], a, w1[0], w1[1]);
            mma16816(acc[3], a, w1[2], w1[3]);
        }
        float2* j0 = reinterpret_cast<float2*>(smem + M_J0);
        if (g < 4) {
#pragma unroll
            for (int i = 0; i < 4; i++) j0[(warp - 4) * 64 + g * 16 + i * 4 + t] = make_float2(acc[i][0], acc[i][1]);
        }
        asm volatile("bar.sync 1, 128;" ::: "memory");
        const bool again = sl == blk && blk + 128 - nblk >= nblk;
        if (again && tid == 224) {
            mbar_expect_tx(jbar, 36864);
            tma3d(sbase + J0W, &p.tm_j0, (blk + 128 - nblk) * 32, 0, 0, jbar, pol);
        }
        if (warp < 6) {
            const float2 v0 = j0[j], v1 = j0[64 + j], v2 = j0[128 + j], v3 = j0[192 + j];
            st_relaxed64(&g_qll[(j >> 4) * 2048 + sl * 16 + (j & 15)],
                         (unsigned long long)pack_bf16((v0.x + v1.x) + (v2.x + v3.x), (v0.y + v1.y) + (v2.y + v3.y)) |
                             ((unsigned long long)(epoch + 1) << 32));
            __syncwarp();
            if (lane == 0) asm volatile("red.relaxed.cta.shared::cta.add.u32 [%0], 1;" ::"r"(sbase + M_HELP + 24) : "memory");
        } else if (warp == 7) {
            if (blk < C_LINES) g_ctl[(epoch & 1) ^ 1][blk][lane] = 0;
        }
        TS(1);
        if (!again) break;
        asm volatile("bar.sync 1, 128;" ::: "memory");
        }
    }
    if (isB) {
        b_chain<CLU>(p, smem, sbase, bi, epoch, pol);
        if (CLU) b_final(p, sbase, blk, epoch, pol);
        return;
    }
    const int sl = nb >> 3, rank = blk & 7;
    if (warp < NW + XW) {
        a_worker<CLU>(p, u0, warp >= NW + ((nb & 3) < (CLU ? X3C : X3) ? 1 : 0), warp < NEARLY && !hold, hold, nstatic, wslot, wbar, sbase + M_HELP,
                      epoch, pol);
        const bool two = sl < 9 && rank == 7;
        if (CLU && (warp == 3 || (warp == 2 && two)) && sl < 10) {
            epoch = __shfl_sync(~0u, epoch, 0);
            unsigned n = 0;
            while (ld_acquire_cta_shared(sbase + M_HELP + 12) == 0) { __nanosleep(1000); if (++n > SPIN_LIMIT) __trap(); }
            asm volatile("barrier.cluster.wait.acquire.aligned;" ::: "memory");
            f_collect((sl < 9 ? g_vdone : g_cdone) + 4 * rank, sl < 9 ? 4 * UPP : epoch + 1, (sl < 9 ? g_oacc : g_octx) + 4 * rank * 128,
                      two ? (warp == 2 ? CM2 : 15 - CM2) : 15, sbase);
            if (warp == 2) return;
            mbar_wait(sbase + F_BAR, 0);
#pragma unroll 1
            for (int i = 0; i < 2; i++) f_receive(p.out + (sl < 9 ? sl * 64 : DM + 512) + rank * 8, 0, i == 0, sbase);
        }
        return;
    }
    if (warp == 7) {
#pragma unroll 1
        for (int i = nb; i < 4 * NH; i += nnb) g_oacc[i * 32 + lane] = make_float4(0.f, 0.f, 0.f, 0.f);
        if (nb < NREP * NH) g_vdone[nb][lane] = 0;
        __syncwarp();
        k_helper(sbase + M_HELP, epoch);
        if (nb == 0 && lane == 0) g_epoch = epoch + 1;
        __syncwarp();
    }
    if (CLU) {
        if (sl < 10) {
            const CUtensorMap* tm = sl < 9 ? &p.tm_fa : &p.tm_fb;
            asm volatile("barrier.cluster.wait.acquire.aligned;" ::: "memory");
            f_project(tm, min(sl, 8), rank, 0, warp & 3, A0 + (warp & 3) * AJ + rank * AR - max(0, (warp & 3) * 8 + rank - AK) * AC, ASTEP, epoch + 1, sbase, pol);
        }
    } else if (warp == 6 && nb < NFIN) {
        finisher(p, sbase, nb);
        TS(4);
    } else if (warp != 7 && warp >= 6 - NPOLL && nb < NFIN) {
        v_poller(sbase, nb, warp - (6 - NPOLL));
    }
}

}

typedef CUresult (*EncodeFn)(CUtensorMap*, CUtensorMapDataType, cuuint32_t, void*, const cuuint64_t*, const cuuint64_t*,
                             const cuuint32_t*, const cuuint32_t*, CUtensorMapInterleave, CUtensorMapSwizzle,
                             CUtensorMapL2promotion, CUtensorMapFloatOOBfill);

extern "C" void kernel_launch(void* const* d_in, const int* in_sizes, int n_in, void* d_out, int out_size) {
    (void)in_sizes; (void)n_in; (void)out_size;
    static int nsm = 0, ncl = 0;
    static EncodeFn encode = nullptr;
    cudaLaunchConfig_t cfg = {};
    cudaLaunchAttribute at[1];
    at[0].id = cudaLaunchAttributeClusterDimension;
    at[0].val.clusterDim.x = 8; at[0].val.clusterDim.y = 1; at[0].val.clusterDim.z = 1;
    cfg.blockDim = dim3(256); cfg.dynamicSmemBytes = SMEM_BYTES; cfg.stream = cudaStreamPerThread; cfg.attrs = at; cfg.numAttrs = 1;
    if (nsm == 0) {
        int dev = 0;
        cudaGetDevice(&dev);
        cudaDeviceGetAttribute(&nsm, cudaDevAttrMultiProcessorCount, dev);
        cudaFuncSetAttribute(fused_decode_kernel<false>, cudaFuncAttributeMaxDynamicSharedMemorySize, SMEM_BYTES);
        cudaFuncSetAttribute(fused_decode_kernel<true>, cudaFuncAttributeMaxDynamicSharedMemorySize, SMEM_BYTES);
        cfg.gridDim = dim3(128);
        if (cudaOccupancyMaxActiveClusters(&ncl, fused_decode_kernel<true>, &cfg) != cudaSuccess) { ncl = 0; (void)cudaGetLastError(); }
        if (ncl > MINCL) ncl = MINCL;
        void* fn = nullptr;
        cudaDriverEntryPointQueryResult qr;
        cudaGetDriverEntryPoint("cuTensorMapEncodeTiled", &fn, cudaEnableDefault, &qr);
        encode = (EncodeFn)fn;
    }
    Params p;
    auto panels = [&](CUtensorMap* tm, void* ptr, int rows, int cols, int box_rows, int box_panels,
                      CUtensorMapL2promotion promo = CU_TENSOR_MAP_L2_PROMOTION_L2_256B) {
        const cuuint64_t gd[3] = {64, (cuuint64_t)rows, (cuuint64_t)(cols / 64)}, gs[2] = {(cuuint64_t)cols * 2, 128};
        const cuuint32_t box[3] = {64, (cuuint32_t)box_rows, (cuuint32_t)box_panels}, es[3] = {1, 1, 1};
        encode(tm, CU_TENSOR_MAP_DATA_TYPE_BFLOAT16, 3, ptr, gd, gs, box, es, CU_TENSOR_MAP_INTERLEAVE_NONE,
               CU_TENSOR_MAP_SWIZZLE_128B, promo, CU_TENSOR_MAP_FLOAT_OOB_FILL_NONE);
    };
    panels(&p.tm_wq, d_in[7], DM, 4096, 128, 2);
    panels(&p.tm_wuk, d_in[8], 512, 4096, 128, 2);
    panels(&p.tm_wuv, d_in[9], 512, 4096, 128, 2);
    panels(&p.tm_wo, d_in[10], 4096, DM, 32, 9);
    panels(&p.tm_ckv, d_in[6], 4 * SK, 512, 32, 8);
    panels(&p.tm_fa, d_in[4], 4096, DM, 128 / PH, 1, CU_TENSOR_MAP_L2_PROMOTION_L2_128B);
    panels(&p.tm_fb, d_in[10], 4096, DM, 128 / PH, 1, CU_TENSOR_MAP_L2_PROMOTION_L2_128B);
    {
        const cuuint64_t gd[3] = {4096, 192, 3}, gs[2] = {8192, 192 * 8192};
        const cuuint32_t box[3] = {32, 192, 3}, es[3] = {1, 1, 1};
        encode(&p.tm_j0, CU_TENSOR_MAP_DATA_TYPE_BFLOAT16, 3, d_in[3], gd, gs, box, es, CU_TENSOR_MAP_INTERLEAVE_NONE,
               CU_TENSOR_MAP_SWIZZLE_64B, CU_TENSOR_MAP_L2_PROMOTION_L2_128B, CU_TENSOR_MAP_FLOAT_OOB_FILL_NONE);
    }
    p.xa = (const __nv_bfloat16*)d_in[0];
    p.kc = (const __nv_bfloat16*)d_in[1];
    p.vc = (const __nv_bfloat16*)d_in[2];
    p.pf = (const char*)d_in[1] + (size_t)PFOFF * TILE_BYTES - PF0 * PFS;
    p.wo = (const __nv_bfloat16*)d_in[4];
    p.xb = (const __nv_bfloat16*)d_in[5];
    p.out = (__nv_bfloat16*)d_out;
    if (ncl >= MINCL) {
        cfg.gridDim = dim3(8 * ncl);
        cudaLaunchKernelEx(&cfg, fused_decode_kernel<true>, p);
    } else {
        fused_decode_kernel<false><<<nsm, 256, SMEM_BYTES, cudaStreamPerThread>>>(p);
    }
}
```

```cpp
#include <cuda_runtime.h>
#include <cuda.h>
#include <cuda_bf16.h>
#include <stdint.h>

namespace {

constexpr int NH = 32, SK = 4096, DM = 576;
constexpr int KEYS = 128;
constexpr int UPP = SK / KEYS;
constexpr int NUK = 4 * NH * UPP;
constexpr int TILE_BYTES = KEYS * 256;
#define NWORK 2
constexpr int NW = NWORK;
constexpr int NBCTA = 32;
constexpr int MINCL = 15;
constexpr int NFIN = 72;
constexpr int SLOT = 32768;
constexpr int NSLOT = 6;
constexpr int BRING = 5;
constexpr int J0W = 5 * SLOT;
constexpr int MISC = NSLOT * SLOT + 4096;
constexpr int XP = 1168, CP = 1040, QP = 272;
constexpr int M_XA = MISC;
constexpr int M_XB = M_XA + 4 * XP;
constexpr int M_CH = M_XB + 4 * XP;
constexpr int M_CL = M_CH + 4 * CP;
constexpr int M_QB = M_CL + 4 * CP;
constexpr int M_QA = M_CH;
constexpr int M_J0 = M_QB + 4 * QP;
constexpr int M_P = M_J0 + 2048;
constexpr int M_ALPHA = M_P + 2560;
constexpr int M_OMEGA = M_ALPHA + 128;
constexpr int M_BAR = M_OMEGA + 128;
constexpr int M_HELP = M_BAR + 128;
constexpr int F_W = 4 * SLOT;
constexpr int F_BF = (M_HELP + 128 + 255) / 256 * 256;
constexpr int F_RX = F_BF + 4096;
constexpr int F_BAR = F_RX + 2048;
constexpr int SMEM_BYTES = F_BAR + 128 + 1024;
static_assert(SMEM_BYTES <= 232448 && M_BAR % 8 == 0 && M_QA % 16 == 0 && M_P % 16 == 0, "smem layout");
#define XW 2
#define X3 1
#define X3C 3
#define NEARLY 3
#define BD 5
#define FPF 3
#define FSLEEP 800
#define VS0 24
#define EARLY 100
#define ELOG 5
#define TPU 159
#define A0 3000
#define AJ 700
#define AR (AJ / 8)
#define LAG 2
#define PFN 96
#define PFS 128
#define PFC PFN
#define PFLD 0
#define PF0 128
#define PFOFF 0
#define CM2 10
#define B0 2500
#define BJ 700
#define BS 300
#define BR (BJ / 8)
#define NPOLL 2
#define PGAP 200
static_assert(X3C <= 3 && NW == 2, "warp 2 of rank 7 is free");
static_assert(NW + XW <= 4 && NEARLY <= NW + XW && BD <= BRING, "slots 4 and 5 hold the finisher weights");
#define KMAX 4
#define VMAX 4
constexpr int KMIN = 2, VMIN = 0;
constexpr float SCALE = 0.08838834764831845f;
constexpr float LOG2E = 1.4426950408889634f;
constexpr unsigned SPIN_LIMIT = 1u << 24;

#define NREP 2
#define NREPC 1
constexpr int C_QUEUE = 0, C_KDONE = 1, C_BBAR = 3, C_LINES = 5;

struct Params {
    const char* pf;
    const __nv_bfloat16 *kc, *xa, *vc, *wo, *xb;
    __nv_bfloat16* out;
    CUtensorMap tm_j0;
    CUtensorMap tm_wq, tm_wuk, tm_ckv, tm_wuv, tm_wo;
    CUtensorMap tm_fa, tm_fb;
};

__device__ unsigned g_epoch;
__device__ unsigned g_ctl[2][C_LINES][32];
__device__ uint2 g_qll[4 * 2048];
__device__ uint2 g_scores[128 * SK / 4];
__device__ float2 g_stats[128 * UPP];
__device__ float4 g_oacc[128 * 32];
__device__ unsigned g_vdone[NREP * NH][32];
__device__ float4 g_octx[128 * 32];
__device__ unsigned g_cdone[NH][32];
__device__ unsigned long long g_dry[16][16];
__device__ uint4 g_qabs[4 * 8 * 4 * 4 * 32];
__device__ float2 g_bpart[NBCTA * NH * 256];
__device__ float2 g_bml[NBCTA * NH];
__device__ uint4 g_outb[NBCTA * NH * 36];

#define TS(i)
#define TSV(i, v)
#define LAND(i)
#define CLK(x)
#define ACC(a, x, y)

__device__ __forceinline__ uint32_t smem_u32(const void* p) { return (uint32_t)__cvta_generic_to_shared(p); }
__device__ __forceinline__ void mbar_init(uint32_t bar, uint32_t cnt) {
    asm volatile("mbarrier.init.shared::cta.b64 [%0], %1;" ::"r"(bar), "r"(cnt) : "memory");
}
__device__ __forceinline__ void mbar_expect_tx(uint32_t bar, uint32_t bytes) {
    asm volatile("mbarrier.arrive.expect_tx.shared::cta.b64 _, [%0], %1;" ::"r"(bar), "r"(bytes) : "memory");
}
__device__ __forceinline__ bool mbar_try(uint32_t bar, uint32_t parity) {
    uint32_t ok;
    asm volatile("{\n.reg .pred p;\nmbarrier.try_wait.parity.shared::cta.b64 p, [%1], %2;\nselp.u32 %0, 1, 0, p;\n}\n"
                 : "=r"(ok) : "r"(bar), "r"(parity) : "memory");
    return ok;
}
__device__ __forceinline__ void mbar_wait(uint32_t bar, uint32_t parity) {
    unsigned n = 0;
    while (!mbar_try(bar, parity)) { if (++n > SPIN_LIMIT) __trap(); }
}
__device__ __forceinline__ void mbar_spin(uint32_t bar) {
    asm volatile("{\n.reg .pred p;\n.reg .u32 n;\nmov.u32 n, 0;\nSPIN:\nmbarrier.try_wait.parity.shared::cta.b64 p, [%0], 0;\n@p bra.uni DONE;\n"
                 "add.u32 n, n, 1;\nsetp.lt.u32 p, n, 0x1000000;\n@p bra.uni SPIN;\ntrap;\nDONE:\n}" ::"r"(bar) : "memory");
}
__device__ __forceinline__ void mbar_spin_cluster(uint32_t bar) {
    asm volatile("{\n.reg .pred p;\n.reg .u32 n;\nmov.u32 n, 0;\nSPIN:\nmbarrier.try_wait.parity.relaxed.cluster.shared::cta.b64 p, [%0], 0;\n"
                 "@p bra.uni DONE;\nadd.u32 n, n, 1;\nsetp.lt.u32 p, n, 0x1000000;\n@p bra.uni SPIN;\ntrap;\nDONE:\n"
                 "fence.acquire.sync_restrict::shared::cluster.cluster;\n}" ::"r"(bar) : "memory");
}
__device__ __forceinline__ void bulk_load(uint32_t dst, const void* src, uint32_t bytes, uint32_t bar, uint64_t pol) {
    asm volatile("cp.async.bulk.shared::cluster.global.mbarrier::complete_tx::bytes.L2::cache_hint [%0], [%1], %2, [%3], %4;"
                 ::"r"(dst), "l"(src), "r"(bytes), "r"(bar), "l"(pol) : "memory");
}
__device__ __forceinline__ void tma3d(uint32_t dst, const CUtensorMap* tm, int c0, int c1, int c2, uint32_t bar, uint64_t pol) {
    asm volatile("cp.async.bulk.tensor.3d.shared::cluster.global.mbarrier::complete_tx::bytes.L2::cache_hint [%0], [%1, {%3,%4,%5}], [%2], %6;"
                 ::"r"(dst), "l"(tm), "r"(bar), "r"(c0), "r"(c1), "r"(c2), "l"(pol) : "memory");
}
__device__ __forceinline__ void l2_prefetch(const void* src, uint32_t bytes) {
    asm volatile("cp.async.bulk.prefetch.L2.global [%0], %1;" ::"l"(src), "r"(bytes) : "memory");
}
__device__ __forceinline__ void ldsm4(uint32_t (&r)[4], uint32_t addr) {
    asm volatile("ldmatrix.sync.aligned.m8n8.x4.shared.b16 {%0,%1,%2,%3}, [%4];"
                 : "=r"(r[0]), "=r"(r[1]), "=r"(r[2]), "=r"(r[3]) : "r"(addr));
}
__device__ __forceinline__ void ldsm4t(uint32_t (&r)[4], uint32_t addr) {
    asm volatile("ldmatrix.sync.aligned.m8n8.x4.trans.shared.b16 {%0,%1,%2,%3}, [%4];"
                 : "=r"(r[0]), "=r"(r[1]), "=r"(r[2]), "=r"(r[3]) : "r"(addr));
}
__device__ __forceinline__ void mma16816(float (&d)[4], const uint32_t (&a)[4], uint32_t b0, uint32_t b1) {
    asm("mma.sync.aligned.m16n8k16.row.col.f32.bf16.bf16.f32 {%0,%1,%2,%3}, {%4,%5,%6,%7}, {%8,%9}, {%0,%1,%2,%3};"
        : "+f"(d[0]), "+f"(d[1]), "+f"(d[2]), "+f"(d[3])
        : "r"(a[0]), "r"(a[1]), "r"(a[2]), "r"(a[3]), "r"(b0), "r"(b1));
}
__device__ __forceinline__ uint32_t lds32(uint32_t a) {
    uint32_t v;
    asm volatile("ld.shared.u32 %0, [%1];" : "=r"(v) : "r"(a));
    return v;
}
__device__ __forceinline__ unsigned ld_acquire(const unsigned* p) {
    unsigned v;
    asm volatile("ld.acquire.gpu.global.u32 %0, [%1];" : "=r"(v) : "l"(p) : "memory");
    return v;
}
__device__ __forceinline__ uint2 ld_relaxed8(const void* p) {
    uint2 v;
    asm volatile("ld.relaxed.gpu.global.v2.u32 {%0,%1}, [%2];" : "=r"(v.x), "=r"(v.y) : "l"(p) : "memory");
    return v;
}
__device__ __forceinline__ unsigned ld_relaxed4(const void* p) {
    unsigned v;
    asm volatile("ld.relaxed.gpu.global.u32 %0, [%1];" : "=r"(v) : "l"(p) : "memory");
    return v;
}
__device__ __forceinline__ unsigned atom_inc(unsigned* p) {
    unsigned v;
    asm volatile("atom.relaxed.gpu.global.inc.u32 %0, [%1], 0x7fffffff;" : "=r"(v) : "l"(p) : "memory");
    return v;
}
__device__ __forceinline__ unsigned long long ld_relaxed64(const void* p) {
    unsigned long long v;
    asm volatile("ld.relaxed.gpu.global.u64 %0, [%1];" : "=l"(v) : "l"(p) : "memory");
    return v;
}
__device__ __forceinline__ void st_relaxed64(void* p, unsigned long long v) {
    asm volatile("st.relaxed.gpu.global.u64 [%0], %1;" ::"l"(p), "l"(v) : "memory");
}
__device__ __forceinline__ float4 ld_relaxed16(const void* p) {
    float4 v;
    asm volatile("ld.relaxed.gpu.global.v4.f32 {%0,%1,%2,%3}, [%4];" : "=f"(v.x), "=f"(v.y), "=f"(v.z), "=f"(v.w) : "l"(p) : "memory");
    return v;
}
__device__ __forceinline__ uint32_t mapa(uint32_t a, uint32_t rank) {
    uint32_t r;
    asm("mapa.shared::cluster.u32 %0, %1, %2;" : "=r"(r) : "r"(a), "r"(rank));
    return r;
}
__device__ __forceinline__ uint32_t time_ns() { uint32_t t; asm volatile("mov.u32 %0, %globaltimer_lo;" : "=r"(t)); return t; }
__device__ __forceinline__ void fence_gpu() { asm volatile("fence.acq_rel.gpu;" ::: "memory"); }
__device__ __forceinline__ void red_add_u32(unsigned* p, unsigned v) {
    asm volatile("red.relaxed.gpu.global.add.u32 [%0], %1;" ::"l"(p), "r"(v) : "memory");
}
__device__ __forceinline__ void st_tagged2(void* p, float a, float b, unsigned tag) {
    const unsigned long long hi = (unsigned long long)tag << 32;
    asm volatile("st.relaxed.gpu.global.v2.b64 [%0], {%1,%2};" ::"l"(p), "l"(hi | __float_as_uint(a)), "l"(hi | __float_as_uint(b)) : "memory");
}
__device__ __forceinline__ ulonglong2 ld_tagged2(const void* p) {
    ulonglong2 v;
    asm volatile("ld.relaxed.gpu.global.v2.b64 {%0,%1}, [%2];" : "=l"(v.x), "=l"(v.y) : "l"(p) : "memory");
    return v;
}
__device__ __forceinline__ float4 atom_add_f4(void* p, float a, float b, float c, float d) {
    float4 r;
    asm volatile("atom.relaxed.gpu.global.add.v4.f32 {%0,%1,%2,%3}, [%4], {%5,%6,%7,%8};"
                 : "=f"(r.x), "=f"(r.y), "=f"(r.z), "=f"(r.w) : "l"(p), "f"(a), "f"(b), "f"(c), "f"(d) : "memory");
    return r;
}
__device__ __forceinline__ void red_release_cta_shared(uint32_t a, unsigned v) {
    asm volatile("red.release.cta.shared::cta.add.u32 [%0], %1;" ::"r"(a), "r"(v) : "memory");
}
__device__ __forceinline__ unsigned ld_acquire_cta_shared(uint32_t a) {
    unsigned v;
    asm volatile("ld.acquire.cta.shared::cta.u32 %0, [%1];" : "=r"(v) : "r"(a) : "memory");
    return v;
}
__device__ __forceinline__ void st_release_cta_shared(uint32_t a, unsigned v) {
    asm volatile("st.release.cta.shared::cta.u32 [%0], %1;" ::"r"(a), "r"(v) : "memory");
}
__device__ __forceinline__ void wait_count(const unsigned* p, unsigned target) {
    unsigned n = 0;
    while (ld_acquire(p) < target) { if (++n > SPIN_LIMIT) __trap(); }
}
__device__ __forceinline__ uint32_t pack_bf16(float lo, float hi) {
    uint32_t r;
    asm("cvt.rn.bf16x2.f32 %0, %1, %2;" : "=r"(r) : "f"(hi), "f"(lo));
    return r;
}
__device__ __forceinline__ float bf_lo(uint32_t v) { return __uint_as_float(v << 16); }
__device__ __forceinline__ float bf_hi(uint32_t v) { return __uint_as_float(v & 0xffff0000u); }
__device__ __forceinline__ float ex2(float x) { float y; asm("ex2.approx.ftz.f32 %0, %1;" : "=f"(y) : "f"(x)); return y; }
__device__ __forceinline__ float expsub(float a, float b) { return ex2((a - b) * LOG2E); }
__device__ __forceinline__ float warp_max(float v) {
#pragma unroll
    for (int m = 16; m; m >>= 1) v = fmaxf(v, __shfl_xor_sync(~0u, v, m));
    return v;
}
__device__ __forceinline__ float warp_sum(float v) {
#pragma unroll
    for (int m = 16; m; m >>= 1) v += __shfl_xor_sync(~0u, v, m);
    return v;
}
template <bool CLU>
__device__ __forceinline__ unsigned unit_block(int u) {
    const unsigned x = ((unsigned)u & (NUK - 1)) / UPP;
    const int lg = u < NUK ? min(KMAX, max(KMIN, 29 - __clz(x | 1))) : (CLU && (int)x >= 4 * VS0 ? 0 : min(VMAX, max(VMIN, 29 - __clz((127 - x) | 1))));
    const unsigned r = x & ((4u << lg) - 1);
    return ((x - r + (r & ((1u << lg) - 1)) * 4 + (r >> lg)) * UPP) | ((unsigned)u & (UPP - 1));
}
__device__ __forceinline__ const char* block_src(const void* base, unsigned blk) {
    const unsigned po = blk / UPP;
    return reinterpret_cast<const char*>(base) + (size_t)(((po & 3) * NH + (po >> 2)) * UPP + blk % UPP) * TILE_BYTES;
}

template <bool CLU>
__device__ __forceinline__ void a_worker(const Params& p, int un, bool once, bool pre, bool hold, int nstatic, uint32_t slot, uint32_t bar,
                                         uint32_t help, unsigned epoch, uint64_t pol) {
    constexpr int NU = 2 * NUK, NR = CLU ? NREPC : NREP;
    const int lane = threadIdx.x & 31, g = lane >> 2, t = lane & 3;
    const int li = lane & 7;
    uint32_t kaddr[4], vaddr[8];
    {
        const int e = (lane >> 3) & 1, kk = lane >> 4;
#pragma unroll
        for (int s = 0; s < 4; s++) kaddr[s] = slot + (16 * li + e) * 256 + ((2 * s + kk + li) & 7) * 16;
        const int vrow = 4 * (li >> 1) + (li & 1) + 2 * kk;
#pragma unroll
        for (int c = 0; c < 8; c++) vaddr[c] = slot + vrow * 256 + e * 128 + ((c + li) & 7) * 16;
#pragma unroll
        for (int c = 0; c < 8; c++) asm volatile("" : "+r"(vaddr[c]));
    }
    const uint32_t vmask = (g >> 1) != t ? 0u : ((g & 1) ? 0xffff0000u : 0xffffu);
    int kseen = -1;
    unsigned long long H0 = 0, H1 = 0;
    auto header = [&](int v, unsigned vb) {
        if (v >= NU) return;
        const void *a0, *a1;
        if (v < NUK) {
            const unsigned po = vb / UPP;
            a0 = g_qll + (po & 3) * 2048 + (po >> 2) * 64 + lane;
            a1 = reinterpret_cast<const uint2*>(a0) + 32;
        } else {
            const int half = vb / (NUK / 2);
            if (half > kseen) {
                unsigned n = 0;
                while (ld_acquire_cta_shared(help + 12 + 4 * half) == 0) { if (++n > (SPIN_LIMIT << 4)) __trap(); }
                kseen = half;
            }
            a0 = &g_scores[vb * (KEYS / 4) + lane];
            a1 = &g_stats[(vb / UPP) * UPP + lane];
        }
        H0 = ld_relaxed64(a0);
        H1 = ld_relaxed64(a1);
    };
    asm volatile("bar.sync 2, %0;" ::"n"(32 * (NW + XW + 1)) : "memory");
    epoch = __shfl_sync(~0u, epoch, 0);
    if (hold) { unsigned n = 0; while (ld_acquire_cta_shared(help + 24) < 2) { if (++n > (SPIN_LIMIT << 4)) __trap(); } }
    unsigned (*ctl)[32] = g_ctl[epoch & 1];
    const unsigned tag = epoch + 1;
    unsigned nxt = once ? NU : 0;
    int u = -1;
    unsigned bu = 0, bn = unit_block<CLU>(un);
    bool have = false;
    uint32_t phase = 0;
    unsigned kpend = 0;
    const unsigned zero = gridDim.x >> 24;
    uint32_t Q[16];
    float4 oret = make_float4(0.f, 0.f, 0.f, 0.f);
    while (true) {
        const char* nsrc = block_src(un < NUK ? p.kc : p.vc, bn);
        float4* odst = &g_oacc[(bu / UPP) * 32 + lane];
        unsigned* vdst = &g_vdone[(lane & (NR - 1)) * NH + bu / (4 * UPP)][0];
        float d[8][4];
        CLK(c1);
        asm volatile("" : "+l"(odst));
        if (u >= NUK) {
#pragma unroll
            for (int j = 0; j < 8; j++) { d[j][0] = d[j][1] = d[j][2] = d[j][3] = 0.f; }
            mbar_wait(bar, phase);
            LAND(NUK + bu);
            uint32_t a[2][8][4];
#pragma unroll
            for (int c = 0; c < 8; c++) ldsm4t(a[0][c], vaddr[c]);
#pragma unroll
            for (int j = 0; j < 8; j++) {
                if (j < 7) {
#pragma unroll
                    for (int c = 0; c < 8; c++) ldsm4t(a[(j + 1) & 1][c], vaddr[c] + (j + 1) * 4096);
                }
#pragma unroll
                for (int c = 0; c < 8; c++) mma16816(d[c], a[j & 1][c], Q[2 * j], Q[2 * j + 1]);
            }
            float o[4];
#pragma unroll
            for (int r = 0; r < 2; r++) {
                o[2 * r] = d[0][2 * r] + d[7][2 * r + 1];
                o[2 * r + 1] = d[0][2 * r + 1] + d[1][2 * r];
#pragma unroll
                for (int k = 1; k < 4; k++) {
                    const int src = (lane & 28) | ((t - k) & 3);
                    o[2 * r] += __shfl_sync(~0u, d[2 * k][2 * r] + d[2 * k - 1][2 * r + 1], src);
                    o[2 * r + 1] += __shfl_sync(~0u, d[2 * k][2 * r + 1] + d[2 * k + 1][2 * r], src);
                }
            }
            oret = atom_add_f4(odst, o[0], o[1], o[2], o[3]);
        } else if (u >= 0) {
#pragma unroll
            for (int j = 0; j < 8; j++) { d[j][0] = d[j][1] = d[j][2] = d[j][3] = 0.f; }
            mbar_wait(bar, phase);
            LAND(bu);
            uint32_t a[2][8][4];
#pragma unroll
            for (int j = 0; j < 8; j++) ldsm4(a[0][j], kaddr[0] + (4 * (j & 3) + 2 * (j >> 2)) * 256);
#pragma unroll
            for (int s = 0; s < 8; s++) {
                if (s < 7) {
#pragma unroll
                    for (int j = 0; j < 8; j++)
                        ldsm4(a[(s + 1) & 1][j], kaddr[(s + 1) & 3] + (4 * (j & 3) + 2 * (j >> 2)) * 256 + ((s + 1) >> 2) * 128);
                }
#pragma unroll
                for (int j = 0; j < 8; j++)
                    mma16816(d[j], a[s & 1][j], Q[(s & 4) * 2 + ((2 * s - 2 * j) & 7)], Q[(s & 4) * 2 + ((2 * s + 1 - 2 * j) & 7)]);
            }
        }
        if (u >= 0) phase ^= 1;
        CLK(c2b);
        if (un < NU && lane == 0) {
            if (!once) nxt = atom_inc(&ctl[C_QUEUE][0]);
            if (u >= 0 || !pre) {
                mbar_expect_tx(bar, TILE_BYTES);
                bulk_load(slot, nsrc, TILE_BYTES, bar, pol);
            }
        }
        const uint32_t tk = clock();
        CLK(c3);
        if ((unsigned)u < (unsigned)NUK) {
            const int j0 = (t - (g >> 1)) & 3;
            float v[4];
#pragma unroll
            for (int q = 0; q < 4; q++) {
                const int jq = (q >> 1) * 4, e = (q & 1) * 2;
                const float x0 = (g & 1) ? d[jq + 0][e + 1] : d[jq + 0][e];
                const float x1 = (g & 1) ? d[jq + 1][e + 1] : d[jq + 1][e];
                const float x2 = (g & 1) ? d[jq + 2][e + 1] : d[jq + 2][e];
                const float x3 = (g & 1) ? d[jq + 3][e + 1] : d[jq + 3][e];
                const float y0 = (j0 & 1) ? x1 : x0, y1 = (j0 & 1) ? x3 : x2;
                v[q] = (j0 & 2) ? y1 : y0;
            }
            const uint32_t r0 = pack_bf16(v[0], v[1]), r1 = pack_bf16(v[2], v[3]);
            const uint32_t s0 = pack_bf16(bf_lo(r0) * SCALE, bf_hi(r0) * SCALE);
            const uint32_t s1 = pack_bf16(bf_lo(r1) * SCALE, bf_hi(r1) * SCALE);
            g_scores[bu * (KEYS / 4) + 4 * g + j0] = make_uint2(s0, s1);
            const float f0 = bf_lo(s0), f1 = bf_hi(s0), f2 = bf_lo(s1), f3 = bf_hi(s1);
            const float m = warp_max(fmaxf(fmaxf(f0, f1), fmaxf(f2, f3)));
            const float l = warp_sum((expsub(f0, m) + expsub(f1, m)) + (expsub(f2, m) + expsub(f3, m)));
            if (lane == 0) g_stats[bu] = make_float2(m, l);
            kpend++;
            if (un / (NUK / 2) != u / (NUK / 2)) {
                __syncwarp();
                if (lane == 0) {
                    red_release_cta_shared(help + 4 * (u / (NUK / 2)), kpend);
                    if (un >= NUK) red_release_cta_shared(help + 8, 1u);
                }
                kpend = 0;
            }
        }
        CLK(c4);
        int unn = NU;
        if (un < NU) {
            unsigned n = 0;
            while (true) {
                if (!have) header(un, bn);
                if (un >= NUK || __all_sync(~0u, (uint32_t)(H0 >> 32) == tag && (uint32_t)(H1 >> 32) == tag)) break;
                if (++n > SPIN_LIMIT) __trap();
                have = false;
            }
            if (un >= NUK) {
                const uint32_t s0 = (uint32_t)H0, s1 = (uint32_t)(H0 >> 32);
                const float mu = __uint_as_float((uint32_t)H1);
                const float m = warp_max(mu);
                const float l = warp_sum(__uint_as_float((uint32_t)(H1 >> 32)) * expsub(mu, m));
                const float inv = 1.0f / l;
                const uint32_t w0 = pack_bf16(expsub(bf_lo(s0), m) * inv, expsub(bf_hi(s0), m) * inv);
                const uint32_t w1 = pack_bf16(expsub(bf_lo(s1), m) * inv, expsub(bf_hi(s1), m) * inv);
#pragma unroll
                for (int j = 0; j < 8; j++) {
                    Q[2 * j] = __shfl_sync(~0u, w0, 4 * j + t) & vmask;
                    Q[2 * j + 1] = __shfl_sync(~0u, w1, 4 * j + t) & vmask;
                }
            } else {
#pragma unroll
                for (int j = 0; j < 8; j++) {
                    const int src = (((j + g) & 7) << 2) + t;
                    Q[j] = __shfl_sync(~0u, (uint32_t)H0, src);
                    Q[8 + j] = __shfl_sync(~0u, (uint32_t)H1, src);
                }
            }
            unn = nstatic + (int)__shfl_sync(~0u, nxt, 0);
            if (CLU && ((NU - EARLY - unn) & ~(7 << ELOG)) == 0 && lane < MINCL)
                st_relaxed64(&g_dry[lane][(NU - EARLY - unn) >> ELOG],
                             (time_ns() - (((uint32_t)clock() - tk) >> 1) + (NU - unn) * TPU / 16) | (unsigned long long)tag << 32);
        }
        if (u >= NUK && lane < NR)
            red_add_u32(vdst,
                        1u + ((__float_as_uint(oret.x) | __float_as_uint(oret.y) | __float_as_uint(oret.z) | __float_as_uint(oret.w)) & zero));
        if (un >= NU) break;
        bu = bn;
        have = !(un < NUK && unn >= NUK && !(un >= NUK / 2 && unn < NUK + NUK / 2));
        bn = unit_block<CLU>(unn);
        if (have) header(unn, bn);
        u = un;
        un = unn;
    }
}

__device__ __forceinline__ void k_helper(uint32_t help, unsigned epoch) {
    if ((threadIdx.x & 31) != 0) return;
    unsigned (*ctl)[32] = g_ctl[epoch & 1];
    unsigned sent0 = 0, sent1 = 0, n = 0;
    int seen = 0;
    bool fin = false;
    while (!fin || seen < 2) {
        if (!fin) {
            fin = ld_acquire_cta_shared(help + 8) == NW + XW;
            const unsigned c0 = ld_acquire_cta_shared(help), c1 = ld_acquire_cta_shared(help + 4);
            if (c0 != sent0 || c1 != sent1) {
                fence_gpu();
                if (c0 != sent0) red_add_u32(&ctl[C_KDONE][0], c0 - sent0);
                if (c1 != sent1) red_add_u32(&ctl[C_KDONE + 1][0], c1 - sent1);
                sent0 = c0; sent1 = c1;
            }
        }
        if (seen < 2 && ld_acquire(&ctl[C_KDONE + seen][0]) >= NUK / 2) {
            st_release_cta_shared(help + 12 + 4 * seen, 1u);
            seen++;
        } else {
            __nanosleep(300);
        }
        if (++n > SPIN_LIMIT) __trap();
    }
}

__device__ __forceinline__ void v_poller(uint32_t sbase, int f, int w) {
    constexpr int HL = NH;
    const int lane = threadIdx.x & 31;
    const unsigned (*cp)[32] = &g_vdone[((f * NPOLL + w) % NREP) * NH];
    unsigned n = 0;
    while (ld_acquire_cta_shared(sbase + M_HELP + 12) == 0) { __nanosleep(1000); if (++n > SPIN_LIMIT) __trap(); }
    int h = 0;
    bool fast = false;
    while (h < HL) {
        const unsigned r = __ballot_sync(~0u, ld_acquire(&cp[min(h + (lane & 3), HL - 1)][0]) >= 4 * UPP) & 15u;
        if (r & 1) {
            h = min(HL, h + __ffs(~r) - 1);
            __syncwarp();
            if (lane == 0) asm volatile("red.release.cta.shared::cta.max.u32 [%0], %1;" ::"r"(sbase + M_HELP + 20), "r"(h) : "memory");
        }
        if (h < HL - 4) {
            __nanosleep(h ? 300 : 1000);
        } else if (!fast) {
            fast = true;
            const long long t0 = clock64();
            while (clock64() - t0 < w * PGAP) {}
        }
        if (++n > SPIN_LIMIT) __trap();
    }
}
__device__ __forceinline__ void finisher(const Params& p, uint32_t sbase, int f) {
    constexpr int HL = NH;
    const int lane = threadIdx.x & 31;
    {
        const char* wg = reinterpret_cast<const char*>(p.wo);
        const uint32_t dst = sbase + 4 * SLOT + (16 * (lane & 7) + (lane >> 3)) * 16;
#pragma unroll 1
        for (int h = -FPF - 4; h < HL; h++) {
            if (lane == 0 && (unsigned)(h + FPF) < (unsigned)HL) l2_prefetch(wg + (size_t)(h + FPF) * 147456 + f * 2048, 2048);
            if (h >= 0) {
#pragma unroll
                for (int r = 0; r < 4; r++)
                    asm volatile("cp.async.cg.shared.global [%0], [%1], 16;" ::"r"(dst + h * 2048 + ((r & 1) * 4 + (r >> 1) * 8) * 16),
                                 "l"(wg + (size_t)(h * 128 + r * 32 + lane) * (DM * 2) + f * 16) : "memory");
            }
            __nanosleep(FSLEEP);
        }
        asm volatile("cp.async.wait_all;" ::: "memory");
        __syncwarp();
    }
    TS(11);
    const float4* vec = g_oacc + ((lane >> 2) & 3) * 32 + (lane >> 4) * 16 + (lane & 3);
    float acc[2][2][4];
#pragma unroll
    for (int i = 0; i < 16; i++) acc[i >> 3][(i >> 2) & 1][i & 3] = 0.f;
    uint32_t* outp = reinterpret_cast<uint32_t*>(p.out + (lane >> 2) * (2 * DM) + f * 8 + (lane & 3) * 2);
    uint32_t wa = sbase + 4 * SLOT + lane * 16;
    auto project = [&](const float4 (&x)[4], const uint32_t (&w)[4][4]) {
#pragma unroll
        for (int s = 0; s < 4; s++) {
            const uint32_t a[4] = {pack_bf16(x[s].x, x[s].y), 0u, pack_bf16(x[s].z, x[s].w), 0u};
            mma16816(acc[0][s & 1], a, w[s >> 1][(s & 1) * 2], w[s >> 1][(s & 1) * 2 + 1]);
            mma16816(acc[1][s & 1], a, w[2 + (s >> 1)][(s & 1) * 2], w[2 + (s >> 1)][(s & 1) * 2 + 1]);
        }
    };
    int h = 0;
    unsigned n = 0;
    while (h < HL) {
        uint32_t w[4][4];
#pragma unroll
        for (int q = 0; q < 4; q++) ldsm4t(w[q], wa + q * 512);
        int ready;
        while ((ready = ld_acquire_cta_shared(sbase + M_HELP + 20)) <= h) {
            if (h < HL - 3) __nanosleep(100);
            if (++n > (SPIN_LIMIT << 4)) __trap();
        }
        float4 x[4], y[4];
#pragma unroll
        for (int s = 0; s < 4; s++) x[s] = ld_relaxed16(vec + s * 4);
        const bool two = ready > h + 1;
        if (two) {
#pragma unroll
            for (int s = 0; s < 4; s++) y[s] = ld_relaxed16(vec + 128 + s * 4);
        }
        project(x, w);
        if (two) {
#pragma unroll
            for (int q = 0; q < 4; q++) ldsm4t(w[q], wa + 2048 + q * 512);
            project(y, w);
        }
        const int nr = two ? 2 : 1;
        h += nr;
        vec += nr * 128;
        wa += nr * 2048;
        const float o0 = acc[0][0][0] + acc[0][1][0] + __shfl_down_sync(~0u, acc[1][0][0] + acc[1][1][0], 16);
        const float o1 = acc[0][0][1] + acc[0][1][1] + __shfl_down_sync(~0u, acc[1][0][1] + acc[1][1][1], 16);
        asm volatile("{\n.reg .pred p;\nsetp.ne.u32 p, %2, 0;\n@p st.global.u32 [%0], %1;\n}" ::"l"(outp), "r"(pack_bf16(o0, o1)),
                     "r"((uint32_t)(lane < 16 && h == NH)) : "memory");
    }
}

__device__ __noinline__ void f_collect(const unsigned (*flag)[32], unsigned full, const float4* src, unsigned todo, uint32_t sbase) {
    const int lane = threadIdx.x & 31, g = lane >> 2, t = lane & 3;
    const bool last = todo != 15;
    unsigned n = 0;
    while (todo) {
        const unsigned v = ld_acquire(&flag[t][0]);
        unsigned m = __ballot_sync(~0u, v == full) & todo;
        if (m == 0) {
            if (!last || __shfl_sync(~0u, v, 0) == 0) __nanosleep(200);
            if (++n > SPIN_LIMIT) __trap();
            continue;
        }
        __syncwarp();
        todo ^= m;
        if (last) TS(16);
        do {
            const int h0 = __ffs(m) - 1, h1 = 31 - __clz(m);
            m &= ~((1u << h0) | (1u << h1));
            float4 x[8];
#pragma unroll
            for (int b = 0; b < 8; b++) x[b] = ld_relaxed16(src + ((b & 4) ? h1 : h0) * 128 + (b & 3) * 32 + lane);
#pragma unroll
            for (int b = 0; b < 8; b++) {
                const uint32_t lo = pack_bf16(x[b].x, x[b].y), hi = pack_bf16(x[b].z, x[b].w);
                const uint32_t o = __shfl_xor_sync(~0u, (g & 1) ? lo : hi, 4);
                const uint32_t e0 = (g & 1) ? o : lo, e1 = (g & 1) ? hi : o;
                asm volatile("st.shared.v2.u32 [%0], {%1,%2};"
                             ::"r"(sbase + F_BF + ((b & 4) ? h1 : h0) * 1024 + t * 256 + ((b ^ t) & 3) * 64 + g * 8),
                               "r"(__byte_perm(e0, e1, 0x5410)), "r"(__byte_perm(e0, e1, 0x7632)) : "memory");
            }
            __syncwarp();
            if (lane < (h0 == h1 ? 1 : 2))
                asm volatile("mbarrier.arrive.shared::cta.b64 _, [%0];" ::"r"(sbase + F_BAR + 32 + (lane ? h1 : h0) * 8) : "memory");
        } while (m);
    }
    if (last) TS(17);
}

__device__ __forceinline__ void f_project(const CUtensorMap* tm, int panel, int rank, int warp, int sl, int delay, unsigned tag, uint32_t sbase, uint64_t pol) {
    const int j = warp & 3;
    const int lane = threadIdx.x & 31, g = lane >> 2, t = lane & 3;
    const uint32_t wb = sbase + F_W - sl * 2 * SLOT, bars = sbase + F_BAR + 64 + sl * 32;
    const uint32_t wa = wb + ((lane & 7) + (lane >> 4) * 8) * 128 + (((2 * j + ((lane >> 3) & 1)) ^ (lane & 7)) * 16);
    const uint32_t ba = sbase + F_BF + (g & 3) * 64 + t * 16;
    const uint32_t rdst = mapa(sbase + F_RX + sl * 1024 + rank * 128 + g * 16 + (t & 1) * 8, 2 * j + (t >> 1));
    const uint32_t rbar = mapa(sbase + F_BAR + 16 + sl * 8, 2 * j + (t >> 1));
    unsigned n = 0;
    if (warp == 7) {
        if (lane == 0) asm volatile("prefetch.tensormap [%0];" ::"l"(tm) : "memory");
        unsigned long long v;
        while (!__all_sync(~0u, (v = ld_relaxed64(&g_dry[blockIdx.x >> 3][g])) >> 32 == tag)) {
            __nanosleep(200);
            if (++n > SPIN_LIMIT) __trap();
        }
        const uint32_t t0 = __shfl_sync(~0u, (uint32_t)v, 0);
        const uint32_t t1 = t0 + (__reduce_add_sync(~0u, (int)((uint32_t)v - t0)) >> 5);
        if (lane == 0) asm volatile("st.shared.u32 [%0+8], %1;\nmbarrier.arrive.shared::cta.b64 _, [%0];" ::"r"(sbase + F_BAR), "r"(t1) : "memory");
        TS(22);
    }
    mbar_wait(sbase + F_BAR, 0);
    float acc[2][4];
#pragma unroll
    for (int i = 0; i < 8; i++) acc[i >> 2][i & 3] = 0.f;
    const bool up = t & 2;
#pragma unroll 1
    for (int h = 0; h < 4; h++) {
        if (h == max(j - LAG, 0)) {
            const uint32_t due = lds32(sbase + F_BAR + 8) + delay;
            while ((int)(time_ns() - due) < 0 && ++n < SPIN_LIMIT) {}
            asm volatile("{\n.reg .pred p;\nelect.sync _|p, 0xffffffff;\n@p mbarrier.arrive.expect_tx.shared::cta.b64 _, [%2], 16384;\n"
                         "@p cp.async.bulk.tensor.3d.shared::cluster.global.mbarrier::complete_tx::bytes.L2::cache_hint [%0], [%1, {0,%3,%4}], [%2], %5;\n}"
                         ::"r"(wb + j * 16384), "l"(tm), "r"(bars + j * 8), "r"((rank * 4 + j) * 128), "r"(panel), "l"(pol) : "memory");
            TS(18);
        }
        uint32_t wp = wa + h * 16384, last = h == 3;
        mbar_spin(sbase + F_BAR + 32 + h * 8);
        uint32_t a[8][4], bf[4][4];
#pragma unroll
        for (int s = 0; s < 4; s++)
            asm volatile("ld.shared.v4.u32 {%0,%1,%2,%3}, [%4];" : "=r"(bf[s][0]), "=r"(bf[s][1]), "=r"(bf[s][2]), "=r"(bf[s][3])
                         : "r"(((ba + h * 1024) ^ (s * 64)) + s * 256) : "memory");
        asm volatile("" : "+r"(wp), "+r"(last));
        mbar_spin(bars + h * 8);
        if (h == 3) TS(19);
#pragma unroll
        for (int s = 0; s < 8; s++) ldsm4t(a[s], wp + s * 2048);
#pragma unroll
        for (int s = 0; s < 8; s++) mma16816(acc[s & 1], a[s], bf[s & 3][(s >> 2) * 2], bf[s & 3][(s >> 2) * 2 + 1]);
        const float v0 = up ? acc[0][2] + acc[1][2] : acc[0][0] + acc[1][0], v1 = up ? acc[0][3] + acc[1][3] : acc[0][1] + acc[1][1];
        asm volatile("{\n.reg .pred p;\nsetp.ne.u32 p, %4, 0;\n"
                     "@p st.async.weak.shared::cluster.mbarrier::complete_tx::bytes.v2.b32 [%0], {%1,%2}, [%3];\n}"
                     ::"r"(rdst), "r"(__float_as_uint(v0)), "r"(__float_as_uint(v1)), "r"(rbar), "r"(last) : "memory");
    }
    TS(20);
}

__device__ __forceinline__ void f_receive(__nv_bfloat16* out, int sl, bool dry, uint32_t sbase) {
    const int lane = threadIdx.x & 31;
    out += (lane & 3) * (2 * DM) + (lane >> 2);
    uint32_t src = sbase + F_RX + sl * 1024 + lane * 4;
    asm volatile("" : "+l"(out), "+r"(src));
    mbar_spin_cluster(sbase + F_BAR + (dry ? 0 : 16 + sl * 8));
    float v[8];
#pragma unroll
    for (int r = 0; r < 8; r++) asm volatile("ld.shared.f32 %0, [%1];" : "=f"(v[r]) : "r"(src + r * 128) : "memory");
    const float o = ((v[0] + v[1]) + (v[2] + v[3])) + ((v[4] + v[5]) + (v[6] + v[7]));
    asm volatile("{\n.reg .pred p;\nsetp.eq.u32 p, %2, 0;\n@p st.global.u16 [%0], %1;\n}"
                 ::"l"(out), "h"((unsigned short)pack_bf16(o, 0.f)), "r"((uint32_t)dry) : "memory");
    TS(15);
}

constexpr int BS_WUK = 5, BS_Q = 9, BS_CKV = 11, BS_PART = 27, BS_WUV = 29, BS_END = 33;

__device__ __noinline__ void b_issue(const Params& p, int n, int bi, uint32_t sbase, uint64_t pol) {
    if (n >= BS_END || (n >= BS_Q && n < BS_CKV) || (n >= BS_PART && n < BS_WUV)) return;
    const uint32_t bar = sbase + M_BAR + (NSLOT + n % BRING) * 8;
    const CUtensorMap* tm;
    int row, panel = 2 * bi;
    if (n < BS_WUK) { tm = &p.tm_wq; row = n * 128; }
    else if (n < BS_Q) { tm = &p.tm_wuk; row = (n - BS_WUK) * 128; }
    else if (n < BS_PART) {
        tm = &p.tm_ckv; panel = 0;
        row = (bi >> 3) * SK + ((n - BS_CKV) * 8 + (bi & 7)) * 32;
    }
    else { tm = &p.tm_wuv; row = (n - BS_WUV) * 128; }
    mbar_expect_tx(bar, n == 0 ? 32768 + 4 * 1152 : 32768);
    tma3d(sbase + (n % BRING) * SLOT, tm, 0, row, panel, bar, pol);
}
__device__ __forceinline__ void b_issue_xchg(int n, const void* src, uint32_t sbase, uint64_t pol) {
    asm volatile("fence.proxy.async;" ::: "memory");
#pragma unroll
    for (int i = 0; i < 2; i++) {
        const uint32_t bar = sbase + M_BAR + (NSLOT + (n + i) % BRING) * 8;
        mbar_expect_tx(bar, 32768);
        bulk_load(sbase + ((n + i) % BRING) * SLOT, reinterpret_cast<const char*>(src) + i * 32768, 32768, bar, pol);
    }
}
__device__ __forceinline__ void b_wait(int n, uint32_t sbase) {
    mbar_wait(sbase + M_BAR + (NSLOT + n % BRING) * 8, (n / BRING) & 1);
}

__device__ __noinline__ void b_gemm(const Params& p, uint32_t sbase, int n0, int n1, int ktot, uint32_t xh, uint32_t xl, int pitch,
                                    int bi, uint64_t pol) {
    const int tid = threadIdx.x, warp = tid >> 5, lane = tid & 31, g = lane >> 2, t = lane & 3;
    const uint32_t woff = (warp >> 2) * 16384 + (lane & 15) * 128 + ((((warp & 3) * 2 + (lane >> 4)) ^ (lane & 7)) * 16);
    const uint32_t xoff = (g & 3) * pitch + t * 4;
    float acc[2][4];
#pragma unroll
    for (int i = 0; i < 8; i++) acc[i >> 2][i & 3] = 0.f;
#pragma unroll 1
    for (int n = n0; n < n1; n++) {
        b_wait(n, sbase);
        const uint32_t slot = sbase + (n % BRING) * SLOT + woff;
        const int k0 = (n - n0) * 128;
        const int ns = min(8, (ktot - k0) >> 4);
#pragma unroll 2
        for (int s = 0; s < ns; s++) {
            uint32_t a[4], w[4];
            const uint32_t xo = xoff + (k0 + 16 * s) * 2;
            a[0] = lds32(xh + xo); a[2] = lds32(xh + xo + 16);
            a[1] = xl ? lds32(xl + xo) : 0u; a[3] = xl ? lds32(xl + xo + 16) : 0u;
            ldsm4t(w, slot + s * 2048);
            mma16816(acc[0], a, w[0], w[1]);
            mma16816(acc[1], a, w[2], w[3]);
        }
        __syncthreads();
        if (tid == 0) b_issue(p, n + BD, bi, sbase, pol);
    }
    if (g < 4) {
#pragma unroll
        for (int j = 0; j < 2; j++)
            asm volatile("st.shared.u32 [%0], %1;" ::"r"(sbase + M_QB + g * QP + (warp * 16 + j * 8 + t * 2) * 2),
                         "r"(pack_bf16(acc[j][0] + acc[j][2], acc[j][1] + acc[j][3])) : "memory");
    }
    __syncthreads();
}

__device__ __forceinline__ void b_exchange(unsigned* c, int n, const void* src, uint32_t sbase, uint64_t pol) {
    TS(n == BS_Q ? 24 : 28);
    __syncthreads();
    if (threadIdx.x == 0) {
        TS(n == BS_Q ? 25 : 29);
        fence_gpu();
        TS(n == BS_Q ? 26 : 30);
        red_add_u32(c, 1u);
        wait_count(c, NBCTA);
        TS(n == BS_Q ? 27 : 31);
        b_issue_xchg(n, src, sbase, pol);
    }
}

template <bool CLU>
__device__ __noinline__ void b_chain(const Params& p, char* smem, uint32_t sbase, int bi, unsigned epoch, uint64_t pol) {
    const int tid = threadIdx.x, warp = tid >> 5, lane = tid & 31, g = lane >> 2, t = lane & 3;
    unsigned (*ctl)[32] = g_ctl[epoch & 1];
    float* red = reinterpret_cast<float*>(smem + 5 * SLOT);
    __syncthreads();
    b_gemm(p, sbase, 0, BS_WUK, DM, sbase + M_XB, 0, XP, bi, pol);
    TS(6);
    {
        uint32_t Q[16];
#pragma unroll
        for (int c = 0; c < 16; c++) Q[c] = lds32(sbase + M_QB + (g & 3) * QP + c * 16 + t * 4);
        float* qa = reinterpret_cast<float*>(smem + M_QA);
#pragma unroll 1
        for (int n = BS_WUK; n < BS_Q; n++) {
            b_wait(n, sbase);
            const uint32_t base = sbase + (n % BRING) * SLOT + (warp * 16 + (lane & 15)) * 128;
            float d[2][4];
#pragma unroll
            for (int i = 0; i < 8; i++) d[i >> 2][i & 3] = 0.f;
#pragma unroll
            for (int s = 0; s < 8; s++) {
                uint32_t a[4];
                ldsm4(a, base + (s >> 2) * 16384 + (((2 * (s & 3) + (lane >> 4)) ^ (lane & 7)) * 16));
                mma16816(d[s & 1], a, Q[2 * s], Q[2 * s + 1]);
            }
            const int c = (n - BS_WUK) * 128 + warp * 16 + g + 8 * (t >> 1);
            qa[(2 * (t & 1)) * 512 + c] = (t & 2) ? d[0][2] + d[1][2] : d[0][0] + d[1][0];
            qa[(2 * (t & 1) + 1) * 512 + c] = (t & 2) ? d[0][3] + d[1][3] : d[0][1] + d[1][1];
            __syncthreads();
            if (tid == 0) b_issue(p, n + BD, bi, sbase, pol);
        }
#pragma unroll 1
        for (int r = 0; r < 2; r++) {
            const int id = tid + r * 256;
            const int b = id >> 7, c0 = ((id >> 2) & 31) * 16 + (id & 3) * 2;
            const float2 u0 = *reinterpret_cast<const float2*>(qa + b * 512 + c0);
            const float2 u1 = *reinterpret_cast<const float2*>(qa + b * 512 + c0 + 8);
            const uint32_t h0 = pack_bf16(u0.x, u0.y), h1 = pack_bf16(u1.x, u1.y);
            const uint32_t l0 = pack_bf16(u0.x - bf_lo(h0), u0.y - bf_hi(h0)), l1 = pack_bf16(u1.x - bf_lo(h1), u1.y - bf_hi(h1));
            g_qabs[((id >> 2) * 4 + (bi >> 3)) * 32 + (bi & 7) * 4 + (id & 3)] = make_uint4(h0, l0, h1, l1);
        }
    }
    b_exchange(&ctl[C_BBAR][0], BS_Q, &g_qabs[(bi >> 3) * 4096], sbase, pol);
    {
        uint32_t qf[4][4][4];
        b_wait(BS_Q + (warp >> 2), sbase);
        TS(7);
        {
            const uint4* qs = reinterpret_cast<const uint4*>(smem + ((BS_Q + (warp >> 2)) % BRING) * SLOT) + (warp & 3) * 512 + lane;
#pragma unroll
            for (int s = 0; s < 4; s++)
#pragma unroll
                for (int i = 0; i < 4; i++) {
                    const uint4 v = qs[(s * 4 + i) * 32];
                    qf[i][s][0] = v.x; qf[i][s][1] = v.y; qf[i][s][2] = v.z; qf[i][s][3] = v.w;
                }
        }
        __syncthreads();
        if (tid == 0) { b_issue(p, BS_Q + BD, bi, sbase, pol); b_issue(p, BS_Q + 1 + BD, bi, sbase, pol); }
        float acc[2][8][4];
#pragma unroll
        for (int i = 0; i < 2; i++)
#pragma unroll
            for (int j = 0; j < 8; j++) { acc[i][j][0] = acc[i][j][1] = acc[i][j][2] = acc[i][j][3] = 0.f; }
        float mrun = -INFINITY, lrun = 0.f;
        const int head = tid >> 3, kq = tid & 7;
        float* alpha = reinterpret_cast<float*>(smem + M_ALPHA);
        for (int n = BS_CKV; n < BS_PART; n++) {
            b_wait(n, sbase);
            const uint32_t slot = sbase + (n % BRING) * SLOT;
            float sc[4][4][4];
#pragma unroll
            for (int i = 0; i < 4; i++)
#pragma unroll
                for (int j = 0; j < 4; j++) { sc[i][j][0] = sc[i][j][1] = sc[i][j][2] = sc[i][j][3] = 0.f; }
#pragma unroll
            for (int j = 0; j < 4; j++)
#pragma unroll
                for (int sp = 0; sp < 2; sp++) {
                    uint32_t bf[4];
                    ldsm4(bf, slot + warp * 4096 + (8 * j + (lane & 7)) * 128 + (((4 * sp + (lane >> 3)) ^ (lane & 7)) * 16));
#pragma unroll
                    for (int i = 0; i < 4; i++) {
                        mma16816(sc[i][j], qf[i][2 * sp], bf[0], bf[1]);
                        mma16816(sc[i][j], qf[i][2 * sp + 1], bf[2], bf[3]);
                    }
                }
#pragma unroll
            for (int i = 0; i < 4; i++)
#pragma unroll
                for (int j = 0; j < 4; j++)
                    *reinterpret_cast<float2*>(red + warp * 1024 + (8 * i + g) * 32 + ((8 * j) ^ (8 * (g & 3))) + 2 * t) =
                        make_float2(sc[i][j][0] + sc[i][j][2], sc[i][j][1] + sc[i][j][3]);
            __syncthreads();
            if (tid == 0 && n > BS_CKV) b_issue(p, n - 1 + BD, bi, sbase, pol);
            {
                float4 s = make_float4(0.f, 0.f, 0.f, 0.f);
#pragma unroll
                for (int w = 0; w < 8; w++) {
                    const float4 v = *reinterpret_cast<const float4*>(red + w * 1024 + head * 32 + ((4 * kq) ^ (8 * (head & 3))));
                    s.x += v.x; s.y += v.y; s.z += v.z; s.w += v.w;
                }
                const uint32_t r0 = pack_bf16(s.x, s.y), r1 = pack_bf16(s.z, s.w);
                const uint32_t s0 = pack_bf16(bf_lo(r0) * SCALE, bf_hi(r0) * SCALE);
                const uint32_t s1 = pack_bf16(bf_lo(r1) * SCALE, bf_hi(r1) * SCALE);
                const float f0 = bf_lo(s0), f1 = bf_hi(s0), f2 = bf_lo(s1), f3 = bf_hi(s1);
                float mx = fmaxf(fmaxf(f0, f1), fmaxf(f2, f3));
                mx = fmaxf(mx, __shfl_xor_sync(~0u, mx, 1));
                mx = fmaxf(mx, __shfl_xor_sync(~0u, mx, 2));
                mx = fmaxf(mx, __shfl_xor_sync(~0u, mx, 4));
                const float mnew = fmaxf(mrun, mx);
                const float al = expsub(mrun, mnew);
                const float p0 = expsub(f0, mnew), p1 = expsub(f1, mnew), p2 = expsub(f2, mnew), p3 = expsub(f3, mnew);
                lrun = lrun * al + ((p0 + p1) + (p2 + p3));
                mrun = mnew;
                *reinterpret_cast<uint2*>(smem + M_P + head * 80 + kq * 8) = make_uint2(pack_bf16(p0, p1), pack_bf16(p2, p3));
                if (kq == 0) alpha[head] = al;
            }
            __syncthreads();
            {
                uint32_t pf[2][2][4];
#pragma unroll
                for (int i = 0; i < 2; i++)
#pragma unroll
                    for (int ks = 0; ks < 2; ks++)
                        ldsm4(pf[i][ks], sbase + M_P + (16 * i + (lane & 15)) * 80 + (16 * ks + 8 * (lane >> 4)) * 2);
#pragma unroll
                for (int i = 0; i < 2; i++) {
                    const float a0 = alpha[16 * i + g], a1 = alpha[16 * i + 8 + g];
#pragma unroll
                    for (int j = 0; j < 8; j++) { acc[i][j][0] *= a0; acc[i][j][1] *= a0; acc[i][j][2] *= a1; acc[i][j][3] *= a1; }
                }
#pragma unroll
                for (int j = 0; j < 8; j++) {
                    uint32_t bf[4];
                    ldsm4t(bf, slot + warp * 4096 + lane * 128 + ((j ^ (lane & 7)) * 16));
#pragma unroll
                    for (int i = 0; i < 2; i++) {
                        mma16816(acc[i][j], pf[i][0], bf[0], bf[1]);
                        mma16816(acc[i][j], pf[i][1], bf[2], bf[3]);
                    }
                }
            }
        }
        __syncthreads();
        if (tid == 0) b_issue(p, BS_PART - 1 + BD, bi, sbase, pol);
        lrun += __shfl_xor_sync(~0u, lrun, 1);
        lrun += __shfl_xor_sync(~0u, lrun, 2);
        lrun += __shfl_xor_sync(~0u, lrun, 4);
        if (kq == 0) g_bml[head * NBCTA + bi] = make_float2(mrun, lrun);
#pragma unroll
        for (int i = 0; i < 2; i++)
#pragma unroll
            for (int j = 0; j < 8; j++) {
                g_bpart[((16 * i + g) * NBCTA + bi) * 256 + warp * 32 + j * 4 + t] = make_float2(acc[i][j][0], acc[i][j][1]);
                g_bpart[((16 * i + 8 + g) * NBCTA + bi) * 256 + warp * 32 + j * 4 + t] = make_float2(acc[i][j][2], acc[i][j][3]);
            }
    }
    if (!CLU) {
#pragma unroll 1
        for (int i = tid; i < NH * 36; i += 256) g_outb[bi * NH * 36 + i] = make_uint4(0u, epoch, 0u, epoch);
    }
    b_exchange(&ctl[C_BBAR + 1][0], BS_PART, &g_bpart[bi * NBCTA * 256], sbase, pol);
    {
        float* omega = reinterpret_cast<float*>(smem + M_OMEGA);
        if (warp == 0) {
            __syncwarp();
            const uint2 ml = ld_relaxed8(&g_bml[bi * NBCTA + lane]);
            const float ms = __uint_as_float(ml.x);
            float m = ms;
            m = fmaxf(m, __shfl_xor_sync(~0u, m, 1));
            m = fmaxf(m, __shfl_xor_sync(~0u, m, 2));
            m = fmaxf(m, __shfl_xor_sync(~0u, m, 4));
            const float w = expsub(ms, m);
            float l = w * __uint_as_float(ml.y);
            l += __shfl_xor_sync(~0u, l, 1);
            l += __shfl_xor_sync(~0u, l, 2);
            l += __shfl_xor_sync(~0u, l, 4);
            omega[lane] = w / l;
        }
        __syncthreads();
        b_wait(BS_PART, sbase);
        b_wait(BS_PART + 1, sbase);
#pragma unroll 1
        for (int b = 0; b < 4; b++) {
            const float2* ps = reinterpret_cast<const float2*>(smem + ((BS_PART + (b >> 1)) % BRING) * SLOT) + (b & 1) * 2048 + tid;
            float c0 = 0.f, c1 = 0.f;
#pragma unroll
            for (int s = 0; s < 8; s++) {
                const float w = omega[b * 8 + s];
                const float2 v = ps[s * 256];
                c0 = fmaf(w, v.x, c0);
                c1 = fmaf(w, v.y, c1);
            }
            const uint32_t hi = pack_bf16(c0, c1);
            *reinterpret_cast<uint32_t*>(smem + M_CH + b * CP + tid * 4) = hi;
            *reinterpret_cast<uint32_t*>(smem + M_CL + b * CP + tid * 4) = pack_bf16(c0 - bf_lo(hi), c1 - bf_hi(hi));
        }
        __syncthreads();
        if (tid == 0) { b_issue(p, BS_PART + BD, bi, sbase, pol); b_issue(p, BS_PART + 1 + BD, bi, sbase, pol); }
    }
    b_gemm(p, sbase, BS_WUV, BS_END, 512, sbase + M_CH, sbase + M_CL, CP, bi, pol);
    TS(12);
    if (CLU) {
        if (warp < 4) {
            const unsigned short* c = reinterpret_cast<const unsigned short*>(smem + M_QB + warp * QP) + 16 * t + g;
            g_octx[(bi * 4 + warp) * 32 + lane] = make_float4(bf_lo(c[0]), bf_lo(c[8]), bf_lo(c[64]), bf_lo(c[72]));
        }
        __syncthreads();
        if (tid == 0) asm volatile("st.release.gpu.global.u32 [%0], %1;" ::"l"(&g_cdone[bi][0]), "r"(epoch + 1) : "memory");
        return;
    }
    if (tid == 0) {
#pragma unroll 1
        for (int i = 0; i < 4; i++) {
            mbar_expect_tx(sbase + M_BAR + i * 8, 36864);
            tma3d(sbase + i * 36864, &p.tm_wo, 0, bi * 128 + i * 32, 0, sbase + M_BAR + i * 8, pol);
        }
    }
    TS(8);
    {
        float acc[9][4];
#pragma unroll
        for (int j = 0; j < 9; j++) { acc[j][0] = acc[j][1] = acc[j][2] = acc[j][3] = 0.f; }
#pragma unroll 1
        for (int i = 0; i < 4; i++) {
            const uint32_t xo = sbase + M_QB + (g & 3) * QP + i * 64 + t * 4;
            const uint32_t a0[4] = {lds32(xo), 0u, lds32(xo + 16), 0u}, a1[4] = {lds32(xo + 32), 0u, lds32(xo + 48), 0u};
            mbar_wait(sbase + M_BAR + i * 8, 0);
#pragma unroll
            for (int j = 0; j < 9; j++) {
                const int nt = warp * 9 + j;
                uint32_t w[4];
                ldsm4t(w, sbase + i * 36864 + (nt >> 3) * 4096 + lane * 128 + (((nt & 7) ^ (lane & 7)) * 16));
                mma16816(acc[j], a0, w[0], w[1]);
                mma16816(acc[j], a1, w[2], w[3]);
            }
        }
        if (g < 4) {
#pragma unroll
            for (int j = 0; j < 9; j++) {
                const int c2 = (warp * 9 + j) * 4 + t;
                st_tagged2(&g_outb[((c2 / 9) * NH + bi) * 36 + g * 9 + c2 % 9], acc[j][0], acc[j][1], epoch + 1);
            }
        }
    }
    TS(9);
    {
        const uint4* src = g_outb + (bi * NH + (tid >> 3)) * 36 + (tid & 7);
        float2* part = reinterpret_cast<float2*>(red);
        unsigned n = 0;
        while (true) {
            ulonglong2 v[5];
            bool ok = true;
#pragma unroll
            for (int i = 0; i < 5; i++)
                if (i < 4 || (tid & 7) < 4) v[i] = ld_tagged2(src + i * 8);
#pragma unroll
            for (int i = 0; i < 5; i++)
                if (i < 4 || (tid & 7) < 4) {
                    ok = ok && (unsigned)(v[i].x >> 32) == epoch + 1 && (unsigned)(v[i].y >> 32) == epoch + 1;
                    part[(tid >> 3) * 36 + (tid & 7) + i * 8] = make_float2(__uint_as_float((unsigned)v[i].x), __uint_as_float((unsigned)v[i].y));
                }
            if (ok) break;
            __nanosleep(400);
            if (++n > SPIN_LIMIT) __trap();
        }
        __syncthreads();
        if (tid < 36) {
            float s0 = 0.f, s1 = 0.f;
#pragma unroll 8
            for (int h = 0; h < NH; h++) { const float2 v = part[h * 36 + tid]; s0 += v.x; s1 += v.y; }
            *reinterpret_cast<uint32_t*>(p.out + (tid / 9) * 2 * DM + DM + bi * 18 + (tid % 9) * 2) = pack_bf16(s0, s1);
        }
    }
    TS(10);
}

template <bool CLU>
__global__ void __launch_bounds__(256, 1) fused_decode_kernel(const __grid_constant__ Params p) {
    asm volatile("{\n.reg .pred p;\n.reg .u32 a;\n.reg .u64 b;\nsub.u32 a, %1, %4;\nsetp.lt.u32 p, a, %3;\nmad.lo.u32 a, %2, %6, %1;\n"
                 "mad.wide.u32 b, a, %5, %0;\n"
                 "@p prefetch.global.L2 [b];\n}"
                 ::"l"(p.pf), "r"(threadIdx.x), "r"(blockIdx.x), "n"(PFN), "n"(PF0), "n"(PFS), "n"(PFC) : "memory");
    extern __shared__ __align__(1024) char smem_raw[];
    const uint32_t sbase = (smem_u32(smem_raw) + 1023u) & ~1023u;
    if (CLU && threadIdx.x < 32 && blockIdx.x >= NBCTA) {
        const unsigned u0 = blockIdx.x - NBCTA, u1 = u0 + 8 * MINCL - NBCTA;
        asm volatile("{\n.reg .pred p;\nelect.sync _|p, 0xffffffff;\n"
                     "@p mbarrier.init.shared::cta.b64 [%0], 1;\n"
                     "@p mbarrier.init.shared::cta.b64 [%0+8], 1;\n"
                     "@p fence.mbarrier_init.release.cluster;\n"
                     "@p mbarrier.arrive.expect_tx.shared::cta.b64 _, [%0], 32768;\n"
                     "@p cp.async.bulk.shared::cluster.global.mbarrier::complete_tx::bytes.L2::cache_hint [%1], [%2], 32768, [%0], %4;\n"
                     "@p mbarrier.arrive.expect_tx.shared::cta.b64 _, [%0+8], 32768;\n"
                     "@p cp.async.bulk.shared::cluster.global.mbarrier::complete_tx::bytes.L2::cache_hint [%1+32768], [%3], 32768, [%0+8], %4;\n}"
                     ::"r"(sbase + M_BAR), "r"(sbase), "l"(reinterpret_cast<const char*>(p.kc) + (size_t)u0 * TILE_BYTES),
                       "l"(reinterpret_cast<const char*>(p.kc) + (size_t)((u1 >> 7) * 1024 + (u1 & 127)) * TILE_BYTES), "l"(0x12F0000000000000ull) : "memory");
    }
    char* smem = smem_raw + (sbase - smem_u32(smem_raw));
    const int tid = threadIdx.x, warp = __shfl_sync(~0u, tid >> 5, 0), lane = tid & 31;
    const int blk = blockIdx.x;
    const bool isB = CLU ? blk < NBCTA : (blk & 3) == 0 && (blk >> 2) < NBCTA;
    const int bi = CLU ? blk : blk >> 2;
    const int nb = CLU ? blk - NBCTA : blk - min(NBCTA, (blk + 3) >> 2);
    const int nblk = CLU ? 8 * MINCL : gridDim.x, nnb = nblk - NBCTA;
    const int nstatic = nnb * (NW + XW);
    uint64_t pol;
    asm volatile("createpolicy.fractional.L2::evict_first.b64 %0, 1.0;" : "=l"(pol));
    const uint32_t wbar = sbase + M_BAR + warp * 8, wslot = sbase + warp * SLOT;
    const int u0 = warp * nnb + nb;
    const bool hold = ((blk >> 2) >> KMIN << KMIN) * 4 * UPP < nstatic;
    const uint32_t jbar = sbase + M_BAR + (NSLOT + BRING) * 8;
    if (warp == 7) {
        if (lane == 0 && blk < 128) {
            mbar_init(jbar, 1);
            asm volatile("fence.mbarrier_init.release.cluster;" ::: "memory");
            uint64_t poln;
            asm volatile("createpolicy.fractional.L2::evict_normal.b64 %0, 1.0;" : "=l"(poln));
            mbar_expect_tx(jbar, 36864 + 4 * 1152);
            tma3d(sbase + J0W, &p.tm_j0, blk * 32, 0, 0, jbar, poln);
            bulk_load(sbase + M_XA, p.xa, 4608, jbar, poln);
        }
        if (lane < 8) reinterpret_cast<unsigned*>(smem + M_HELP)[lane] = 0;
        __syncwarp();
        if (!isB) asm volatile("bar.arrive 2, %0;" ::"n"(32 * (NW + XW + 1)) : "memory");
    }
    if (warp < 4 && lane == 0 && (!CLU || isB || warp >= 2)) {
        mbar_init(wbar, 1);

        asm volatile("fence.mbarrier_init.release.cluster;" ::: "memory");
        if (warp < NEARLY && !isB && !hold) {
            mbar_expect_tx(wbar, TILE_BYTES);
            bulk_load(wslot, block_src(p.kc, unit_block<CLU>(u0)), TILE_BYTES, wbar, pol);
        }
    }
    unsigned epoch = 0;
    if (lane == 0) epoch = ld_relaxed4(&g_epoch);
    TS(0);
    if (CLU) {
        if (warp == 6) {
            if (lane < 16 && lane != 1) mbar_init(sbase + F_BAR + lane * 8, 1);
            if ((lane >> 1) == 1) mbar_expect_tx(sbase + F_BAR + lane * 8, 1024);
            asm volatile("fence.mbarrier_init.release.cluster;" ::: "memory");
        }
        asm volatile("barrier.cluster.arrive.relaxed.aligned;" ::: "memory");
    }
    if ((warp >> 1) == 2 && blk < 128) st_relaxed64(&g_qll[((tid - 128) >> 4) * 2048 + blk * 16 + (tid & 15)], 0ull);
    if (isB || warp >= NW + XW) epoch = __shfl_sync(~0u, epoch, 0);
    if (isB && warp == 3) asm volatile("bar.sync 1, 160;" ::: "memory");
    if (isB && tid == 96) {
#pragma unroll 1
        for (int i = 0; i < BRING; i++) mbar_init(sbase + M_BAR + (NSLOT + i) * 8, 1);
        asm volatile("fence.mbarrier_init.release.cluster;" ::: "memory");
        if (hold) { unsigned n = 0; while (ld_acquire_cta_shared(sbase + M_HELP + 24) < 2) { if (++n > (SPIN_LIMIT << 4)) __trap(); } }
#pragma unroll 1
        for (int b = 0; b < 4; b++) bulk_load(sbase + M_XB + b * XP, p.xb + b * DM, 1152, sbase + M_BAR + NSLOT * 8, pol);
#pragma unroll 1
        for (int n = 0; n < BD; n++) b_issue(p, n, bi, sbase, pol);
    }
    if (warp >= 4 && blk < 128) {
        const int g = lane >> 2, t = lane & 3, j = tid - 128;
        asm volatile("bar.sync 1, %0;" ::"r"(isB ? 160 : 128) : "memory");
#pragma unroll 1
        for (int sl = blk, ph = 0;; sl += 128 - nblk, ph = 1) {
        mbar_wait(jbar, ph);
        TS(13);
        float acc[4][4];
#pragma unroll
        for (int i = 0; i < 16; i++) acc[i >> 2][i & 3] = 0.f;
        const uint32_t wa = sbase + J0W + ((warp - 4) * 144 + (lane & 15)) * 64;
        const uint32_t sw = (lane >> 1) & 3, xa = sbase + M_XA + (g & 3) * 1152 + (warp - 4) * 288 + t * 4;
#pragma unroll 3
        for (int s = 0; s < 9; s++) {
            const uint32_t a[4] = {lds32(xa + s * 32), 0u, lds32(xa + s * 32 + 16), 0u};
            uint32_t w0[4], w1[4];
            ldsm4t(w0, wa + s * 1024 + (((lane >> 4) ^ sw) * 16));
            ldsm4t(w1, wa + s * 1024 + (((2 + (lane >> 4)) ^ sw) * 16));
            mma16816(acc[0], a, w0[0], w0[1]);
            mma16816(acc[1], a, w0[2], w0[3]);
            mma16816(acc[2], a, w1[0], w1[1]);
            mma16816(acc[3], a, w1[2], w1[3]);
        }
        float2* j0 = reinterpret_cast<float2*>(smem + M_J0);
        if (g < 4) {
#pragma unroll
            for (int i = 0; i < 4; i++) j0[(warp - 4) * 64 + g * 16 + i * 4 + t] = make_float2(acc[i][0], acc[i][1]);
        }
        asm volatile("bar.sync 1, 128;" ::: "memory");
        const bool again = sl == blk && blk + 128 - nblk >= nblk;
        if (again && tid == 224) {
            mbar_expect_tx(jbar, 36864);
            tma3d(sbase + J0W, &p.tm_j0, (blk + 128 - nblk) * 32, 0, 0, jbar, pol);
        }
        if (warp < 6) {
            const float2 v0 = j0[j], v1 = j0[64 + j], v2 = j0[128 + j], v3 = j0[192 + j];
            st_relaxed64(&g_qll[(j >> 4) * 2048 + sl * 16 + (j & 15)],
                         (unsigned long long)pack_bf16((v0.x + v1.x) + (v2.x + v3.x), (v0.y + v1.y) + (v2.y + v3.y)) |
                             ((unsigned long long)(epoch + 1) << 32));
            __syncwarp();
            if (lane == 0) asm volatile("red.relaxed.cta.shared::cta.add.u32 [%0], 1;" ::"r"(sbase + M_HELP + 24) : "memory");
        } else if (warp == 7) {
            if (blk < C_LINES) g_ctl[(epoch & 1) ^ 1][blk][lane] = 0;
        }
        TS(1);
        if (!again) break;
        asm volatile("bar.sync 1, 128;" ::: "memory");
        }
    }
    const int cl = blk >> 3, rank = blk & 7;
    const bool partA = CLU && cl >= 4 && cl < 13;
    if (isB) {
        b_chain<CLU>(p, smem, sbase, bi, epoch, pol);
        if (!CLU) return;
    } else if (warp < NW + XW) {
        a_worker<CLU>(p, u0, warp >= NW + ((nb & 3) < (CLU ? X3C : X3) ? 1 : 0), warp < NEARLY && !hold, hold, nstatic, wslot, wbar, sbase + M_HELP,
                      epoch, pol);
        if (!CLU || warp < (partA && rank == 7 ? 2 : 3)) return;
        epoch = __shfl_sync(~0u, epoch, 0);
        unsigned n = 0;
        while (ld_acquire_cta_shared(sbase + M_HELP + 12) == 0) { __nanosleep(1000); if (++n > SPIN_LIMIT) __trap(); }
    } else if (warp == 7) {
#pragma unroll 1
        for (int i = nb; i < 4 * NH; i += nnb) g_oacc[i * 32 + lane] = make_float4(0.f, 0.f, 0.f, 0.f);
        if (nb < NREP * NH) g_vdone[nb][lane] = 0;
        __syncwarp();
        k_helper(sbase + M_HELP, epoch);
        if (nb == 0 && lane == 0) g_epoch = epoch + 1;
        __syncwarp();
    } else if (!CLU && nb < NFIN) {
        if (warp == 6) {
            finisher(p, sbase, nb);
            TS(4);
        } else if (warp >= 6 - NPOLL) {
            v_poller(sbase, nb, warp - (6 - NPOLL));
        }
    }
    if (!CLU || cl > 13) return;
    asm volatile("barrier.cluster.wait.acquire.aligned;" ::: "memory");
    if (isB ? warp == 0 : warp < 4) {
        f_collect((partA ? g_vdone : g_cdone) + 4 * rank, partA ? 4 * UPP : epoch + 1, (partA ? g_oacc : g_octx) + 4 * rank * 128,
                  partA && rank == 7 ? (warp == 2 ? CM2 : 15 - CM2) : 15, sbase);
        if (warp == 2) return;
    }
    const int sl = isB ? warp >> 2 : 0, panel = isB ? 2 * cl + sl : min(cl - 4, 8);
#pragma unroll 1
    for (int i = 0;; i++) {
        if (isB ? (warp & 3) == 0 : warp == 3) f_receive(p.out + (partA ? 0 : DM) + panel * 64 + rank * 8, sl, i == 0, sbase);
        if (i) return;
        if (isB || warp >= 4)
            f_project(partA ? &p.tm_fa : &p.tm_fb, panel, rank, warp, sl,
                      isB ? B0 + (warp & 3) * BJ + sl * BS + rank * BR : A0 + (warp & 3) * AJ + rank * AR, epoch + 1, sbase, pol);
    }
}

}

typedef CUresult (*EncodeFn)(CUtensorMap*, CUtensorMapDataType, cuuint32_t, void*, const cuuint64_t*, const cuuint64_t*,
                             const cuuint32_t*, const cuuint32_t*, CUtensorMapInterleave, CUtensorMapSwizzle,
                             CUtensorMapL2promotion, CUtensorMapFloatOOBfill);

extern "C" void kernel_launch(void* const* d_in, const int* in_sizes, int n_in, void* d_out, int out_size) {
    (void)in_sizes; (void)n_in; (void)out_size;
    static int nsm = 0, ncl = 0;
    static EncodeFn encode = nullptr;
    cudaLaunchConfig_t cfg = {};
    cudaLaunchAttribute at[1];
    at[0].id = cudaLaunchAttributeClusterDimension;
    at[0].val.clusterDim.x = 8; at[0].val.clusterDim.y = 1; at[0].val.clusterDim.z = 1;
    cfg.blockDim = dim3(256); cfg.dynamicSmemBytes = SMEM_BYTES; cfg.stream = cudaStreamPerThread; cfg.attrs = at; cfg.numAttrs = 1;
    if (nsm == 0) {
        int dev = 0;
        cudaGetDevice(&dev);
        cudaDeviceGetAttribute(&nsm, cudaDevAttrMultiProcessorCount, dev);
        cudaFuncSetAttribute(fused_decode_kernel<false>, cudaFuncAttributeMaxDynamicSharedMemorySize, SMEM_BYTES);
        cudaFuncSetAttribute(fused_decode_kernel<true>, cudaFuncAttributeMaxDynamicSharedMemorySize, SMEM_BYTES);
        cfg.gridDim = dim3(128);
        if (cudaOccupancyMaxActiveClusters(&ncl, fused_decode_kernel<true>, &cfg) != cudaSuccess) { ncl = 0; (void)cudaGetLastError(); }
        if (ncl > MINCL) ncl = MINCL;
        void* fn = nullptr;
        cudaDriverEntryPointQueryResult qr;
        cudaGetDriverEntryPoint("cuTensorMapEncodeTiled", &fn, cudaEnableDefault, &qr);
        encode = (EncodeFn)fn;
    }
    Params p;
    auto panels = [&](CUtensorMap* tm, void* ptr, int rows, int cols, int box_rows, int box_panels,
                      CUtensorMapL2promotion promo = CU_TENSOR_MAP_L2_PROMOTION_L2_256B) {
        const cuuint64_t gd[3] = {64, (cuuint64_t)rows, (cuuint64_t)(cols / 64)}, gs[2] = {(cuuint64_t)cols * 2, 128};
        const cuuint32_t box[3] = {64, (cuuint32_t)box_rows, (cuuint32_t)box_panels}, es[3] = {1, 1, 1};
        encode(tm, CU_TENSOR_MAP_DATA_TYPE_BFLOAT16, 3, ptr, gd, gs, box, es, CU_TENSOR_MAP_INTERLEAVE_NONE,
               CU_TENSOR_MAP_SWIZZLE_128B, promo, CU_TENSOR_MAP_FLOAT_OOB_FILL_NONE);
    };
    panels(&p.tm_wq, d_in[7], DM, 4096, 128, 2);
    panels(&p.tm_wuk, d_in[8], 512, 4096, 128, 2);
    panels(&p.tm_wuv, d_in[9], 512, 4096, 128, 2);
    panels(&p.tm_wo, d_in[10], 4096, DM, 32, 9);
    panels(&p.tm_ckv, d_in[6], 4 * SK, 512, 32, 8);
    panels(&p.tm_fa, d_in[4], 4096, DM, 128, 1, CU_TENSOR_MAP_L2_PROMOTION_L2_128B);
    panels(&p.tm_fb, d_in[10], 4096, DM, 128, 1, CU_TENSOR_MAP_L2_PROMOTION_L2_128B);
    {
        const cuuint64_t gd[3] = {4096, 192, 3}, gs[2] = {8192, 192 * 8192};
        const cuuint32_t box[3] = {32, 192, 3}, es[3] = {1, 1, 1};
        encode(&p.tm_j0, CU_TENSOR_MAP_DATA_TYPE_BFLOAT16, 3, d_in[3], gd, gs, box, es, CU_TENSOR_MAP_INTERLEAVE_NONE,
               CU_TENSOR_MAP_SWIZZLE_64B, CU_TENSOR_MAP_L2_PROMOTION_L2_128B, CU_TENSOR_MAP_FLOAT_OOB_FILL_NONE);
    }
    p.xa = (const __nv_bfloat16*)d_in[0];
    p.kc = (const __nv_bfloat16*)d_in[1];
    p.vc = (const __nv_bfloat16*)d_in[2];
    p.pf = (const char*)d_in[1] + (size_t)PFOFF * TILE_BYTES - PF0 * PFS;
    p.wo = (const __nv_bfloat16*)d_in[4];
    p.xb = (const __nv_bfloat16*)d_in[5];
    p.out = (__nv_bfloat16*)d_out;
    if (ncl >= MINCL) {
        cfg.gridDim = dim3(8 * ncl);
        cudaLaunchKernelEx(&cfg, fused_decode_kernel<true>, p);
    } else {
        fused_decode_kernel<false><<<nsm, 256, SMEM_BYTES, cudaStreamPerThread>>>(p);
    }
}
```

```cpp
#include <cuda_runtime.h>
#include <cuda.h>
#include <cuda_bf16.h>
#include <stdint.h>

namespace {

constexpr int NH = 32, SK = 4096, DM = 576;
constexpr int KEYS = 128;
constexpr int UPP = SK / KEYS;
constexpr int NUK = 4 * NH * UPP;
constexpr int TILE_BYTES = KEYS * 256;
#define NWORK 2
constexpr int NW = NWORK;
constexpr int NBCTA = 32;
constexpr int MINCL = 15;
constexpr int NFIN = 72;
constexpr int SLOT = 32768;
constexpr int NSLOT = 6;
constexpr int BRING = 5;
constexpr int J0W = 5 * SLOT;
constexpr int MISC = NSLOT * SLOT + 4096;
constexpr int XP = 1168, CP = 1040, QP = 272;
constexpr int M_XA = MISC;
constexpr int M_XB = M_XA + 4 * XP;
constexpr int M_CH = M_XB + 4 * XP;
constexpr int M_CL = M_CH + 4 * CP;
constexpr int M_QB = M_CL + 4 * CP;
constexpr int M_QA = M_CH;
constexpr int M_J0 = M_QB + 4 * QP;
constexpr int M_P = M_J0 + 2048;
constexpr int M_ALPHA = M_P + 2560;
constexpr int M_OMEGA = M_ALPHA + 128;
constexpr int M_BAR = M_OMEGA + 128;
constexpr int M_HELP = M_BAR + 128;
constexpr int F_W = 4 * SLOT;
constexpr int F_BF = (M_HELP + 128 + 255) / 256 * 256;
constexpr int F_RX = F_BF + 4096;
constexpr int F_BAR = F_RX + 2048;
constexpr int SMEM_BYTES = F_BAR + 128 + 1024;
static_assert(SMEM_BYTES <= 232448 && M_BAR % 8 == 0 && M_QA % 16 == 0 && M_P % 16 == 0, "smem layout");
#define XW 2
#define X3 1
#define X3C 7
#define NEARLY 3
#define BD 5
#define FPF 3
#define FSLEEP 800
#define VS0 24
#define EARLY 100
#define ELOG 5
#define TPU 159
#define A0 (1950 + 185 * X3C)
#define AJ 700
#define AR (AJ / 8)
#define LAG 2
#define PF0 128
#define PFS 128
#define PFN 96
#define CM2 10
#define B0 (1450 + 185 * X3C)
#define BJ 700
#define BS 300
#define BR (BJ / 8)
#define NPOLL 2
#define PGAP 200
static_assert(X3C <= 7 && NW == 2, "warp 2 of rank 7 is free");
static_assert(NW + XW <= 4 && NEARLY <= NW + XW && BD <= BRING, "slots 4 and 5 hold the finisher weights");
#define KMAX 4
#define VMAX 4
constexpr int KMIN = 2, VMIN = 0;
constexpr float SCALE = 0.08838834764831845f;
constexpr float LOG2E = 1.4426950408889634f;
constexpr unsigned SPIN_LIMIT = 1u << 24;

#define NREP 2
#define NREPC 1
constexpr int C_QUEUE = 0, C_KDONE = 1, C_BBAR = 3, C_LINES = 5;

struct Params {
    const __nv_bfloat16 *kc, *xa, *vc, *wo, *xb;
    __nv_bfloat16* out;
    CUtensorMap tm_j0;
    CUtensorMap tm_wq, tm_wuk, tm_ckv, tm_wuv, tm_wo;
    CUtensorMap tm_fa, tm_fb;
};

__device__ unsigned g_epoch;
__device__ unsigned g_ctl[2][C_LINES][32];
__device__ uint2 g_qll[4 * 2048];
__device__ uint2 g_scores[128 * SK / 4];
__device__ float2 g_stats[128 * UPP];
__device__ float4 g_oacc[128 * 32];
__device__ unsigned g_vdone[NREP * NH][32];
__device__ float4 g_octx[128 * 32];
__device__ unsigned g_cdone[NH][32];
__device__ unsigned long long g_dry[16][16];
__device__ uint4 g_qabs[4 * 8 * 4 * 4 * 32];
__device__ float2 g_bpart[NBCTA * NH * 256];
__device__ float2 g_bml[NBCTA * NH];
__device__ uint4 g_outb[NBCTA * NH * 36];

#define TS(i)
#define TSV(i, v)
#define LAND(i)
#define CLK(x)
#define ACC(a, x, y)

__device__ __forceinline__ uint32_t smem_u32(const void* p) { return (uint32_t)__cvta_generic_to_shared(p); }
__device__ __forceinline__ void mbar_init(uint32_t bar, uint32_t cnt) {
    asm volatile("mbarrier.init.shared::cta.b64 [%0], %1;" ::"r"(bar), "r"(cnt) : "memory");
}
__device__ __forceinline__ void mbar_expect_tx(uint32_t bar, uint32_t bytes) {
    asm volatile("mbarrier.arrive.expect_tx.shared::cta.b64 _, [%0], %1;" ::"r"(bar), "r"(bytes) : "memory");
}
__device__ __forceinline__ bool mbar_try(uint32_t bar, uint32_t parity) {
    uint32_t ok;
    asm volatile("{\n.reg .pred p;\nmbarrier.try_wait.parity.shared::cta.b64 p, [%1], %2;\nselp.u32 %0, 1, 0, p;\n}\n"
                 : "=r"(ok) : "r"(bar), "r"(parity) : "memory");
    return ok;
}
__device__ __forceinline__ void mbar_wait(uint32_t bar, uint32_t parity) {
    unsigned n = 0;
    while (!mbar_try(bar, parity)) { if (++n > SPIN_LIMIT) __trap(); }
}
__device__ __forceinline__ void mbar_spin(uint32_t bar) {
    asm volatile("{\n.reg .pred p;\n.reg .u32 n;\nmov.u32 n, 0;\nSPIN:\nmbarrier.try_wait.parity.shared::cta.b64 p, [%0], 0;\n@p bra.uni DONE;\n"
                 "add.u32 n, n, 1;\nsetp.lt.u32 p, n, 0x1000000;\n@p bra.uni SPIN;\ntrap;\nDONE:\n}" ::"r"(bar) : "memory");
}
__device__ __forceinline__ void mbar_spin_cluster(uint32_t bar) {
    asm volatile("{\n.reg .pred p;\n.reg .u32 n;\nmov.u32 n, 0;\nSPIN:\nmbarrier.try_wait.parity.relaxed.cluster.shared::cta.b64 p, [%0], 0;\n"
                 "@p bra.uni DONE;\nadd.u32 n, n, 1;\nsetp.lt.u32 p, n, 0x1000000;\n@p bra.uni SPIN;\ntrap;\nDONE:\n"
                 "fence.acquire.sync_restrict::shared::cluster.cluster;\n}" ::"r"(bar) : "memory");
}
__device__ __forceinline__ void bulk_load(uint32_t dst, const void* src, uint32_t bytes, uint32_t bar, uint64_t pol) {
    asm volatile("cp.async.bulk.shared::cluster.global.mbarrier::complete_tx::bytes.L2::cache_hint [%0], [%1], %2, [%3], %4;"
                 ::"r"(dst), "l"(src), "r"(bytes), "r"(bar), "l"(pol) : "memory");
}
__device__ __forceinline__ void mbar_init_warp(uint32_t bar) {
    asm volatile("{\n.reg .pred p;\nelect.sync _|p, 0xffffffff;\n@p mbarrier.init.shared::cta.b64 [%0], 1;\n@p fence.mbarrier_init.release.cluster;\n}"
                 ::"r"(bar) : "memory");
}
__device__ __forceinline__ void tile_load_warp(uint32_t dst, const void* src, uint32_t bar, uint64_t pol) {
    asm volatile("{\n.reg .pred p;\nelect.sync _|p, 0xffffffff;\n@p mbarrier.arrive.expect_tx.shared::cta.b64 _, [%2], %4;\n"
                 "@p cp.async.bulk.shared::cluster.global.mbarrier::complete_tx::bytes.L2::cache_hint [%0], [%1], %4, [%2], %3;\n}"
                 ::"r"(dst), "l"(src), "r"(bar), "l"(pol), "n"(TILE_BYTES) : "memory");
}
__device__ __forceinline__ void tma3d_warp(uint32_t dst, const CUtensorMap* tm, int c0, int c1, int c2, uint32_t bar, uint32_t bytes, uint64_t pol) {
    asm volatile("{\n.reg .pred p;\nelect.sync _|p, 0xffffffff;\n@p mbarrier.arrive.expect_tx.shared::cta.b64 _, [%2], %7;\n"
                 "@p cp.async.bulk.tensor.3d.shared::cluster.global.mbarrier::complete_tx::bytes.L2::cache_hint [%0], [%1, {%3,%4,%5}], [%2], %6;\n}"
                 ::"r"(dst), "l"(tm), "r"(bar), "r"(c0), "r"(c1), "r"(c2), "l"(pol), "r"(bytes) : "memory");
}
__device__ __forceinline__ void tma3d(uint32_t dst, const CUtensorMap* tm, int c0, int c1, int c2, uint32_t bar, uint64_t pol) {
    asm volatile("cp.async.bulk.tensor.3d.shared::cluster.global.mbarrier::complete_tx::bytes.L2::cache_hint [%0], [%1, {%3,%4,%5}], [%2], %6;"
                 ::"r"(dst), "l"(tm), "r"(bar), "r"(c0), "r"(c1), "r"(c2), "l"(pol) : "memory");
}
__device__ __forceinline__ void l2_prefetch(const void* src, uint32_t bytes) {
    asm volatile("cp.async.bulk.prefetch.L2.global [%0], %1;" ::"l"(src), "r"(bytes) : "memory");
}
__device__ __forceinline__ void ldsm4(uint32_t (&r)[4], uint32_t addr) {
    asm volatile("ldmatrix.sync.aligned.m8n8.x4.shared.b16 {%0,%1,%2,%3}, [%4];"
                 : "=r"(r[0]), "=r"(r[1]), "=r"(r[2]), "=r"(r[3]) : "r"(addr));
}
__device__ __forceinline__ void ldsm4t(uint32_t (&r)[4], uint32_t addr) {
    asm volatile("ldmatrix.sync.aligned.m8n8.x4.trans.shared.b16 {%0,%1,%2,%3}, [%4];"
                 : "=r"(r[0]), "=r"(r[1]), "=r"(r[2]), "=r"(r[3]) : "r"(addr));
}
__device__ __forceinline__ void mma16816(float (&d)[4], const uint32_t (&a)[4], uint32_t b0, uint32_t b1) {
    asm("mma.sync.aligned.m16n8k16.row.col.f32.bf16.bf16.f32 {%0,%1,%2,%3}, {%4,%5,%6,%7}, {%8,%9}, {%0,%1,%2,%3};"
        : "+f"(d[0]), "+f"(d[1]), "+f"(d[2]), "+f"(d[3])
        : "r"(a[0]), "r"(a[1]), "r"(a[2]), "r"(a[3]), "r"(b0), "r"(b1));
}
__device__ __forceinline__ uint32_t lds32(uint32_t a) {
    uint32_t v;
    asm volatile("ld.shared.u32 %0, [%1];" : "=r"(v) : "r"(a));
    return v;
}
__device__ __forceinline__ unsigned ld_acquire(const unsigned* p) {
    unsigned v;
    asm volatile("ld.acquire.gpu.global.u32 %0, [%1];" : "=r"(v) : "l"(p) : "memory");
    return v;
}
__device__ __forceinline__ uint2 ld_relaxed8(const void* p) {
    uint2 v;
    asm volatile("ld.relaxed.gpu.global.v2.u32 {%0,%1}, [%2];" : "=r"(v.x), "=r"(v.y) : "l"(p) : "memory");
    return v;
}
__device__ __forceinline__ unsigned ld_relaxed4(const void* p) {
    unsigned v;
    asm volatile("ld.relaxed.gpu.global.u32 %0, [%1];" : "=r"(v) : "l"(p) : "memory");
    return v;
}
__device__ __forceinline__ unsigned atom_inc(unsigned* p) {
    unsigned v;
    asm volatile("atom.relaxed.gpu.global.inc.u32 %0, [%1], 0x7fffffff;" : "=r"(v) : "l"(p) : "memory");
    return v;
}
__device__ __forceinline__ unsigned long long ld_relaxed64(const void* p) {
    unsigned long long v;
    asm volatile("ld.relaxed.gpu.global.u64 %0, [%1];" : "=l"(v) : "l"(p) : "memory");
    return v;
}
__device__ __forceinline__ void st_relaxed64(void* p, unsigned long long v) {
    asm volatile("st.relaxed.gpu.global.u64 [%0], %1;" ::"l"(p), "l"(v) : "memory");
}
__device__ __forceinline__ float4 ld_relaxed16(const void* p) {
    float4 v;
    asm volatile("ld.relaxed.gpu.global.v4.f32 {%0,%1,%2,%3}, [%4];" : "=f"(v.x), "=f"(v.y), "=f"(v.z), "=f"(v.w) : "l"(p) : "memory");
    return v;
}
__device__ __forceinline__ uint32_t mapa(uint32_t a, uint32_t rank) {
    uint32_t r;
    asm("mapa.shared::cluster.u32 %0, %1, %2;" : "=r"(r) : "r"(a), "r"(rank));
    return r;
}
__device__ __forceinline__ uint32_t time_ns() { uint32_t t; asm volatile("mov.u32 %0, %globaltimer_lo;" : "=r"(t)); return t; }
__device__ __forceinline__ void fence_gpu() { asm volatile("fence.acq_rel.gpu;" ::: "memory"); }
__device__ __forceinline__ void red_add_u32(unsigned* p, unsigned v) {
    asm volatile("red.relaxed.gpu.global.add.u32 [%0], %1;" ::"l"(p), "r"(v) : "memory");
}
__device__ __forceinline__ void st_tagged2(void* p, float a, float b, unsigned tag) {
    const unsigned long long hi = (unsigned long long)tag << 32;
    asm volatile("st.relaxed.gpu.global.v2.b64 [%0], {%1,%2};" ::"l"(p), "l"(hi | __float_as_uint(a)), "l"(hi | __float_as_uint(b)) : "memory");
}
__device__ __forceinline__ ulonglong2 ld_tagged2(const void* p) {
    ulonglong2 v;
    asm volatile("ld.relaxed.gpu.global.v2.b64 {%0,%1}, [%2];" : "=l"(v.x), "=l"(v.y) : "l"(p) : "memory");
    return v;
}
__device__ __forceinline__ float4 atom_add_f4(void* p, float a, float b, float c, float d) {
    float4 r;
    asm volatile("atom.relaxed.gpu.global.add.v4.f32 {%0,%1,%2,%3}, [%4], {%5,%6,%7,%8};"
                 : "=f"(r.x), "=f"(r.y), "=f"(r.z), "=f"(r.w) : "l"(p), "f"(a), "f"(b), "f"(c), "f"(d) : "memory");
    return r;
}
__device__ __forceinline__ void red_release_cta_shared(uint32_t a, unsigned v) {
    asm volatile("red.release.cta.shared::cta.add.u32 [%0], %1;" ::"r"(a), "r"(v) : "memory");
}
__device__ __forceinline__ unsigned ld_acquire_cta_shared(uint32_t a) {
    unsigned v;
    asm volatile("ld.acquire.cta.shared::cta.u32 %0, [%1];" : "=r"(v) : "r"(a) : "memory");
    return v;
}
__device__ __forceinline__ void st_release_cta_shared(uint32_t a, unsigned v) {
    asm volatile("st.release.cta.shared::cta.u32 [%0], %1;" ::"r"(a), "r"(v) : "memory");
}
__device__ __forceinline__ void wait_count(const unsigned* p, unsigned target) {
    unsigned n = 0;
    while (ld_acquire(p) < target) { if (++n > SPIN_LIMIT) __trap(); }
}
__device__ __forceinline__ uint32_t pack_bf16(float lo, float hi) {
    uint32_t r;
    asm("cvt.rn.bf16x2.f32 %0, %1, %2;" : "=r"(r) : "f"(hi), "f"(lo));
    return r;
}
__device__ __forceinline__ float bf_lo(uint32_t v) { return __uint_as_float(v << 16); }
__device__ __forceinline__ float bf_hi(uint32_t v) { return __uint_as_float(v & 0xffff0000u); }
__device__ __forceinline__ float ex2(float x) { float y; asm("ex2.approx.ftz.f32 %0, %1;" : "=f"(y) : "f"(x)); return y; }
__device__ __forceinline__ float expsub(float a, float b) { return ex2((a - b) * LOG2E); }
__device__ __forceinline__ float warp_max(float v) {
#pragma unroll
    for (int m = 16; m; m >>= 1) v = fmaxf(v, __shfl_xor_sync(~0u, v, m));
    return v;
}
__device__ __forceinline__ float warp_sum(float v) {
#pragma unroll
    for (int m = 16; m; m >>= 1) v += __shfl_xor_sync(~0u, v, m);
    return v;
}
template <bool CLU>
__device__ __forceinline__ unsigned unit_block(int u) {
    const unsigned x = ((unsigned)u & (NUK - 1)) / UPP;
    const int lg = u < NUK ? min(KMAX, max(KMIN, 29 - __clz(x | 1))) : (CLU && (int)x >= 4 * VS0 ? 0 : min(VMAX, max(VMIN, 29 - __clz((127 - x) | 1))));
    const unsigned r = x & ((4u << lg) - 1);
    return ((x - r + (r & ((1u << lg) - 1)) * 4 + (r >> lg)) * UPP) | ((unsigned)u & (UPP - 1));
}
__device__ __forceinline__ const char* block_src(const void* base, unsigned blk) {
    const unsigned po = blk / UPP;
    return reinterpret_cast<const char*>(base) + (size_t)(((po & 3) * NH + (po >> 2)) * UPP + blk % UPP) * TILE_BYTES;
}

template <bool CLU>
__device__ __forceinline__ void a_worker(const Params& p, int un, bool once, bool pre, bool hold, int nstatic, uint32_t slot, uint32_t bar,
                                         uint32_t help, unsigned epoch, uint64_t pol) {
    constexpr int NU = 2 * NUK, NR = CLU ? NREPC : NREP;
    const int lane = threadIdx.x & 31, g = lane >> 2, t = lane & 3;
    const int li = lane & 7;
    uint32_t kaddr[4], vaddr[8];
    {
        const int e = (lane >> 3) & 1, kk = lane >> 4;
#pragma unroll
        for (int s = 0; s < 4; s++) kaddr[s] = slot + (16 * li + e) * 256 + ((2 * s + kk + li) & 7) * 16;
        const int vrow = 4 * (li >> 1) + (li & 1) + 2 * kk;
#pragma unroll
        for (int c = 0; c < 8; c++) vaddr[c] = slot + vrow * 256 + e * 128 + ((c + li) & 7) * 16;
#pragma unroll
        for (int c = 0; c < 8; c++) asm volatile("" : "+r"(vaddr[c]));
    }
    const uint32_t vmask = (g >> 1) != t ? 0u : ((g & 1) ? 0xffff0000u : 0xffffu);
    int kseen = -1;
    unsigned long long H0 = 0, H1 = 0;
    auto header = [&](int v, unsigned vb) {
        if (v >= NU) return;
        const void *a0, *a1;
        if (v < NUK) {
            const unsigned po = vb / UPP;
            a0 = g_qll + (po & 3) * 2048 + (po >> 2) * 64 + lane;
            a1 = reinterpret_cast<const uint2*>(a0) + 32;
        } else {
            const int half = vb / (NUK / 2);
            if (half > kseen) {
                unsigned n = 0;
                while (ld_acquire_cta_shared(help + 12 + 4 * half) == 0) { if (++n > (SPIN_LIMIT << 4)) __trap(); }
                kseen = half;
            }
            a0 = &g_scores[vb * (KEYS / 4) + lane];
            a1 = &g_stats[(vb / UPP) * UPP + lane];
        }
        H0 = ld_relaxed64(a0);
        H1 = ld_relaxed64(a1);
    };
    asm volatile("bar.sync 2, %0;" ::"n"(32 * (NW + XW + 1)) : "memory");
    epoch = __shfl_sync(~0u, epoch, 0);
    if (hold) { unsigned n = 0; while (ld_acquire_cta_shared(help + 24) < 2) { if (++n > (SPIN_LIMIT << 4)) __trap(); } }
    unsigned (*ctl)[32] = g_ctl[epoch & 1];
    const unsigned tag = epoch + 1;
    unsigned nxt = once ? NU : 0;
    int u = -1;
    unsigned bu = 0, bn = unit_block<CLU>(un);
    bool have = false;
    uint32_t phase = 0;
    unsigned kpend = 0;
    const unsigned zero = gridDim.x >> 24;
    uint32_t Q[16];
    float4 oret = make_float4(0.f, 0.f, 0.f, 0.f);
    while (true) {
        const char* nsrc = block_src(un < NUK ? p.kc : p.vc, bn);
        float4* odst = &g_oacc[(bu / UPP) * 32 + lane];
        unsigned* vdst = &g_vdone[(lane & (NR - 1)) * NH + bu / (4 * UPP)][0];
        float d[8][4];
        CLK(c1);
        uint32_t act = un >= NU ? 0u : (u >= 0 || !pre ? 1u : 0u) | (!once && lane == 0 ? 2u : 0u);
        asm volatile("" : "+l"(odst), "+l"(nsrc), "+r"(act));
        if (u >= NUK) {
#pragma unroll
            for (int j = 0; j < 8; j++) { d[j][0] = d[j][1] = d[j][2] = d[j][3] = 0.f; }
            mbar_wait(bar, phase);
            LAND(NUK + bu);
            uint32_t a[2][8][4];
#pragma unroll
            for (int c = 0; c < 8; c++) ldsm4t(a[0][c], vaddr[c]);
#pragma unroll
            for (int j = 0; j < 8; j++) {
                if (j < 7) {
#pragma unroll
                    for (int c = 0; c < 8; c++) ldsm4t(a[(j + 1) & 1][c], vaddr[c] + (j + 1) * 4096);
                }
#pragma unroll
                for (int c = 0; c < 8; c++) mma16816(d[c], a[j & 1][c], Q[2 * j], Q[2 * j + 1]);
            }
            float o[4];
#pragma unroll
            for (int r = 0; r < 2; r++) {
                o[2 * r] = d[0][2 * r] + d[7][2 * r + 1];
                o[2 * r + 1] = d[0][2 * r + 1] + d[1][2 * r];
#pragma unroll
                for (int k = 1; k < 4; k++) {
                    const int src = (lane & 28) | ((t - k) & 3);
                    o[2 * r] += __shfl_sync(~0u, d[2 * k][2 * r] + d[2 * k - 1][2 * r + 1], src);
                    o[2 * r + 1] += __shfl_sync(~0u, d[2 * k][2 * r + 1] + d[2 * k + 1][2 * r], src);
                }
            }
            oret = atom_add_f4(odst, o[0], o[1], o[2], o[3]);
        } else if (u >= 0) {
#pragma unroll
            for (int j = 0; j < 8; j++) { d[j][0] = d[j][1] = d[j][2] = d[j][3] = 0.f; }
            mbar_wait(bar, phase);
            LAND(bu);
            uint32_t a[2][8][4];
#pragma unroll
            for (int j = 0; j < 8; j++) ldsm4(a[0][j], kaddr[0] + (4 * (j & 3) + 2 * (j >> 2)) * 256);
#pragma unroll
            for (int s = 0; s < 8; s++) {
                if (s < 7) {
#pragma unroll
                    for (int j = 0; j < 8; j++)
                        ldsm4(a[(s + 1) & 1][j], kaddr[(s + 1) & 3] + (4 * (j & 3) + 2 * (j >> 2)) * 256 + ((s + 1) >> 2) * 128);
                }
#pragma unroll
                for (int j = 0; j < 8; j++)
                    mma16816(d[j], a[s & 1][j], Q[(s & 4) * 2 + ((2 * s - 2 * j) & 7)], Q[(s & 4) * 2 + ((2 * s + 1 - 2 * j) & 7)]);
            }
        }
        if (u >= 0) phase ^= 1;
        CLK(c2b);
        asm volatile("{\n.reg .pred p, q;\n.reg .u32 a;\nelect.sync _|p, 0xffffffff;\nand.b32 a, %5, 1;\nsetp.ne.and.u32 q, a, 0, p;\n"
                     "@q mbarrier.arrive.expect_tx.shared::cta.b64 _, [%2], %4;\n"
                     "@q cp.async.bulk.shared::cluster.global.mbarrier::complete_tx::bytes.L2::cache_hint [%0], [%1], %4, [%2], %3;\n}"
                     ::"r"(slot), "l"(nsrc), "r"(bar), "l"(pol), "n"(TILE_BYTES), "r"(act) : "memory");
        if (act & 2) nxt = atom_inc(&ctl[C_QUEUE][0]);
        const uint32_t tk = clock();
        CLK(c3);
        if ((unsigned)u < (unsigned)NUK) {
            const int j0 = (t - (g >> 1)) & 3;
            float v[4];
#pragma unroll
            for (int q = 0; q < 4; q++) {
                const int jq = (q >> 1) * 4, e = (q & 1) * 2;
                const float x0 = (g & 1) ? d[jq + 0][e + 1] : d[jq + 0][e];
                const float x1 = (g & 1) ? d[jq + 1][e + 1] : d[jq + 1][e];
                const float x2 = (g & 1) ? d[jq + 2][e + 1] : d[jq + 2][e];
                const float x3 = (g & 1) ? d[jq + 3][e + 1] : d[jq + 3][e];
                const float y0 = (j0 & 1) ? x1 : x0, y1 = (j0 & 1) ? x3 : x2;
                v[q] = (j0 & 2) ? y1 : y0;
            }
            const uint32_t r0 = pack_bf16(v[0], v[1]), r1 = pack_bf16(v[2], v[3]);
            const uint32_t s0 = pack_bf16(bf_lo(r0) * SCALE, bf_hi(r0) * SCALE);
            const uint32_t s1 = pack_bf16(bf_lo(r1) * SCALE, bf_hi(r1) * SCALE);
            g_scores[bu * (KEYS / 4) + 4 * g + j0] = make_uint2(s0, s1);
            const float f0 = bf_lo(s0), f1 = bf_hi(s0), f2 = bf_lo(s1), f3 = bf_hi(s1);
            const float m = warp_max(fmaxf(fmaxf(f0, f1), fmaxf(f2, f3)));
            const float l = warp_sum((expsub(f0, m) + expsub(f1, m)) + (expsub(f2, m) + expsub(f3, m)));
            if (lane == 0) g_stats[bu] = make_float2(m, l);
            kpend++;
            if (un / (NUK / 2) != u / (NUK / 2)) {
                __syncwarp();
                if (lane == 0) {
                    red_release_cta_shared(help + 4 * (u / (NUK / 2)), kpend);
                    if (un >= NUK) red_release_cta_shared(help + 8, 1u);
                }
                kpend = 0;
            }
        }
        CLK(c4);
        int unn = NU;
        if (un < NU) {
            unsigned n = 0;
            while (true) {
                if (!have) header(un, bn);
                if (un >= NUK || __all_sync(~0u, (uint32_t)(H0 >> 32) == tag && (uint32_t)(H1 >> 32) == tag)) break;
                if (++n > SPIN_LIMIT) __trap();
                have = false;
            }
            if (un >= NUK) {
                const uint32_t s0 = (uint32_t)H0, s1 = (uint32_t)(H0 >> 32);
                const float mu = __uint_as_float((uint32_t)H1);
                const float m = warp_max(mu);
                const float l = warp_sum(__uint_as_float((uint32_t)(H1 >> 32)) * expsub(mu, m));
                const float inv = 1.0f / l;
                const uint32_t w0 = pack_bf16(expsub(bf_lo(s0), m) * inv, expsub(bf_hi(s0), m) * inv);
                const uint32_t w1 = pack_bf16(expsub(bf_lo(s1), m) * inv, expsub(bf_hi(s1), m) * inv);
#pragma unroll
                for (int j = 0; j < 8; j++) {
                    Q[2 * j] = __shfl_sync(~0u, w0, 4 * j + t) & vmask;
                    Q[2 * j + 1] = __shfl_sync(~0u, w1, 4 * j + t) & vmask;
                }
            } else {
#pragma unroll
                for (int j = 0; j < 8; j++) {
                    const int src = (((j + g) & 7) << 2) + t;
                    Q[j] = __shfl_sync(~0u, (uint32_t)H0, src);
                    Q[8 + j] = __shfl_sync(~0u, (uint32_t)H1, src);
                }
            }
            unn = nstatic + (int)__shfl_sync(~0u, nxt, 0);
            if (CLU && ((NU - EARLY - unn) & ~(7 << ELOG)) == 0 && lane < MINCL)
                st_relaxed64(&g_dry[lane][(NU - EARLY - unn) >> ELOG],
                             (time_ns() - (((uint32_t)clock() - tk) >> 1) + (NU - unn) * TPU / 16) | (unsigned long long)tag << 32);
        }
        if (u >= NUK && lane < NR)
            red_add_u32(vdst,
                        1u + ((__float_as_uint(oret.x) | __float_as_uint(oret.y) | __float_as_uint(oret.z) | __float_as_uint(oret.w)) & zero));
        if (un >= NU) break;
        bu = bn;
        have = !(un < NUK && unn >= NUK && !(un >= NUK / 2 && unn < NUK + NUK / 2));
        bn = unit_block<CLU>(unn);
        if (have) header(unn, bn);
        u = un;
        un = unn;
    }
}

__device__ __forceinline__ void k_helper(uint32_t help, unsigned epoch) {
    if ((threadIdx.x & 31) != 0) return;
    unsigned (*ctl)[32] = g_ctl[epoch & 1];
    unsigned sent0 = 0, sent1 = 0, n = 0;
    int seen = 0;
    bool fin = false;
    while (!fin || seen < 2) {
        if (!fin) {
            fin = ld_acquire_cta_shared(help + 8) == NW + XW;
            const unsigned c0 = ld_acquire_cta_shared(help), c1 = ld_acquire_cta_shared(help + 4);
            if (c0 != sent0 || c1 != sent1) {
                fence_gpu();
                if (c0 != sent0) red_add_u32(&ctl[C_KDONE][0], c0 - sent0);
                if (c1 != sent1) red_add_u32(&ctl[C_KDONE + 1][0], c1 - sent1);
                sent0 = c0; sent1 = c1;
            }
        }
        if (seen < 2 && ld_acquire(&ctl[C_KDONE + seen][0]) >= NUK / 2) {
            st_release_cta_shared(help + 12 + 4 * seen, 1u);
            seen++;
        } else {
            __nanosleep(300);
        }
        if (++n > SPIN_LIMIT) __trap();
    }
}

__device__ __forceinline__ void v_poller(uint32_t sbase, int f, int w) {
    constexpr int HL = NH;
    const int lane = threadIdx.x & 31;
    const unsigned (*cp)[32] = &g_vdone[((f * NPOLL + w) % NREP) * NH];
    unsigned n = 0;
    while (ld_acquire_cta_shared(sbase + M_HELP + 12) == 0) { __nanosleep(1000); if (++n > SPIN_LIMIT) __trap(); }
    int h = 0;
    bool fast = false;
    while (h < HL) {
        const unsigned r = __ballot_sync(~0u, ld_acquire(&cp[min(h + (lane & 3), HL - 1)][0]) >= 4 * UPP) & 15u;
        if (r & 1) {
            h = min(HL, h + __ffs(~r) - 1);
            __syncwarp();
            if (lane == 0) asm volatile("red.release.cta.shared::cta.max.u32 [%0], %1;" ::"r"(sbase + M_HELP + 20), "r"(h) : "memory");
        }
        if (h < HL - 4) {
            __nanosleep(h ? 300 : 1000);
        } else if (!fast) {
            fast = true;
            const long long t0 = clock64();
            while (clock64() - t0 < w * PGAP) {}
        }
        if (++n > SPIN_LIMIT) __trap();
    }
}
__device__ __forceinline__ void finisher(const Params& p, uint32_t sbase, int f) {
    constexpr int HL = NH;
    const int lane = threadIdx.x & 31;
    {
        const char* wg = reinterpret_cast<const char*>(p.wo);
        const uint32_t dst = sbase + 4 * SLOT + (16 * (lane & 7) + (lane >> 3)) * 16;
#pragma unroll 1
        for (int h = -FPF - 4; h < HL; h++) {
            if (lane == 0 && (unsigned)(h + FPF) < (unsigned)HL) l2_prefetch(wg + (size_t)(h + FPF) * 147456 + f * 2048, 2048);
            if (h >= 0) {
#pragma unroll
                for (int r = 0; r < 4; r++)
                    asm volatile("cp.async.cg.shared.global [%0], [%1], 16;" ::"r"(dst + h * 2048 + ((r & 1) * 4 + (r >> 1) * 8) * 16),
                                 "l"(wg + (size_t)(h * 128 + r * 32 + lane) * (DM * 2) + f * 16) : "memory");
            }
            __nanosleep(FSLEEP);
        }
        asm volatile("cp.async.wait_all;" ::: "memory");
        __syncwarp();
    }
    TS(11);
    const float4* vec = g_oacc + ((lane >> 2) & 3) * 32 + (lane >> 4) * 16 + (lane & 3);
    float acc[2][2][4];
#pragma unroll
    for (int i = 0; i < 16; i++) acc[i >> 3][(i >> 2) & 1][i & 3] = 0.f;
    uint32_t* outp = reinterpret_cast<uint32_t*>(p.out + (lane >> 2) * (2 * DM) + f * 8 + (lane & 3) * 2);
    uint32_t wa = sbase + 4 * SLOT + lane * 16;
    auto project = [&](const float4 (&x)[4], const uint32_t (&w)[4][4]) {
#pragma unroll
        for (int s = 0; s < 4; s++) {
            const uint32_t a[4] = {pack_bf16(x[s].x, x[s].y), 0u, pack_bf16(x[s].z, x[s].w), 0u};
            mma16816(acc[0][s & 1], a, w[s >> 1][(s & 1) * 2], w[s >> 1][(s & 1) * 2 + 1]);
            mma16816(acc[1][s & 1], a, w[2 + (s >> 1)][(s & 1) * 2], w[2 + (s >> 1)][(s & 1) * 2 + 1]);
        }
    };
    int h = 0;
    unsigned n = 0;
    while (h < HL) {
        uint32_t w[4][4];
#pragma unroll
        for (int q = 0; q < 4; q++) ldsm4t(w[q], wa + q * 512);
        int ready;
        while ((ready = ld_acquire_cta_shared(sbase + M_HELP + 20)) <= h) {
            if (h < HL - 3) __nanosleep(100);
            if (++n > (SPIN_LIMIT << 4)) __trap();
        }
        float4 x[4], y[4];
#pragma unroll
        for (int s = 0; s < 4; s++) x[s] = ld_relaxed16(vec + s * 4);
        const bool two = ready > h + 1;
        if (two) {
#pragma unroll
            for (int s = 0; s < 4; s++) y[s] = ld_relaxed16(vec + 128 + s * 4);
        }
        project(x, w);
        if (two) {
#pragma unroll
            for (int q = 0; q < 4; q++) ldsm4t(w[q], wa + 2048 + q * 512);
            project(y, w);
        }
        const int nr = two ? 2 : 1;
        h += nr;
        vec += nr * 128;
        wa += nr * 2048;
        const float o0 = acc[0][0][0] + acc[0][1][0] + __shfl_down_sync(~0u, acc[1][0][0] + acc[1][1][0], 16);
        const float o1 = acc[0][0][1] + acc[0][1][1] + __shfl_down_sync(~0u, acc[1][0][1] + acc[1][1][1], 16);
        asm volatile("{\n.reg .pred p;\nsetp.ne.u32 p, %2, 0;\n@p st.global.u32 [%0], %1;\n}" ::"l"(outp), "r"(pack_bf16(o0, o1)),
                     "r"((uint32_t)(lane < 16 && h == NH)) : "memory");
    }
}

__device__ __noinline__ void f_collect(const unsigned (*flag)[32], unsigned full, const float4* src, unsigned todo, uint32_t sbase) {
    const int lane = threadIdx.x & 31, g = lane >> 2, t = lane & 3;
    const bool last = todo != 15;
    unsigned n = 0;
    while (todo) {
        const unsigned v = ld_acquire(&flag[t][0]);
        unsigned m = __ballot_sync(~0u, v == full) & todo;
        if (m == 0) {
            if (!last || __shfl_sync(~0u, v, 0) == 0) __nanosleep(200);
            if (++n > SPIN_LIMIT) __trap();
            continue;
        }
        __syncwarp();
        todo ^= m;
        if (last) TS(16);
        do {
            const int h0 = __ffs(m) - 1, h1 = 31 - __clz(m);
            m &= ~((1u << h0) | (1u << h1));
            float4 x[8];
#pragma unroll
            for (int b = 0; b < 8; b++) x[b] = ld_relaxed16(src + ((b & 4) ? h1 : h0) * 128 + (b & 3) * 32 + lane);
#pragma unroll
            for (int b = 0; b < 8; b++) {
                const uint32_t lo = pack_bf16(x[b].x, x[b].y), hi = pack_bf16(x[b].z, x[b].w);
                const uint32_t o = __shfl_xor_sync(~0u, (g & 1) ? lo : hi, 4);
                const uint32_t e0 = (g & 1) ? o : lo, e1 = (g & 1) ? hi : o;
                asm volatile("st.shared.v2.u32 [%0], {%1,%2};"
                             ::"r"(sbase + F_BF + ((b & 4) ? h1 : h0) * 1024 + t * 256 + ((b ^ t) & 3) * 64 + g * 8),
                               "r"(__byte_perm(e0, e1, 0x5410)), "r"(__byte_perm(e0, e1, 0x7632)) : "memory");
            }
            __syncwarp();
            if (lane < (h0 == h1 ? 1 : 2))
                asm volatile("mbarrier.arrive.shared::cta.b64 _, [%0];" ::"r"(sbase + F_BAR + 32 + (lane ? h1 : h0) * 8) : "memory");
        } while (m);
    }
    if (last) TS(17);
}

__device__ __forceinline__ void f_project(const CUtensorMap* tm, int panel, int rank, int warp, int sl, int delay, unsigned tag, uint32_t sbase, uint64_t pol) {
    const int j = warp & 3;
    const int lane = threadIdx.x & 31, g = lane >> 2, t = lane & 3;
    const uint32_t wb = sbase + F_W - sl * 2 * SLOT, bars = sbase + F_BAR + 64 + sl * 32;
    const uint32_t wa = wb + ((lane & 7) + (lane >> 4) * 8) * 128 + (((2 * j + ((lane >> 3) & 1)) ^ (lane & 7)) * 16);
    const uint32_t ba = sbase + F_BF + (g & 3) * 64 + t * 16;
    const uint32_t rdst = mapa(sbase + F_RX + sl * 1024 + rank * 128 + g * 16 + (t & 1) * 8, 2 * j + (t >> 1));
    const uint32_t rbar = mapa(sbase + F_BAR + 16 + sl * 8, 2 * j + (t >> 1));
    unsigned n = 0;
    if (warp == 7) {
        if (lane == 0) asm volatile("prefetch.tensormap [%0];" ::"l"(tm) : "memory");
        unsigned long long v;
        while (!__all_sync(~0u, (v = ld_relaxed64(&g_dry[blockIdx.x >> 3][g])) >> 32 == tag)) {
            __nanosleep(200);
            if (++n > SPIN_LIMIT) __trap();
        }
        const uint32_t t0 = __shfl_sync(~0u, (uint32_t)v, 0);
        const uint32_t t1 = t0 + (__reduce_add_sync(~0u, (int)((uint32_t)v - t0)) >> 5);
        if (lane == 0) asm volatile("st.shared.u32 [%0+8], %1;\nmbarrier.arrive.shared::cta.b64 _, [%0];" ::"r"(sbase + F_BAR), "r"(t1) : "memory");
        TS(22);
    }
    mbar_wait(sbase + F_BAR, 0);
    float acc[2][4];
#pragma unroll
    for (int i = 0; i < 8; i++) acc[i >> 2][i & 3] = 0.f;
    const bool up = t & 2;
#pragma unroll 1
    for (int h = 0; h < 4; h++) {
        if (h == max(j - LAG, 0)) {
            const uint32_t due = lds32(sbase + F_BAR + 8) + delay;
            while ((int)(time_ns() - due) < 0 && ++n < SPIN_LIMIT) {}
            tma3d_warp(wb + j * 16384, tm, 0, (rank * 4 + j) * 128, panel, bars + j * 8, 16384, pol);
            TS(18);
        }
        uint32_t wp = wa + h * 16384, last = h == 3;
        mbar_spin(sbase + F_BAR + 32 + h * 8);
        uint32_t a[8][4], bf[4][4];
#pragma unroll
        for (int s = 0; s < 4; s++)
            asm volatile("ld.shared.v4.u32 {%0,%1,%2,%3}, [%4];" : "=r"(bf[s][0]), "=r"(bf[s][1]), "=r"(bf[s][2]), "=r"(bf[s][3])
                         : "r"(((ba + h * 1024) ^ (s * 64)) + s * 256) : "memory");
        asm volatile("" : "+r"(wp), "+r"(last));
        mbar_spin(bars + h * 8);
        if (h == 3) TS(19);
#pragma unroll
        for (int s = 0; s < 8; s++) ldsm4t(a[s], wp + s * 2048);
#pragma unroll
        for (int s = 0; s < 8; s++) mma16816(acc[s & 1], a[s], bf[s & 3][(s >> 2) * 2], bf[s & 3][(s >> 2) * 2 + 1]);
        const float v0 = up ? acc[0][2] + acc[1][2] : acc[0][0] + acc[1][0], v1 = up ? acc[0][3] + acc[1][3] : acc[0][1] + acc[1][1];
        asm volatile("{\n.reg .pred p;\nsetp.ne.u32 p, %4, 0;\n"
                     "@p st.async.weak.shared::cluster.mbarrier::complete_tx::bytes.v2.b32 [%0], {%1,%2}, [%3];\n}"
                     ::"r"(rdst), "r"(__float_as_uint(v0)), "r"(__float_as_uint(v1)), "r"(rbar), "r"(last) : "memory");
    }
    TS(20);
}

__device__ __forceinline__ void f_receive(__nv_bfloat16* out, int sl, bool dry, uint32_t sbase) {
    const int lane = threadIdx.x & 31;
    out += (lane & 3) * (2 * DM) + (lane >> 2);
    uint32_t src = sbase + F_RX + sl * 1024 + lane * 4;
    asm volatile("" : "+l"(out), "+r"(src));
    mbar_spin_cluster(sbase + F_BAR + (dry ? 0 : 16 + sl * 8));
    float v[8];
#pragma unroll
    for (int r = 0; r < 8; r++) asm volatile("ld.shared.f32 %0, [%1];" : "=f"(v[r]) : "r"(src + r * 128) : "memory");
    const float o = ((v[0] + v[1]) + (v[2] + v[3])) + ((v[4] + v[5]) + (v[6] + v[7]));
    asm volatile("{\n.reg .pred p;\nsetp.eq.u32 p, %2, 0;\n@p st.global.u16 [%0], %1;\n}"
                 ::"l"(out), "h"((unsigned short)pack_bf16(o, 0.f)), "r"((uint32_t)dry) : "memory");
    TS(15);
}

constexpr int BS_WUK = 5, BS_Q = 9, BS_CKV = 11, BS_PART = 27, BS_WUV = 29, BS_END = 33;

__device__ __noinline__ void b_issue(const Params& p, int n, int bi, uint32_t sbase, uint64_t pol) {
    if (n >= BS_END || (n >= BS_Q && n < BS_CKV) || (n >= BS_PART && n < BS_WUV)) return;
    const uint32_t bar = sbase + M_BAR + (NSLOT + n % BRING) * 8;
    const CUtensorMap* tm;
    int row, panel = 2 * bi;
    if (n < BS_WUK) { tm = &p.tm_wq; row = n * 128; }
    else if (n < BS_Q) { tm = &p.tm_wuk; row = (n - BS_WUK) * 128; }
    else if (n < BS_PART) {
        tm = &p.tm_ckv; panel = 0;
        row = (bi >> 3) * SK + ((n - BS_CKV) * 8 + (bi & 7)) * 32;
    }
    else { tm = &p.tm_wuv; row = (n - BS_WUV) * 128; }
    mbar_expect_tx(bar, n == 0 ? 32768 + 4 * 1152 : 32768);
    tma3d(sbase + (n % BRING) * SLOT, tm, 0, row, panel, bar, pol);
}
__device__ __forceinline__ void b_issue_xchg(int n, const void* src, uint32_t sbase, uint64_t pol) {
    asm volatile("fence.proxy.async;" ::: "memory");
#pragma unroll
    for (int i = 0; i < 2; i++) {
        const uint32_t bar = sbase + M_BAR + (NSLOT + (n + i) % BRING) * 8;
        mbar_expect_tx(bar, 32768);
        bulk_load(sbase + ((n + i) % BRING) * SLOT, reinterpret_cast<const char*>(src) + i * 32768, 32768, bar, pol);
    }
}
__device__ __forceinline__ void b_wait(int n, uint32_t sbase) {
    mbar_wait(sbase + M_BAR + (NSLOT + n % BRING) * 8, (n / BRING) & 1);
}

__device__ __noinline__ void b_gemm(const Params& p, uint32_t sbase, int n0, int n1, int ktot, uint32_t xh, uint32_t xl, int pitch,
                                    int bi, uint64_t pol) {
    const int tid = threadIdx.x, warp = tid >> 5, lane = tid & 31, g = lane >> 2, t = lane & 3;
    const uint32_t woff = (warp >> 2) * 16384 + (lane & 15) * 128 + ((((warp & 3) * 2 + (lane >> 4)) ^ (lane & 7)) * 16);
    const uint32_t xoff = (g & 3) * pitch + t * 4;
    float acc[2][4];
#pragma unroll
    for (int i = 0; i < 8; i++) acc[i >> 2][i & 3] = 0.f;
#pragma unroll 1
    for (int n = n0; n < n1; n++) {
        b_wait(n, sbase);
        const uint32_t slot = sbase + (n % BRING) * SLOT + woff;
        const int k0 = (n - n0) * 128;
        const int ns = min(8, (ktot - k0) >> 4);
#pragma unroll 2
        for (int s = 0; s < ns; s++) {
            uint32_t a[4], w[4];
            const uint32_t xo = xoff + (k0 + 16 * s) * 2;
            a[0] = lds32(xh + xo); a[2] = lds32(xh + xo + 16);
            a[1] = xl ? lds32(xl + xo) : 0u; a[3] = xl ? lds32(xl + xo + 16) : 0u;
            ldsm4t(w, slot + s * 2048);
            mma16816(acc[0], a, w[0], w[1]);
            mma16816(acc[1], a, w[2], w[3]);
        }
        __syncthreads();
        if (tid == 0) b_issue(p, n + BD, bi, sbase, pol);
    }
    if (g < 4) {
#pragma unroll
        for (int j = 0; j < 2; j++)
            asm volatile("st.shared.u32 [%0], %1;" ::"r"(sbase + M_QB + g * QP + (warp * 16 + j * 8 + t * 2) * 2),
                         "r"(pack_bf16(acc[j][0] + acc[j][2], acc[j][1] + acc[j][3])) : "memory");
    }
    __syncthreads();
}

__device__ __forceinline__ void b_exchange(unsigned* c, int n, const void* src, uint32_t sbase, uint64_t pol) {
    TS(n == BS_Q ? 24 : 28);
    __syncthreads();
    if (threadIdx.x == 0) {
        TS(n == BS_Q ? 25 : 29);
        fence_gpu();
        TS(n == BS_Q ? 26 : 30);
        red_add_u32(c, 1u);
        wait_count(c, NBCTA);
        TS(n == BS_Q ? 27 : 31);
        b_issue_xchg(n, src, sbase, pol);
    }
}

template <bool CLU>
__device__ __noinline__ void b_chain(const Params& p, char* smem, uint32_t sbase, int bi, unsigned epoch, uint64_t pol) {
    const int tid = threadIdx.x, warp = tid >> 5, lane = tid & 31, g = lane >> 2, t = lane & 3;
    unsigned (*ctl)[32] = g_ctl[epoch & 1];
    float* red = reinterpret_cast<float*>(smem + 5 * SLOT);
    __syncthreads();
    b_gemm(p, sbase, 0, BS_WUK, DM, sbase + M_XB, 0, XP, bi, pol);
    TS(6);
    {
        uint32_t Q[16];
#pragma unroll
        for (int c = 0; c < 16; c++) Q[c] = lds32(sbase + M_QB + (g & 3) * QP + c * 16 + t * 4);
        float* qa = reinterpret_cast<float*>(smem + M_QA);
#pragma unroll 1
        for (int n = BS_WUK; n < BS_Q; n++) {
            b_wait(n, sbase);
            const uint32_t base = sbase + (n % BRING) * SLOT + (warp * 16 + (lane & 15)) * 128;
            float d[2][4];
#pragma unroll
            for (int i = 0; i < 8; i++) d[i >> 2][i & 3] = 0.f;
#pragma unroll
            for (int s = 0; s < 8; s++) {
                uint32_t a[4];
                ldsm4(a, base + (s >> 2) * 16384 + (((2 * (s & 3) + (lane >> 4)) ^ (lane & 7)) * 16));
                mma16816(d[s & 1], a, Q[2 * s], Q[2 * s + 1]);
            }
            const int c = (n - BS_WUK) * 128 + warp * 16 + g + 8 * (t >> 1);
            qa[(2 * (t & 1)) * 512 + c] = (t & 2) ? d[0][2] + d[1][2] : d[0][0] + d[1][0];
            qa[(2 * (t & 1) + 1) * 512 + c] = (t & 2) ? d[0][3] + d[1][3] : d[0][1] + d[1][1];
            __syncthreads();
            if (tid == 0) b_issue(p, n + BD, bi, sbase, pol);
        }
#pragma unroll 1
        for (int r = 0; r < 2; r++) {
            const int id = tid + r * 256;
            const int b = id >> 7, c0 = ((id >> 2) & 31) * 16 + (id & 3) * 2;
            const float2 u0 = *reinterpret_cast<const float2*>(qa + b * 512 + c0);
            const float2 u1 = *reinterpret_cast<const float2*>(qa + b * 512 + c0 + 8);
            const uint32_t h0 = pack_bf16(u0.x, u0.y), h1 = pack_bf16(u1.x, u1.y);
            const uint32_t l0 = pack_bf16(u0.x - bf_lo(h0), u0.y - bf_hi(h0)), l1 = pack_bf16(u1.x - bf_lo(h1), u1.y - bf_hi(h1));
            g_qabs[((id >> 2) * 4 + (bi >> 3)) * 32 + (bi & 7) * 4 + (id & 3)] = make_uint4(h0, l0, h1, l1);
        }
    }
    b_exchange(&ctl[C_BBAR][0], BS_Q, &g_qabs[(bi >> 3) * 4096], sbase, pol);
    {
        uint32_t qf[4][4][4];
        b_wait(BS_Q + (warp >> 2), sbase);
        TS(7);
        {
            const uint4* qs = reinterpret_cast<const uint4*>(smem + ((BS_Q + (warp >> 2)) % BRING) * SLOT) + (warp & 3) * 512 + lane;
#pragma unroll
            for (int s = 0; s < 4; s++)
#pragma unroll
                for (int i = 0; i < 4; i++) {
                    const uint4 v = qs[(s * 4 + i) * 32];
                    qf[i][s][0] = v.x; qf[i][s][1] = v.y; qf[i][s][2] = v.z; qf[i][s][3] = v.w;
                }
        }
        __syncthreads();
        if (tid == 0) { b_issue(p, BS_Q + BD, bi, sbase, pol); b_issue(p, BS_Q + 1 + BD, bi, sbase, pol); }
        float acc[2][8][4];
#pragma unroll
        for (int i = 0; i < 2; i++)
#pragma unroll
            for (int j = 0; j < 8; j++) { acc[i][j][0] = acc[i][j][1] = acc[i][j][2] = acc[i][j][3] = 0.f; }
        float mrun = -INFINITY, lrun = 0.f;
        const int head = tid >> 3, kq = tid & 7;
        float* alpha = reinterpret_cast<float*>(smem + M_ALPHA);
        for (int n = BS_CKV; n < BS_PART; n++) {
            b_wait(n, sbase);
            const uint32_t slot = sbase + (n % BRING) * SLOT;
            float sc[4][4][4];
#pragma unroll
            for (int i = 0; i < 4; i++)
#pragma unroll
                for (int j = 0; j < 4; j++) { sc[i][j][0] = sc[i][j][1] = sc[i][j][2] = sc[i][j][3] = 0.f; }
#pragma unroll
            for (int j = 0; j < 4; j++)
#pragma unroll
                for (int sp = 0; sp < 2; sp++) {
                    uint32_t bf[4];
                    ldsm4(bf, slot + warp * 4096 + (8 * j + (lane & 7)) * 128 + (((4 * sp + (lane >> 3)) ^ (lane & 7)) * 16));
#pragma unroll
                    for (int i = 0; i < 4; i++) {
                        mma16816(sc[i][j], qf[i][2 * sp], bf[0], bf[1]);
                        mma16816(sc[i][j], qf[i][2 * sp + 1], bf[2], bf[3]);
                    }
                }
#pragma unroll
            for (int i = 0; i < 4; i++)
#pragma unroll
                for (int j = 0; j < 4; j++)
                    *reinterpret_cast<float2*>(red + warp * 1024 + (8 * i + g) * 32 + ((8 * j) ^ (8 * (g & 3))) + 2 * t) =
                        make_float2(sc[i][j][0] + sc[i][j][2], sc[i][j][1] + sc[i][j][3]);
            __syncthreads();
            if (tid == 0 && n > BS_CKV) b_issue(p, n - 1 + BD, bi, sbase, pol);
            {
                float4 s = make_float4(0.f, 0.f, 0.f, 0.f);
#pragma unroll
                for (int w = 0; w < 8; w++) {
                    const float4 v = *reinterpret_cast<const float4*>(red + w * 1024 + head * 32 + ((4 * kq) ^ (8 * (head & 3))));
                    s.x += v.x; s.y += v.y; s.z += v.z; s.w += v.w;
                }
                const uint32_t r0 = pack_bf16(s.x, s.y), r1 = pack_bf16(s.z, s.w);
                const uint32_t s0 = pack_bf16(bf_lo(r0) * SCALE, bf_hi(r0) * SCALE);
                const uint32_t s1 = pack_bf16(bf_lo(r1) * SCALE, bf_hi(r1) * SCALE);
                const float f0 = bf_lo(s0), f1 = bf_hi(s0), f2 = bf_lo(s1), f3 = bf_hi(s1);
                float mx = fmaxf(fmaxf(f0, f1), fmaxf(f2, f3));
                mx = fmaxf(mx, __shfl_xor_sync(~0u, mx, 1));
                mx = fmaxf(mx, __shfl_xor_sync(~0u, mx, 2));
                mx = fmaxf(mx, __shfl_xor_sync(~0u, mx, 4));
                const float mnew = fmaxf(mrun, mx);
                const float al = expsub(mrun, mnew);
                const float p0 = expsub(f0, mnew), p1 = expsub(f1, mnew), p2 = expsub(f2, mnew), p3 = expsub(f3, mnew);
                lrun = lrun * al + ((p0 + p1) + (p2 + p3));
                mrun = mnew;
                *reinterpret_cast<uint2*>(smem + M_P + head * 80 + kq * 8) = make_uint2(pack_bf16(p0, p1), pack_bf16(p2, p3));
                if (kq == 0) alpha[head] = al;
            }
            __syncthreads();
            {
                uint32_t pf[2][2][4];
#pragma unroll
                for (int i = 0; i < 2; i++)
#pragma unroll
                    for (int ks = 0; ks < 2; ks++)
                        ldsm4(pf[i][ks], sbase + M_P + (16 * i + (lane & 15)) * 80 + (16 * ks + 8 * (lane >> 4)) * 2);
#pragma unroll
                for (int i = 0; i < 2; i++) {
                    const float a0 = alpha[16 * i + g], a1 = alpha[16 * i + 8 + g];
#pragma unroll
                    for (int j = 0; j < 8; j++) { acc[i][j][0] *= a0; acc[i][j][1] *= a0; acc[i][j][2] *= a1; acc[i][j][3] *= a1; }
                }
#pragma unroll
                for (int j = 0; j < 8; j++) {
                    uint32_t bf[4];
                    ldsm4t(bf, slot + warp * 4096 + lane * 128 + ((j ^ (lane & 7)) * 16));
#pragma unroll
                    for (int i = 0; i < 2; i++) {
                        mma16816(acc[i][j], pf[i][0], bf[0], bf[1]);
                        mma16816(acc[i][j], pf[i][1], bf[2], bf[3]);
                    }
                }
            }
        }
        __syncthreads();
        if (tid == 0) b_issue(p, BS_PART - 1 + BD, bi, sbase, pol);
        lrun += __shfl_xor_sync(~0u, lrun, 1);
        lrun += __shfl_xor_sync(~0u, lrun, 2);
        lrun += __shfl_xor_sync(~0u, lrun, 4);
        if (kq == 0) g_bml[head * NBCTA + bi] = make_float2(mrun, lrun);
#pragma unroll
        for (int i = 0; i < 2; i++)
#pragma unroll
            for (int j = 0; j < 8; j++) {
                g_bpart[((16 * i + g) * NBCTA + bi) * 256 + warp * 32 + j * 4 + t] = make_float2(acc[i][j][0], acc[i][j][1]);
                g_bpart[((16 * i + 8 + g) * NBCTA + bi) * 256 + warp * 32 + j * 4 + t] = make_float2(acc[i][j][2], acc[i][j][3]);
            }
    }
    if (!CLU) {
#pragma unroll 1
        for (int i = tid; i < NH * 36; i += 256) g_outb[bi * NH * 36 + i] = make_uint4(0u, epoch, 0u, epoch);
    }
    b_exchange(&ctl[C_BBAR + 1][0], BS_PART, &g_bpart[bi * NBCTA * 256], sbase, pol);
    {
        float* omega = reinterpret_cast<float*>(smem + M_OMEGA);
        if (warp == 0) {
            __syncwarp();
            const uint2 ml = ld_relaxed8(&g_bml[bi * NBCTA + lane]);
            const float ms = __uint_as_float(ml.x);
            float m = ms;
            m = fmaxf(m, __shfl_xor_sync(~0u, m, 1));
            m = fmaxf(m, __shfl_xor_sync(~0u, m, 2));
            m = fmaxf(m, __shfl_xor_sync(~0u, m, 4));
            const float w = expsub(ms, m);
            float l = w * __uint_as_float(ml.y);
            l += __shfl_xor_sync(~0u, l, 1);
            l += __shfl_xor_sync(~0u, l, 2);
            l += __shfl_xor_sync(~0u, l, 4);
            omega[lane] = w / l;
        }
        __syncthreads();
        b_wait(BS_PART, sbase);
        b_wait(BS_PART + 1, sbase);
#pragma unroll 1
        for (int b = 0; b < 4; b++) {
            const float2* ps = reinterpret_cast<const float2*>(smem + ((BS_PART + (b >> 1)) % BRING) * SLOT) + (b & 1) * 2048 + tid;
            float c0 = 0.f, c1 = 0.f;
#pragma unroll
            for (int s = 0; s < 8; s++) {
                const float w = omega[b * 8 + s];
                const float2 v = ps[s * 256];
                c0 = fmaf(w, v.x, c0);
                c1 = fmaf(w, v.y, c1);
            }
            const uint32_t hi = pack_bf16(c0, c1);
            *reinterpret_cast<uint32_t*>(smem + M_CH + b * CP + tid * 4) = hi;
            *reinterpret_cast<uint32_t*>(smem + M_CL + b * CP + tid * 4) = pack_bf16(c0 - bf_lo(hi), c1 - bf_hi(hi));
        }
        __syncthreads();
        if (tid == 0) { b_issue(p, BS_PART + BD, bi, sbase, pol); b_issue(p, BS_PART + 1 + BD, bi, sbase, pol); }
    }
    b_gemm(p, sbase, BS_WUV, BS_END, 512, sbase + M_CH, sbase + M_CL, CP, bi, pol);
    TS(12);
    if (CLU) {
        if (warp < 4) {
            const unsigned short* c = reinterpret_cast<const unsigned short*>(smem + M_QB + warp * QP) + 16 * t + g;
            g_octx[(bi * 4 + warp) * 32 + lane] = make_float4(bf_lo(c[0]), bf_lo(c[8]), bf_lo(c[64]), bf_lo(c[72]));
        }
        __syncthreads();
        if (tid == 0) asm volatile("st.release.gpu.global.u32 [%0], %1;" ::"l"(&g_cdone[bi][0]), "r"(epoch + 1) : "memory");
        return;
    }
    if (tid == 0) {
#pragma unroll 1
        for (int i = 0; i < 4; i++) {
            mbar_expect_tx(sbase + M_BAR + i * 8, 36864);
            tma3d(sbase + i * 36864, &p.tm_wo, 0, bi * 128 + i * 32, 0, sbase + M_BAR + i * 8, pol);
        }
    }
    TS(8);
    {
        float acc[9][4];
#pragma unroll
        for (int j = 0; j < 9; j++) { acc[j][0] = acc[j][1] = acc[j][2] = acc[j][3] = 0.f; }
#pragma unroll 1
        for (int i = 0; i < 4; i++) {
            const uint32_t xo = sbase + M_QB + (g & 3) * QP + i * 64 + t * 4;
            const uint32_t a0[4] = {lds32(xo), 0u, lds32(xo + 16), 0u}, a1[4] = {lds32(xo + 32), 0u, lds32(xo + 48), 0u};
            mbar_wait(sbase + M_BAR + i * 8, 0);
#pragma unroll
            for (int j = 0; j < 9; j++) {
                const int nt = warp * 9 + j;
                uint32_t w[4];
                ldsm4t(w, sbase + i * 36864 + (nt >> 3) * 4096 + lane * 128 + (((nt & 7) ^ (lane & 7)) * 16));
                mma16816(acc[j], a0, w[0], w[1]);
                mma16816(acc[j], a1, w[2], w[3]);
            }
        }
        if (g < 4) {
#pragma unroll
            for (int j = 0; j < 9; j++) {
                const int c2 = (warp * 9 + j) * 4 + t;
                st_tagged2(&g_outb[((c2 / 9) * NH + bi) * 36 + g * 9 + c2 % 9], acc[j][0], acc[j][1], epoch + 1);
            }
        }
    }
    TS(9);
    {
        const uint4* src = g_outb + (bi * NH + (tid >> 3)) * 36 + (tid & 7);
        float2* part = reinterpret_cast<float2*>(red);
        unsigned n = 0;
        while (true) {
            ulonglong2 v[5];
            bool ok = true;
#pragma unroll
            for (int i = 0; i < 5; i++)
                if (i < 4 || (tid & 7) < 4) v[i] = ld_tagged2(src + i * 8);
#pragma unroll
            for (int i = 0; i < 5; i++)
                if (i < 4 || (tid & 7) < 4) {
                    ok = ok && (unsigned)(v[i].x >> 32) == epoch + 1 && (unsigned)(v[i].y >> 32) == epoch + 1;
                    part[(tid >> 3) * 36 + (tid & 7) + i * 8] = make_float2(__uint_as_float((unsigned)v[i].x), __uint_as_float((unsigned)v[i].y));
                }
            if (ok) break;
            __nanosleep(400);
            if (++n > SPIN_LIMIT) __trap();
        }
        __syncthreads();
        if (tid < 36) {
            float s0 = 0.f, s1 = 0.f;
#pragma unroll 8
            for (int h = 0; h < NH; h++) { const float2 v = part[h * 36 + tid]; s0 += v.x; s1 += v.y; }
            *reinterpret_cast<uint32_t*>(p.out + (tid / 9) * 2 * DM + DM + bi * 18 + (tid % 9) * 2) = pack_bf16(s0, s1);
        }
    }
    TS(10);
}

template <bool CLU>
__global__ void __launch_bounds__(256, 1) fused_decode_kernel(const __grid_constant__ Params p) {
    asm volatile("{\n.reg .pred p;\n.reg .u32 a;\n.reg .u64 b;\nsub.u32 a, %1, %4;\nsetp.lt.u32 p, a, %3;\nmad.lo.u32 a, %2, %3, %1;\n"
                 "mad.wide.u32 b, a, %5, %0;\n@p prefetch.global.L2 [b];\n}"
                 ::"l"(p.kc), "r"(threadIdx.x), "r"(blockIdx.x), "n"(PFN), "n"(PF0), "n"(PFS) : "memory");
    if (blockIdx.x >= 1024) return;
    extern __shared__ __align__(1024) char smem_raw[];
    const uint32_t sbase = (smem_u32(smem_raw) + 1023u) & ~1023u;
    char* smem = smem_raw + (sbase - smem_u32(smem_raw));
    const int tid = threadIdx.x, warp = __shfl_sync(~0u, tid >> 5, 0), lane = tid & 31;
    const int blk = blockIdx.x;
    const bool isB = CLU ? blk < NBCTA : (blk & 3) == 0 && (blk >> 2) < NBCTA;
    const int bi = CLU ? blk : blk >> 2;
    const int nb = CLU ? blk - NBCTA : blk - min(NBCTA, (blk + 3) >> 2);
    const int nblk = CLU ? 8 * MINCL : gridDim.x, nnb = nblk - NBCTA;
    const int nstatic = nnb * (NW + XW);
    uint64_t pol;
    asm volatile("createpolicy.fractional.L2::evict_first.b64 %0, 1.0;" : "=l"(pol));
    const uint32_t wbar = sbase + M_BAR + warp * 8, wslot = sbase + warp * SLOT;
    const int u0 = warp * nnb + nb;
    const bool hold = ((blk >> 2) >> KMIN << KMIN) * 4 * UPP < nstatic;
    const uint32_t jbar = sbase + M_BAR + (NSLOT + BRING) * 8;
    if (warp < 4) {
        mbar_init_warp(wbar);
        if (warp < NEARLY && !isB && !hold)
            tile_load_warp(wslot, reinterpret_cast<const char*>(p.kc) + (size_t)((u0 >> 7) * 1024 + (u0 & 127)) * TILE_BYTES, wbar, pol);
    }
    asm volatile("" ::: "memory");
    if (warp == 7) {
        if (blk < 128) {
            uint64_t poln;
            asm volatile("createpolicy.fractional.L2::evict_normal.b64 %0, 1.0;" : "=l"(poln));
            mbar_init_warp(jbar);
            tma3d_warp(sbase + J0W, &p.tm_j0, blk * 32, 0, 0, jbar, 36864 + 4 * 1152, poln);
            if (lane == 0) bulk_load(sbase + M_XA, p.xa, 4608, jbar, poln);
        }
        if (lane < 8) reinterpret_cast<unsigned*>(smem + M_HELP)[lane] = 0;
        __syncwarp();
        if (!isB) asm volatile("bar.arrive 2, %0;" ::"n"(32 * (NW + XW + 1)) : "memory");
    }
    unsigned epoch = 0;
    if (lane == 0) epoch = ld_relaxed4(&g_epoch);
    TS(0);
    if (CLU) {
        if (warp == 6) {
            if (lane < 16 && lane != 1) mbar_init(sbase + F_BAR + lane * 8, 1);
            if ((lane >> 1) == 1) mbar_expect_tx(sbase + F_BAR + lane * 8, 1024);
            asm volatile("fence.mbarrier_init.release.cluster;" ::: "memory");
        }
        asm volatile("barrier.cluster.arrive.relaxed.aligned;" ::: "memory");
    }
    if ((warp >> 1) == 2 && blk < 128) st_relaxed64(&g_qll[((tid - 128) >> 4) * 2048 + blk * 16 + (tid & 15)], 0ull);
    if (isB || warp >= NW + XW) epoch = __shfl_sync(~0u, epoch, 0);
    if (isB && warp == 3) asm volatile("bar.sync 1, 160;" ::: "memory");
    if (isB && tid == 96) {
#pragma unroll 1
        for (int i = 0; i < BRING; i++) mbar_init(sbase + M_BAR + (NSLOT + i) * 8, 1);
        asm volatile("fence.mbarrier_init.release.cluster;" ::: "memory");
        if (hold) { unsigned n = 0; while (ld_acquire_cta_shared(sbase + M_HELP + 24) < 2) { if (++n > (SPIN_LIMIT << 4)) __trap(); } }
#pragma unroll 1
        for (int b = 0; b < 4; b++) bulk_load(sbase + M_XB + b * XP, p.xb + b * DM, 1152, sbase + M_BAR + NSLOT * 8, pol);
#pragma unroll 1
        for (int n = 0; n < BD; n++) b_issue(p, n, bi, sbase, pol);
    }
    if (warp >= 4 && blk < 128) {
        const int g = lane >> 2, t = lane & 3, j = tid - 128;
        asm volatile("bar.sync 1, %0;" ::"r"(isB ? 160 : 128) : "memory");
#pragma unroll 1
        for (int sl = blk, ph = 0;; sl += 128 - nblk, ph = 1) {
        mbar_wait(jbar, ph);
        TS(13);
        float acc[4][4];
#pragma unroll
        for (int i = 0; i < 16; i++) acc[i >> 2][i & 3] = 0.f;
        const uint32_t wa = sbase + J0W + ((warp - 4) * 144 + (lane & 15)) * 64;
        const uint32_t sw = (lane >> 1) & 3, xa = sbase + M_XA + (g & 3) * 1152 + (warp - 4) * 288 + t * 4;
#pragma unroll 3
        for (int s = 0; s < 9; s++) {
            const uint32_t a[4] = {lds32(xa + s * 32), 0u, lds32(xa + s * 32 + 16), 0u};
            uint32_t w0[4], w1[4];
            ldsm4t(w0, wa + s * 1024 + (((lane >> 4) ^ sw) * 16));
            ldsm4t(w1, wa + s * 1024 + (((2 + (lane >> 4)) ^ sw) * 16));
            mma16816(acc[0], a, w0[0], w0[1]);
            mma16816(acc[1], a, w0[2], w0[3]);
            mma16816(acc[2], a, w1[0], w1[1]);
            mma16816(acc[3], a, w1[2], w1[3]);
        }
        float2* j0 = reinterpret_cast<float2*>(smem + M_J0);
        if (g < 4) {
#pragma unroll
            for (int i = 0; i < 4; i++) j0[(warp - 4) * 64 + g * 16 + i * 4 + t] = make_float2(acc[i][0], acc[i][1]);
        }
        asm volatile("bar.sync 1, 128;" ::: "memory");
        const bool again = sl == blk && blk + 128 - nblk >= nblk;
        if (again && tid == 224) {
            mbar_expect_tx(jbar, 36864);
            tma3d(sbase + J0W, &p.tm_j0, (blk + 128 - nblk) * 32, 0, 0, jbar, pol);
        }
        if (warp < 6) {
            const float2 v0 = j0[j], v1 = j0[64 + j], v2 = j0[128 + j], v3 = j0[192 + j];
            st_relaxed64(&g_qll[(j >> 4) * 2048 + sl * 16 + (j & 15)],
                         (unsigned long long)pack_bf16((v0.x + v1.x) + (v2.x + v3.x), (v0.y + v1.y) + (v2.y + v3.y)) |
                             ((unsigned long long)(epoch + 1) << 32));
            __syncwarp();
            if (lane == 0) asm volatile("red.relaxed.cta.shared::cta.add.u32 [%0], 1;" ::"r"(sbase + M_HELP + 24) : "memory");
        } else if (warp == 7) {
            if (blk < C_LINES) g_ctl[(epoch & 1) ^ 1][blk][lane] = 0;
        }
        TS(1);
        if (!again) break;
        asm volatile("bar.sync 1, 128;" ::: "memory");
        }
    }
    const int cl = blk >> 3, rank = blk & 7;
    const bool partA = CLU && cl >= 4 && cl < 13;
    if (isB) {
        b_chain<CLU>(p, smem, sbase, bi, epoch, pol);
        if (!CLU) return;
    } else if (warp < NW + XW) {
        a_worker<CLU>(p, u0, warp >= NW + ((CLU ? rank < X3C : (nb & 3) < X3) ? 1 : 0), warp < NEARLY && !hold, hold, nstatic, wslot, wbar, sbase + M_HELP,
                      epoch, pol);
        if (!CLU || warp < (partA && rank == 7 ? 2 : 3)) return;
        epoch = __shfl_sync(~0u, epoch, 0);
        unsigned n = 0;
        while (ld_acquire_cta_shared(sbase + M_HELP + 12) == 0) { __nanosleep(1000); if (++n > SPIN_LIMIT) __trap(); }
    } else if (warp == 7) {
#pragma unroll 1
        for (int i = nb; i < 4 * NH; i += nnb) g_oacc[i * 32 + lane] = make_float4(0.f, 0.f, 0.f, 0.f);
        if (nb < NREP * NH) g_vdone[nb][lane] = 0;
        __syncwarp();
        k_helper(sbase + M_HELP, epoch);
        if (nb == 0 && lane == 0) g_epoch = epoch + 1;
        __syncwarp();
    } else if (!CLU && nb < NFIN) {
        if (warp == 6) {
            finisher(p, sbase, nb);
            TS(4);
        } else if (warp >= 6 - NPOLL) {
            v_poller(sbase, nb, warp - (6 - NPOLL));
        }
    }
    if (!CLU || cl > 13) return;
    asm volatile("barrier.cluster.wait.acquire.aligned;" ::: "memory");
    if (isB ? warp == 0 : warp < 4) {
        f_collect((partA ? g_vdone : g_cdone) + 4 * rank, partA ? 4 * UPP : epoch + 1, (partA ? g_oacc : g_octx) + 4 * rank * 128,
                  partA && rank == 7 ? (warp == 2 ? CM2 : 15 - CM2) : 15, sbase);
        if (warp == 2) return;
    }
    const int sl = isB ? warp >> 2 : 0, panel = isB ? 2 * cl + sl : min(cl - 4, 8);
#pragma unroll 1
    for (int i = 0;; i++) {
        if (isB ? (warp & 3) == 0 : warp == 3) f_receive(p.out + (partA ? 0 : DM) + panel * 64 + rank * 8, sl, i == 0, sbase);
        if (i) return;
        if (isB || warp >= 4)
            f_project(partA ? &p.tm_fa : &p.tm_fb, panel, rank, warp, sl,
                      isB ? B0 + (warp & 3) * BJ + sl * BS + rank * BR : A0 + (warp & 3) * AJ + rank * AR, epoch + 1, sbase, pol);
    }
}

}

typedef CUresult (*EncodeFn)(CUtensorMap*, CUtensorMapDataType, cuuint32_t, void*, const cuuint64_t*, const cuuint64_t*,
                             const cuuint32_t*, const cuuint32_t*, CUtensorMapInterleave, CUtensorMapSwizzle,
                             CUtensorMapL2promotion, CUtensorMapFloatOOBfill);

extern "C" void kernel_launch(void* const* d_in, const int* in_sizes, int n_in, void* d_out, int out_size) {
    (void)in_sizes; (void)n_in; (void)out_size;
    static int nsm = 0, ncl = 0;
    static EncodeFn encode = nullptr;
    cudaLaunchConfig_t cfg = {};
    cudaLaunchAttribute at[1];
    at[0].id = cudaLaunchAttributeClusterDimension;
    at[0].val.clusterDim.x = 8; at[0].val.clusterDim.y = 1; at[0].val.clusterDim.z = 1;
    cfg.blockDim = dim3(256); cfg.dynamicSmemBytes = SMEM_BYTES; cfg.stream = cudaStreamPerThread; cfg.attrs = at; cfg.numAttrs = 1;
    if (nsm == 0) {
        int dev = 0;
        cudaGetDevice(&dev);
        cudaDeviceGetAttribute(&nsm, cudaDevAttrMultiProcessorCount, dev);
        cudaFuncSetAttribute(fused_decode_kernel<false>, cudaFuncAttributeMaxDynamicSharedMemorySize, SMEM_BYTES);
        cudaFuncSetAttribute(fused_decode_kernel<true>, cudaFuncAttributeMaxDynamicSharedMemorySize, SMEM_BYTES);
        cfg.gridDim = dim3(128);
        if (cudaOccupancyMaxActiveClusters(&ncl, fused_decode_kernel<true>, &cfg) != cudaSuccess) { ncl = 0; (void)cudaGetLastError(); }
        if (ncl > MINCL) ncl = MINCL;
        void* fn = nullptr;
        cudaDriverEntryPointQueryResult qr;
        cudaGetDriverEntryPoint("cuTensorMapEncodeTiled", &fn, cudaEnableDefault, &qr);
        encode = (EncodeFn)fn;
    }
    Params p;
    auto panels = [&](CUtensorMap* tm, void* ptr, int rows, int cols, int box_rows, int box_panels,
                      CUtensorMapL2promotion promo = CU_TENSOR_MAP_L2_PROMOTION_L2_256B) {
        const cuuint64_t gd[3] = {64, (cuuint64_t)rows, (cuuint64_t)(cols / 64)}, gs[2] = {(cuuint64_t)cols * 2, 128};
        const cuuint32_t box[3] = {64, (cuuint32_t)box_rows, (cuuint32_t)box_panels}, es[3] = {1, 1, 1};
        encode(tm, CU_TENSOR_MAP_DATA_TYPE_BFLOAT16, 3, ptr, gd, gs, box, es, CU_TENSOR_MAP_INTERLEAVE_NONE,
               CU_TENSOR_MAP_SWIZZLE_128B, promo, CU_TENSOR_MAP_FLOAT_OOB_FILL_NONE);
    };
    panels(&p.tm_wq, d_in[7], DM, 4096, 128, 2);
    panels(&p.tm_wuk, d_in[8], 512, 4096, 128, 2);
    panels(&p.tm_wuv, d_in[9], 512, 4096, 128, 2);
    panels(&p.tm_wo, d_in[10], 4096, DM, 32, 9);
    panels(&p.tm_ckv, d_in[6], 4 * SK, 512, 32, 8);
    panels(&p.tm_fa, d_in[4], 4096, DM, 128, 1, CU_TENSOR_MAP_L2_PROMOTION_L2_128B);
    panels(&p.tm_fb, d_in[10], 4096, DM, 128, 1, CU_TENSOR_MAP_L2_PROMOTION_L2_128B);
    {
        const cuuint64_t gd[3] = {4096, 192, 3}, gs[2] = {8192, 192 * 8192};
        const cuuint32_t box[3] = {32, 192, 3}, es[3] = {1, 1, 1};
        encode(&p.tm_j0, CU_TENSOR_MAP_DATA_TYPE_BFLOAT16, 3, d_in[3], gd, gs, box, es, CU_TENSOR_MAP_INTERLEAVE_NONE,
               CU_TENSOR_MAP_SWIZZLE_64B, CU_TENSOR_MAP_L2_PROMOTION_L2_128B, CU_TENSOR_MAP_FLOAT_OOB_FILL_NONE);
    }
    p.xa = (const __nv_bfloat16*)d_in[0];
    p.kc = (const __nv_bfloat16*)d_in[1];
    p.vc = (const __nv_bfloat16*)d_in[2];
    p.wo = (const __nv_bfloat16*)d_in[4];
    p.xb = (const __nv_bfloat16*)d_in[5];
    p.out = (__nv_bfloat16*)d_out;
    if (ncl >= MINCL) {
        cfg.gridDim = dim3(8 * ncl);
        cudaLaunchKernelEx(&cfg, fused_decode_kernel<true>, p);
    } else {
        fused_decode_kernel<false><<<nsm, 256, SMEM_BYTES, cudaStreamPerThread>>>(p);
    }
}
```

```cpp
#include <cuda_runtime.h>
#include <cuda.h>
#include <cuda_bf16.h>
#include <stdint.h>

namespace {

constexpr int NH = 32, SK = 4096, DM = 576;
constexpr int KEYS = 128;
constexpr int UPP = SK / KEYS;
constexpr int NUK = 4 * NH * UPP;
constexpr int TILE_BYTES = KEYS * 256;
#define NWORK 2
constexpr int NW = NWORK;
constexpr int NBCTA = 32;
constexpr int MINCL = 15;
constexpr int NFIN = 72;
constexpr int SLOT = 32768;
constexpr int NSLOT = 6;
constexpr int BRING = 5;
constexpr int J0W = 5 * SLOT;
constexpr int MISC = NSLOT * SLOT + 4096;
constexpr int XP = 1168, CP = 1040, QP = 272;
constexpr int M_XA = MISC;
constexpr int M_XB = M_XA + 4 * XP;
constexpr int M_CH = M_XB + 4 * XP;
constexpr int M_CL = M_CH + 4 * CP;
constexpr int M_QB = M_CL + 4 * CP;
constexpr int M_QA = M_CH;
constexpr int M_J0 = M_QB + 4 * QP;
constexpr int M_P = M_J0 + 2048;
constexpr int M_ALPHA = M_P + 2560;
constexpr int M_OMEGA = M_ALPHA + 128;
constexpr int M_BAR = M_OMEGA + 128;
constexpr int M_HELP = M_BAR + 128;
constexpr int F_W = 4 * SLOT;
constexpr int F_BF = (M_HELP + 383) / 256 * 256;
constexpr int F_RX = F_BF + 4096;
constexpr int F_BAR = F_RX + 2048;
constexpr int SMEM_BYTES = F_BAR + 128 + 1024;
static_assert(SMEM_BYTES <= 232448 && M_BAR % 8 == 0 && M_QA % 16 == 0 && M_P % 16 == 0, "smem layout");
#define XW 2
#define X3 1
#define X3C 5
#define NEARLY 2
#define BD 5
#define FPF 3
#define FSLEEP 800
#define VS0 24
#define PFN 96
#define EARLY 100
#define ELOG 5
#define TPU 159
#define A0 (2000 + 185 * X3C)
#define AJ 700
#define B0 (A0 - 500)
#define BJ 700
#define BS 300
#define LAG 2
#define NPOLL 2
#define PGAP 200
static_assert(X3C <= 7 && NW == 2, "warp 2 of rank 7 is free");
static_assert(NW + XW <= 4 && NEARLY <= NW + XW && BD <= BRING, "slots 4 and 5 hold the finisher weights");
constexpr int KMIN = 2, KMAX = 4, VMIN = 0, VMAX = 4;
constexpr float SCALE = 0.08838834764831845f;
constexpr float LOG2E = 1.4426950408889634f;
constexpr unsigned SPIN_LIMIT = 1u << 24;

#define NREP 2
#define NREPC 1
constexpr int C_QUEUE = 0, C_KDONE = 1, C_BBAR = 3, C_LINES = 5;

struct Scratch {
    unsigned epoch[32];
    unsigned ctl[2][C_LINES][32];
    uint2 qll[4 * 2048];
    uint2 scores[128 * SK / 4];
    float2 stats[128 * UPP];
    float4 oacc[128 * 32];
    unsigned vdone[NREP * NH][32];
    float4 octx[128 * 32];
    unsigned cdone[NH][32];
    unsigned long long dry[16][16];
    uint4 qabs[4 * 8 * 4 * 4 * 32];
    float2 bpart[NBCTA * NH * 256];
    float2 bml[NBCTA * NH];
    uint4 outb[NBCTA * NH * 36];
};
__device__ __align__(256) Scratch g_scratch;

struct Params {
    const __nv_bfloat16 *kc, *xa, *vc, *wo, *xb;
    __nv_bfloat16* out;
    Scratch* s;
    CUtensorMap tm_j0;
    CUtensorMap tm_wq, tm_wuk, tm_ckv, tm_wuv, tm_wo;
    CUtensorMap tm_fa, tm_fb;
};

__device__ __forceinline__ Scratch* scratch(const Params& p) {
    Scratch* s = p.s;
    __builtin_assume(__isGlobal(s));
    return s;
}

#define STI(v)
#define TS(i)
#define TSV(i, v)
#define LAND(i)
#define CLK(x)
#define ACC(a, x, y)

__device__ __forceinline__ uint32_t smem_u32(const void* p) { return (uint32_t)__cvta_generic_to_shared(p); }
__device__ __forceinline__ void mbar_init(uint32_t bar, uint32_t cnt) {
    asm volatile("mbarrier.init.shared::cta.b64 [%0], %1;" ::"r"(bar), "r"(cnt) : "memory");
}
__device__ __forceinline__ void mbar_expect_tx(uint32_t bar, uint32_t bytes) {
    asm volatile("mbarrier.arrive.expect_tx.shared::cta.b64 _, [%0], %1;" ::"r"(bar), "r"(bytes) : "memory");
}
__device__ __forceinline__ bool mbar_try(uint32_t bar, uint32_t parity) {
    uint32_t ok;
    asm volatile("{\n.reg .pred p;\nmbarrier.try_wait.parity.shared::cta.b64 p, [%1], %2;\nselp.u32 %0, 1, 0, p;\n}\n"
                 : "=r"(ok) : "r"(bar), "r"(parity) : "memory");
    return ok;
}
__device__ __forceinline__ void mbar_wait(uint32_t bar, uint32_t parity) {
    unsigned n = 0;
    while (!mbar_try(bar, parity)) { if (++n > SPIN_LIMIT) __trap(); }
}
__device__ __forceinline__ void mbar_spin(uint32_t bar) {
    asm volatile("{\n.reg .pred p;\n.reg .u32 n;\nmov.u32 n, 0;\nSPIN:\nmbarrier.try_wait.parity.shared::cta.b64 p, [%0], 0;\n@p bra.uni DONE;\n"
                 "add.u32 n, n, 1;\nsetp.lt.u32 p, n, 0x1000000;\n@p bra.uni SPIN;\ntrap;\nDONE:\n}" ::"r"(bar) : "memory");
}
__device__ __forceinline__ void mbar_spin_cluster(uint32_t bar) {
    asm volatile("{\n.reg .pred p;\n.reg .u32 n;\nmov.u32 n, 0;\nSPIN:\nmbarrier.try_wait.parity.relaxed.cluster.shared::cta.b64 p, [%0], 0;\n"
                 "@p bra.uni DONE;\nadd.u32 n, n, 1;\nsetp.lt.u32 p, n, 0x1000000;\n@p bra.uni SPIN;\ntrap;\nDONE:\n"
                 "fence.acquire.sync_restrict::shared::cluster.cluster;\n}" ::"r"(bar) : "memory");
}
__device__ __forceinline__ void bulk_load(uint32_t dst, const void* src, uint32_t bytes, uint32_t bar, uint64_t pol) {
    asm volatile("cp.async.bulk.shared::cluster.global.mbarrier::complete_tx::bytes.L2::cache_hint [%0], [%1], %2, [%3], %4;"
                 ::"r"(dst), "l"(src), "r"(bytes), "r"(bar), "l"(pol) : "memory");
}
__device__ __forceinline__ void mbar_init_warp(uint32_t bar) {
    asm volatile("{\n.reg .pred p;\nelect.sync _|p, 0xffffffff;\n@p mbarrier.init.shared::cta.b64 [%0], 1;\n@p fence.mbarrier_init.release.cluster;\n}"
                 ::"r"(bar) : "memory");
}
__device__ __forceinline__ void tile_load_warp(uint32_t dst, const void* src, uint32_t bar, uint64_t pol) {
    asm volatile("{\n.reg .pred p;\nelect.sync _|p, 0xffffffff;\n@p mbarrier.arrive.expect_tx.shared::cta.b64 _, [%2], %4;\n"
                 "@p cp.async.bulk.shared::cluster.global.mbarrier::complete_tx::bytes.L2::cache_hint [%0], [%1], %4, [%2], %3;\n}"
                 ::"r"(dst), "l"(src), "r"(bar), "l"(pol), "n"(TILE_BYTES) : "memory");
}
__device__ __forceinline__ void tma3d_warp(uint32_t dst, const CUtensorMap* tm, int c0, int c1, int c2, uint32_t bar, uint32_t bytes, uint64_t pol) {
    asm volatile("{\n.reg .pred p;\nelect.sync _|p, 0xffffffff;\n@p mbarrier.arrive.expect_tx.shared::cta.b64 _, [%2], %7;\n"
                 "@p cp.async.bulk.tensor.3d.shared::cluster.global.mbarrier::complete_tx::bytes.L2::cache_hint [%0], [%1, {%3,%4,%5}], [%2], %6;\n}"
                 ::"r"(dst), "l"(tm), "r"(bar), "r"(c0), "r"(c1), "r"(c2), "l"(pol), "r"(bytes) : "memory");
}
__device__ __forceinline__ void tma3d(uint32_t dst, const CUtensorMap* tm, int c0, int c1, int c2, uint32_t bar, uint64_t pol) {
    asm volatile("cp.async.bulk.tensor.3d.shared::cluster.global.mbarrier::complete_tx::bytes.L2::cache_hint [%0], [%1, {%3,%4,%5}], [%2], %6;"
                 ::"r"(dst), "l"(tm), "r"(bar), "r"(c0), "r"(c1), "r"(c2), "l"(pol) : "memory");
}
__device__ __forceinline__ void l2_prefetch(const void* src, uint32_t bytes) {
    asm volatile("cp.async.bulk.prefetch.L2.global [%0], %1;" ::"l"(src), "r"(bytes) : "memory");
}
__device__ __forceinline__ void ldsm4(uint32_t (&r)[4], uint32_t addr) {
    asm volatile("ldmatrix.sync.aligned.m8n8.x4.shared.b16 {%0,%1,%2,%3}, [%4];"
                 : "=r"(r[0]), "=r"(r[1]), "=r"(r[2]), "=r"(r[3]) : "r"(addr));
}
__device__ __forceinline__ void ldsm4t(uint32_t (&r)[4], uint32_t addr) {
    asm volatile("ldmatrix.sync.aligned.m8n8.x4.trans.shared.b16 {%0,%1,%2,%3}, [%4];"
                 : "=r"(r[0]), "=r"(r[1]), "=r"(r[2]), "=r"(r[3]) : "r"(addr));
}
__device__ __forceinline__ void mma16816(float (&d)[4], const uint32_t (&a)[4], uint32_t b0, uint32_t b1) {
    asm("mma.sync.aligned.m16n8k16.row.col.f32.bf16.bf16.f32 {%0,%1,%2,%3}, {%4,%5,%6,%7}, {%8,%9}, {%0,%1,%2,%3};"
        : "+f"(d[0]), "+f"(d[1]), "+f"(d[2]), "+f"(d[3])
        : "r"(a[0]), "r"(a[1]), "r"(a[2]), "r"(a[3]), "r"(b0), "r"(b1));
}
__device__ __forceinline__ uint32_t lds32(uint32_t a) {
    uint32_t v;
    asm volatile("ld.shared.u32 %0, [%1];" : "=r"(v) : "r"(a));
    return v;
}
__device__ __forceinline__ unsigned ld_acquire(const unsigned* p) {
    unsigned v;
    asm volatile("ld.acquire.gpu.global.u32 %0, [%1];" : "=r"(v) : "l"(p) : "memory");
    return v;
}
__device__ __forceinline__ uint2 ld_relaxed8(const void* p) {
    uint2 v;
    asm volatile("ld.relaxed.gpu.global.v2.u32 {%0,%1}, [%2];" : "=r"(v.x), "=r"(v.y) : "l"(p) : "memory");
    return v;
}
__device__ __forceinline__ unsigned ld_relaxed4(const void* p) {
    unsigned v;
    asm volatile("ld.relaxed.gpu.global.u32 %0, [%1];" : "=r"(v) : "l"(p) : "memory");
    return v;
}
__device__ __forceinline__ unsigned atom_inc(unsigned* p) {
    unsigned v;
    asm volatile("atom.relaxed.gpu.global.inc.u32 %0, [%1], 0x7fffffff;" : "=r"(v) : "l"(p) : "memory");
    return v;
}
__device__ __forceinline__ unsigned long long ld_relaxed64(const void* p) {
    unsigned long long v;
    asm volatile("ld.relaxed.gpu.global.u64 %0, [%1];" : "=l"(v) : "l"(p) : "memory");
    return v;
}
__device__ __forceinline__ void st_relaxed64(void* p, unsigned long long v) {
    asm volatile("st.relaxed.gpu.global.u64 [%0], %1;" ::"l"(p), "l"(v) : "memory");
}
__device__ __forceinline__ float4 ld_relaxed16(const void* p) {
    float4 v;
    asm volatile("ld.relaxed.gpu.global.v4.f32 {%0,%1,%2,%3}, [%4];" : "=f"(v.x), "=f"(v.y), "=f"(v.z), "=f"(v.w) : "l"(p) : "memory");
    return v;
}
__device__ __forceinline__ uint32_t mapa(uint32_t a, uint32_t rank) {
    uint32_t r;
    asm("mapa.shared::cluster.u32 %0, %1, %2;" : "=r"(r) : "r"(a), "r"(rank));
    return r;
}
__device__ __forceinline__ uint32_t time_ns() { uint32_t t; asm volatile("mov.u32 %0, %globaltimer_lo;" : "=r"(t)); return t; }
__device__ __forceinline__ void fence_gpu() { asm volatile("fence.acq_rel.gpu;" ::: "memory"); }
__device__ __forceinline__ void red_add_u32(unsigned* p, unsigned v) {
    asm volatile("red.relaxed.gpu.global.add.u32 [%0], %1;" ::"l"(p), "r"(v) : "memory");
}
__device__ __forceinline__ void st_tagged2(void* p, float a, float b, unsigned tag) {
    const unsigned long long hi = (unsigned long long)tag << 32;
    asm volatile("st.relaxed.gpu.global.v2.b64 [%0], {%1,%2};" ::"l"(p), "l"(hi | __float_as_uint(a)), "l"(hi | __float_as_uint(b)) : "memory");
}
__device__ __forceinline__ ulonglong2 ld_tagged2(const void* p) {
    ulonglong2 v;
    asm volatile("ld.relaxed.gpu.global.v2.b64 {%0,%1}, [%2];" : "=l"(v.x), "=l"(v.y) : "l"(p) : "memory");
    return v;
}
__device__ __forceinline__ float4 atom_add_f4(void* p, float a, float b, float c, float d) {
    float4 r;
    asm volatile("atom.relaxed.gpu.global.add.v4.f32 {%0,%1,%2,%3}, [%4], {%5,%6,%7,%8};"
                 : "=f"(r.x), "=f"(r.y), "=f"(r.z), "=f"(r.w) : "l"(p), "f"(a), "f"(b), "f"(c), "f"(d) : "memory");
    return r;
}
__device__ __forceinline__ void red_release_cta_shared(uint32_t a, unsigned v) {
    asm volatile("red.release.cta.shared::cta.add.u32 [%0], %1;" ::"r"(a), "r"(v) : "memory");
}
__device__ __forceinline__ unsigned ld_acquire_cta_shared(uint32_t a) {
    unsigned v;
    asm volatile("ld.acquire.cta.shared::cta.u32 %0, [%1];" : "=r"(v) : "r"(a) : "memory");
    return v;
}
__device__ __forceinline__ void st_release_cta_shared(uint32_t a, unsigned v) {
    asm volatile("st.release.cta.shared::cta.u32 [%0], %1;" ::"r"(a), "r"(v) : "memory");
}
__device__ __forceinline__ void wait_count(const unsigned* p, unsigned target) {
    unsigned n = 0;
    while (ld_acquire(p) < target) { if (++n > SPIN_LIMIT) __trap(); }
}
__device__ __forceinline__ uint32_t pack_bf16(float lo, float hi) {
    uint32_t r;
    asm("cvt.rn.bf16x2.f32 %0, %1, %2;" : "=r"(r) : "f"(hi), "f"(lo));
    return r;
}
__device__ __forceinline__ float bf_lo(uint32_t v) { return __uint_as_float(v << 16); }
__device__ __forceinline__ float bf_hi(uint32_t v) { return __uint_as_float(v & 0xffff0000u); }
__device__ __forceinline__ float ex2(float x) { float y; asm("ex2.approx.ftz.f32 %0, %1;" : "=f"(y) : "f"(x)); return y; }
__device__ __forceinline__ float expsub(float a, float b) { return ex2((a - b) * LOG2E); }
__device__ __forceinline__ float warp_max(float v) {
#pragma unroll
    for (int m = 16; m; m >>= 1) v = fmaxf(v, __shfl_xor_sync(~0u, v, m));
    return v;
}
__device__ __forceinline__ float warp_sum(float v) {
#pragma unroll
    for (int m = 16; m; m >>= 1) v += __shfl_xor_sync(~0u, v, m);
    return v;
}
template <bool CLU>
__device__ __forceinline__ unsigned unit_block(int u) {
    const unsigned x = ((unsigned)u & (NUK - 1)) / UPP;
    const int lg = u < NUK ? min(KMAX, max(KMIN, 29 - __clz(x | 1))) : (CLU && (int)x >= 4 * VS0 ? 0 : min(VMAX, max(VMIN, 29 - __clz((127 - x) | 1))));
    const unsigned r = x & ((4u << lg) - 1);
    return ((x - r + (r & ((1u << lg) - 1)) * 4 + (r >> lg)) * UPP) | ((unsigned)u & (UPP - 1));
}
__device__ __forceinline__ const char* block_src(const void* base, unsigned blk) {
    const unsigned po = blk / UPP;
    return reinterpret_cast<const char*>(base) + (size_t)(((po & 3) * NH + (po >> 2)) * UPP + blk % UPP) * TILE_BYTES;
}

template <bool CLU>
__device__ __forceinline__ void a_worker(const Params& p, int un, bool once, bool pre, bool hold, int nstatic, uint32_t slot, uint32_t bar,
                                         uint32_t help, unsigned epoch, uint64_t pol) {
    constexpr int NU = 2 * NUK, NR = CLU ? NREPC : NREP;
    const int lane = threadIdx.x & 31, g = lane >> 2, t = lane & 3;
    const int li = lane & 7;
    uint32_t kaddr[4], vaddr[8];
    {
        const int e = (lane >> 3) & 1, kk = lane >> 4;
#pragma unroll
        for (int s = 0; s < 4; s++) kaddr[s] = slot + (16 * li + e) * 256 + ((2 * s + kk + li) & 7) * 16;
        const int vrow = 4 * (li >> 1) + (li & 1) + 2 * kk;
#pragma unroll
        for (int c = 0; c < 8; c++) vaddr[c] = slot + vrow * 256 + e * 128 + ((c + li) & 7) * 16;
#pragma unroll
        for (int c = 0; c < 8; c++) asm volatile("" : "+r"(vaddr[c]));
    }
    const uint32_t vmask = (g >> 1) != t ? 0u : ((g & 1) ? 0xffff0000u : 0xffffu);
    int kseen = -1;
    unsigned long long H0 = 0, H1 = 0;
    auto header = [&](int v, unsigned vb) {
        const void *a0, *a1;
        if (v < NUK) {
            const unsigned po = vb / UPP;
            a0 = scratch(p)->qll + (po & 3) * 2048 + (po >> 2) * 64 + lane;
            a1 = reinterpret_cast<const uint2*>(a0) + 32;
        } else {
            const int half = vb / (NUK / 2);
            if (half > kseen) {
                unsigned n = 0;
                while (ld_acquire_cta_shared(help + 12 + 4 * half) == 0) { if (++n > (SPIN_LIMIT << 4)) __trap(); }
                kseen = half;
            }
            a0 = &scratch(p)->scores[vb * (KEYS / 4) + lane];
            a1 = &scratch(p)->stats[(vb / UPP) * UPP + lane];
        }
        H0 = ld_relaxed64(a0);
        H1 = ld_relaxed64(a1);
    };
    unsigned bu = 0, bn = unit_block<CLU>(un);
    asm volatile("bar.sync 2, %0;" ::"n"(32 * (NW + XW + 1)) : "memory");
    epoch = __shfl_sync(~0u, epoch, 0);
    if (hold) { unsigned n = 0; while (ld_acquire_cta_shared(help + 24) < 2) { if (++n > (SPIN_LIMIT << 4)) __trap(); } }
    unsigned (*ctl)[32] = scratch(p)->ctl[epoch & 1];
    const unsigned tag = epoch + 1;
    unsigned nxt = once ? NU : 0;
    int u = -1;
    uint32_t phase = 0;
    unsigned kpend = 0;
    const unsigned zero = gridDim.x >> 24;
    uint32_t Q[16];
    float4 oret = make_float4(0.f, 0.f, 0.f, 0.f);
    while (true) {
        const char* nsrc = block_src(un < NUK ? p.kc : p.vc, bn);
        float4* odst = &scratch(p)->oacc[(bu / UPP) * 32 + lane];
        unsigned* vdst = &scratch(p)->vdone[(lane & (NR - 1)) * NH + bu / (4 * UPP)][0];
        float d[8][4];
        CLK(c1);
        uint32_t act = un >= NU ? 0u : (u >= 0 || !pre ? 1u : 0u) | (!once && lane == 0 ? 2u : 0u);
        asm volatile("" : "+l"(odst), "+l"(nsrc), "+r"(act));
        if (u >= NUK) {
#pragma unroll
            for (int j = 0; j < 8; j++) { d[j][0] = d[j][1] = d[j][2] = d[j][3] = 0.f; }
            mbar_wait(bar, phase);
            LAND(NUK + bu);
            uint32_t a[2][8][4];
#pragma unroll
            for (int c = 0; c < 8; c++) ldsm4t(a[0][c], vaddr[c]);
#pragma unroll
            for (int j = 0; j < 8; j++) {
                if (j < 7) {
#pragma unroll
                    for (int c = 0; c < 8; c++) ldsm4t(a[(j + 1) & 1][c], vaddr[c] + (j + 1) * 4096);
                }
#pragma unroll
                for (int c = 0; c < 8; c++) mma16816(d[c], a[j & 1][c], Q[2 * j], Q[2 * j + 1]);
            }
            float o[4];
#pragma unroll
            for (int r = 0; r < 2; r++) {
                o[2 * r] = d[0][2 * r] + d[7][2 * r + 1];
                o[2 * r + 1] = d[0][2 * r + 1] + d[1][2 * r];
#pragma unroll
                for (int k = 1; k < 4; k++) {
                    const int src = (lane & 28) | ((t - k) & 3);
                    o[2 * r] += __shfl_sync(~0u, d[2 * k][2 * r] + d[2 * k - 1][2 * r + 1], src);
                    o[2 * r + 1] += __shfl_sync(~0u, d[2 * k][2 * r + 1] + d[2 * k + 1][2 * r], src);
                }
            }
            oret = atom_add_f4(odst, o[0], o[1], o[2], o[3]);
        } else if (u >= 0) {
#pragma unroll
            for (int j = 0; j < 8; j++) { d[j][0] = d[j][1] = d[j][2] = d[j][3] = 0.f; }
            mbar_wait(bar, phase);
            LAND(bu);
            uint32_t a[2][8][4];
#pragma unroll
            for (int j = 0; j < 8; j++) ldsm4(a[0][j], kaddr[0] + (4 * (j & 3) + 2 * (j >> 2)) * 256);
#pragma unroll
            for (int s = 0; s < 8; s++) {
                if (s < 7) {
#pragma unroll
                    for (int j = 0; j < 8; j++)
                        ldsm4(a[(s + 1) & 1][j], kaddr[(s + 1) & 3] + (4 * (j & 3) + 2 * (j >> 2)) * 256 + ((s + 1) >> 2) * 128);
                }
#pragma unroll
                for (int j = 0; j < 8; j++)
                    mma16816(d[j], a[s & 1][j], Q[(s & 4) * 2 + ((2 * s - 2 * j) & 7)], Q[(s & 4) * 2 + ((2 * s + 1 - 2 * j) & 7)]);
            }
        }
        if (u >= 0) phase ^= 1;
        CLK(c2b);
        asm volatile("{\n.reg .pred p, q;\n.reg .u32 a;\nelect.sync _|p, 0xffffffff;\nand.b32 a, %5, 1;\nsetp.ne.and.u32 q, a, 0, p;\n"
                     "@q mbarrier.arrive.expect_tx.shared::cta.b64 _, [%2], %4;\n"
                     "@q cp.async.bulk.shared::cluster.global.mbarrier::complete_tx::bytes.L2::cache_hint [%0], [%1], %4, [%2], %3;\n}"
                     ::"r"(slot), "l"(nsrc), "r"(bar), "l"(pol), "n"(TILE_BYTES), "r"(act) : "memory");
        if (act & 2) nxt = atom_inc(&ctl[C_QUEUE][0]);
        const uint32_t tk = clock();
        CLK(c3);
        if ((unsigned)u < (unsigned)NUK) {
            const int j0 = (t - (g >> 1)) & 3;
            float v[4];
#pragma unroll
            for (int q = 0; q < 4; q++) {
                const int jq = (q >> 1) * 4, e = (q & 1) * 2;
                const float x0 = (g & 1) ? d[jq + 0][e + 1] : d[jq + 0][e];
                const float x1 = (g & 1) ? d[jq + 1][e + 1] : d[jq + 1][e];
                const float x2 = (g & 1) ? d[jq + 2][e + 1] : d[jq + 2][e];
                const float x3 = (g & 1) ? d[jq + 3][e + 1] : d[jq + 3][e];
                const float y0 = (j0 & 1) ? x1 : x0, y1 = (j0 & 1) ? x3 : x2;
                v[q] = (j0 & 2) ? y1 : y0;
            }
            const uint32_t r0 = pack_bf16(v[0], v[1]), r1 = pack_bf16(v[2], v[3]);
            const uint32_t s0 = pack_bf16(bf_lo(r0) * SCALE, bf_hi(r0) * SCALE);
            const uint32_t s1 = pack_bf16(bf_lo(r1) * SCALE, bf_hi(r1) * SCALE);
            scratch(p)->scores[bu * (KEYS / 4) + 4 * g + j0] = make_uint2(s0, s1);
            const float f0 = bf_lo(s0), f1 = bf_hi(s0), f2 = bf_lo(s1), f3 = bf_hi(s1);
            const float m = warp_max(fmaxf(fmaxf(f0, f1), fmaxf(f2, f3)));
            const float l = warp_sum((expsub(f0, m) + expsub(f1, m)) + (expsub(f2, m) + expsub(f3, m)));
            if (lane == 0) scratch(p)->stats[bu] = make_float2(m, l);
            kpend++;
            if (un / (NUK / 2) != u / (NUK / 2)) {
                __syncwarp();
                if (lane == 0) {
                    red_release_cta_shared(help + 4 * (u / (NUK / 2)), kpend);
                    if (un >= NUK) red_release_cta_shared(help + 8, 1u);
                }
                kpend = 0;
            }
        }
        CLK(c4);
        int unn = NU;
        if (un < NU) {
            unsigned n = 0;
            while (true) {
                header(un, bn);
                if (un >= NUK || __all_sync(~0u, (uint32_t)(H0 >> 32) == tag && (uint32_t)(H1 >> 32) == tag)) break;
                if (++n > SPIN_LIMIT) __trap();
            }
            if (un >= NUK) {
                const uint32_t s0 = (uint32_t)H0, s1 = (uint32_t)(H0 >> 32);
                const float mu = __uint_as_float((uint32_t)H1);
                const float m = warp_max(mu);
                const float l = warp_sum(__uint_as_float((uint32_t)(H1 >> 32)) * expsub(mu, m));
                const float inv = 1.0f / l;
                const uint32_t w0 = pack_bf16(expsub(bf_lo(s0), m) * inv, expsub(bf_hi(s0), m) * inv);
                const uint32_t w1 = pack_bf16(expsub(bf_lo(s1), m) * inv, expsub(bf_hi(s1), m) * inv);
#pragma unroll
                for (int j = 0; j < 8; j++) {
                    Q[2 * j] = __shfl_sync(~0u, w0, 4 * j + t) & vmask;
                    Q[2 * j + 1] = __shfl_sync(~0u, w1, 4 * j + t) & vmask;
                }
            } else {
#pragma unroll
                for (int j = 0; j < 8; j++) {
                    const int src = (((j + g) & 7) << 2) + t;
                    Q[j] = __shfl_sync(~0u, (uint32_t)H0, src);
                    Q[8 + j] = __shfl_sync(~0u, (uint32_t)H1, src);
                }
            }
            unn = nstatic + (int)__shfl_sync(~0u, nxt, 0);
            if (CLU && ((NU - EARLY - unn) & ~(7 << ELOG)) == 0 && lane < MINCL)
                st_relaxed64(&scratch(p)->dry[lane][(NU - EARLY - unn) >> ELOG],
                             (time_ns() - (((uint32_t)clock() - tk) >> 1) + (NU - unn) * TPU / 16) | (unsigned long long)tag << 32);
        }
        if (u >= NUK && lane < NR)
            red_add_u32(vdst,
                        1u + ((__float_as_uint(oret.x) | __float_as_uint(oret.y) | __float_as_uint(oret.z) | __float_as_uint(oret.w)) & zero));
        if (un >= NU) break;
        bu = bn;
        bn = unit_block<CLU>(unn);
        u = un;
        un = unn;
    }
}

__device__ __forceinline__ void k_helper(const Params& p, uint32_t help, unsigned epoch) {
    if ((threadIdx.x & 31) != 0) return;
    unsigned (*ctl)[32] = scratch(p)->ctl[epoch & 1];
    unsigned sent0 = 0, sent1 = 0, n = 0;
    int seen = 0;
    bool fin = false;
    while (!fin || seen < 2) {
        if (!fin) {
            fin = ld_acquire_cta_shared(help + 8) == NW + XW;
            const unsigned c0 = ld_acquire_cta_shared(help), c1 = ld_acquire_cta_shared(help + 4);
            if (c0 != sent0 || c1 != sent1) {
                fence_gpu();
                if (c0 != sent0) red_add_u32(&ctl[C_KDONE][0], c0 - sent0);
                if (c1 != sent1) red_add_u32(&ctl[C_KDONE + 1][0], c1 - sent1);
                sent0 = c0; sent1 = c1;
            }
        }
        if (seen < 2 && ld_acquire(&ctl[C_KDONE + seen][0]) >= NUK / 2) {
            st_release_cta_shared(help + 12 + 4 * seen, 1u);
            seen++;
        } else {
            __nanosleep(300);
        }
        if (++n > SPIN_LIMIT) __trap();
    }
}

__device__ __forceinline__ void v_poller(const Params& p, uint32_t sbase, int f, int w) {
    constexpr int HL = NH;
    const int lane = threadIdx.x & 31;
    const unsigned (*cp)[32] = &scratch(p)->vdone[((f * NPOLL + w) % NREP) * NH];
    unsigned n = 0;
    while (ld_acquire_cta_shared(sbase + M_HELP + 12) == 0) { __nanosleep(1000); if (++n > SPIN_LIMIT) __trap(); }
    int h = 0;
    bool fast = false;
    while (h < HL) {
        const unsigned r = __ballot_sync(~0u, ld_acquire(&cp[min(h + (lane & 3), HL - 1)][0]) >= 4 * UPP) & 15u;
        if (r & 1) {
            h = min(HL, h + __ffs(~r) - 1);
            __syncwarp();
            if (lane == 0) asm volatile("red.release.cta.shared::cta.max.u32 [%0], %1;" ::"r"(sbase + M_HELP + 20), "r"(h) : "memory");
        }
        if (h < HL - 4) {
            __nanosleep(h ? 300 : 1000);
        } else if (!fast) {
            fast = true;
            const long long t0 = clock64();
            while (clock64() - t0 < w * PGAP) {}
        }
        if (++n > SPIN_LIMIT) __trap();
    }
}
__device__ __forceinline__ void finisher(const Params& p, uint32_t sbase, int f) {
    constexpr int HL = NH;
    const int lane = threadIdx.x & 31;
    {
        const char* wg = reinterpret_cast<const char*>(p.wo);
        const uint32_t dst = sbase + 4 * SLOT + (16 * (lane & 7) + (lane >> 3)) * 16;
#pragma unroll 1
        for (int h = -FPF - 4; h < HL; h++) {
            if (lane == 0 && (unsigned)(h + FPF) < (unsigned)HL) l2_prefetch(wg + (size_t)(h + FPF) * 147456 + f * 2048, 2048);
            if (h >= 0) {
#pragma unroll
                for (int r = 0; r < 4; r++)
                    asm volatile("cp.async.cg.shared.global [%0], [%1], 16;" ::"r"(dst + h * 2048 + ((r & 1) * 4 + (r >> 1) * 8) * 16),
                                 "l"(wg + (size_t)(h * 128 + r * 32 + lane) * (DM * 2) + f * 16) : "memory");
            }
            __nanosleep(FSLEEP);
        }
        asm volatile("cp.async.wait_all;" ::: "memory");
        __syncwarp();
    }
    TS(11);
    const float4* vec = scratch(p)->oacc + ((lane >> 2) & 3) * 32 + (lane >> 4) * 16 + (lane & 3);
    float acc[2][2][4];
#pragma unroll
    for (int i = 0; i < 16; i++) acc[i >> 3][(i >> 2) & 1][i & 3] = 0.f;
    uint32_t* outp = reinterpret_cast<uint32_t*>(p.out + (lane >> 2) * (2 * DM) + f * 8 + (lane & 3) * 2);
    uint32_t wa = sbase + 4 * SLOT + lane * 16;
    auto project = [&](const float4 (&x)[4], const uint32_t (&w)[4][4]) {
#pragma unroll
        for (int s = 0; s < 4; s++) {
            const uint32_t a[4] = {pack_bf16(x[s].x, x[s].y), 0u, pack_bf16(x[s].z, x[s].w), 0u};
            mma16816(acc[0][s & 1], a, w[s >> 1][(s & 1) * 2], w[s >> 1][(s & 1) * 2 + 1]);
            mma16816(acc[1][s & 1], a, w[2 + (s >> 1)][(s & 1) * 2], w[2 + (s >> 1)][(s & 1) * 2 + 1]);
        }
    };
    int h = 0;
    unsigned n = 0;
    while (h < HL) {
        uint32_t w[4][4];
#pragma unroll
        for (int q = 0; q < 4; q++) ldsm4t(w[q], wa + q * 512);
        int ready;
        while ((ready = ld_acquire_cta_shared(sbase + M_HELP + 20)) <= h) {
            if (h < HL - 3) __nanosleep(100);
            if (++n > (SPIN_LIMIT << 4)) __trap();
        }
        float4 x[4], y[4];
#pragma unroll
        for (int s = 0; s < 4; s++) x[s] = ld_relaxed16(vec + s * 4);
        const bool two = ready > h + 1;
        if (two) {
#pragma unroll
            for (int s = 0; s < 4; s++) y[s] = ld_relaxed16(vec + 128 + s * 4);
        }
        project(x, w);
        if (two) {
#pragma unroll
            for (int q = 0; q < 4; q++) ldsm4t(w[q], wa + 2048 + q * 512);
            project(y, w);
        }
        const int nr = two ? 2 : 1;
        h += nr;
        vec += nr * 128;
        wa += nr * 2048;
        const float o0 = acc[0][0][0] + acc[0][1][0] + __shfl_down_sync(~0u, acc[1][0][0] + acc[1][1][0], 16);
        const float o1 = acc[0][0][1] + acc[0][1][1] + __shfl_down_sync(~0u, acc[1][0][1] + acc[1][1][1], 16);
        asm volatile("{\n.reg .pred p;\nsetp.ne.u32 p, %2, 0;\n@p st.global.u32 [%0], %1;\n}" ::"l"(outp), "r"(pack_bf16(o0, o1)),
                     "r"((uint32_t)(lane < 16 && h == NH)) : "memory");
    }
}

__device__ __noinline__ void f_collect(const unsigned (*flag)[32], unsigned full, const float4* src, unsigned todo, uint32_t sbase) {
    const int lane = threadIdx.x & 31, g = lane >> 2, t = lane & 3;
    const bool last = todo != 15;
    unsigned n = 0;
    while (todo) {
        const unsigned v = ld_acquire(&flag[t][0]);
        unsigned m = __ballot_sync(~0u, v == full) & todo;
        if (m == 0) {
            if (!last || __shfl_sync(~0u, v, 0) == 0) __nanosleep(200);
            if (++n > SPIN_LIMIT) __trap();
            continue;
        }
        __syncwarp();
        todo ^= m;
        if (last) TS(16);
        do {
            const int h0 = __ffs(m) - 1, h1 = 31 - __clz(m);
            m &= ~((1u << h0) | (1u << h1));
            float4 x[8];
#pragma unroll
            for (int b = 0; b < 8; b++) x[b] = ld_relaxed16(src + ((b & 4) ? h1 : h0) * 128 + (b & 3) * 32 + lane);
#pragma unroll
            for (int b = 0; b < 8; b++) {
                const uint32_t lo = pack_bf16(x[b].x, x[b].y), hi = pack_bf16(x[b].z, x[b].w);
                const uint32_t o = __shfl_xor_sync(~0u, (g & 1) ? lo : hi, 4);
                const uint32_t e0 = (g & 1) ? o : lo, e1 = (g & 1) ? hi : o;
                asm volatile("st.shared.v2.u32 [%0], {%1,%2};"
                             ::"r"(sbase + F_BF + ((b & 4) ? h1 : h0) * 1024 + t * 256 + ((b ^ t) & 3) * 64 + g * 8),
                               "r"(__byte_perm(e0, e1, 0x5410)), "r"(__byte_perm(e0, e1, 0x7632)) : "memory");
            }
            __syncwarp();
            if (lane < (h0 == h1 ? 1 : 2))
                asm volatile("mbarrier.arrive.shared::cta.b64 _, [%0];" ::"r"(sbase + F_BAR + 32 + (lane ? h1 : h0) * 8) : "memory");
        } while (m);
    }
    if (last) TS(17);
}

__device__ __forceinline__ void f_project(const Params& p, const CUtensorMap* tm, int panel, int rank, int warp, int sl, int delay, unsigned tag, uint32_t sbase, uint64_t pol) {
    const int j = warp & 3;
    const int lane = threadIdx.x & 31, g = lane >> 2, t = lane & 3;
    const uint32_t wb = sbase + F_W - sl * 2 * SLOT, bars = sbase + F_BAR + 64 + sl * 32;
    const uint32_t wa = wb + ((lane & 7) + (lane >> 4) * 8) * 128 + (((2 * j + ((lane >> 3) & 1)) ^ (lane & 7)) * 16);
    const uint32_t ba = sbase + F_BF + (g & 3) * 64 + t * 16;
    const uint32_t rdst = mapa(sbase + F_RX + sl * 1024 + rank * 128 + g * 16 + (t & 1) * 8, 2 * j + (t >> 1));
    const uint32_t rbar = mapa(sbase + F_BAR + 16 + sl * 8, 2 * j + (t >> 1));
    unsigned n = 0;
    if (warp == 7) {
        if (lane == 0) asm volatile("prefetch.tensormap [%0];" ::"l"(tm) : "memory");
        unsigned long long v;
        while (!__all_sync(~0u, (v = ld_relaxed64(&scratch(p)->dry[blockIdx.x >> 3][g])) >> 32 == tag)) {
            __nanosleep(200);
            if (++n > SPIN_LIMIT) __trap();
        }
        const uint32_t t0 = __shfl_sync(~0u, (uint32_t)v, 0);
        const uint32_t t1 = t0 + (__reduce_add_sync(~0u, (int)((uint32_t)v - t0)) >> 5);
        if (lane == 0) asm volatile("st.shared.u32 [%0+8], %1;\nmbarrier.arrive.shared::cta.b64 _, [%0];" ::"r"(sbase + F_BAR), "r"(t1) : "memory");
        TS(22);
    }
    mbar_wait(sbase + F_BAR, 0);
    float acc[2][4];
#pragma unroll
    for (int i = 0; i < 8; i++) acc[i >> 2][i & 3] = 0.f;
    const bool up = t & 2;
#pragma unroll 1
    for (int h = 0; h < 4; h++) {
        if (h == max(j - LAG, 0)) {
            const uint32_t due = lds32(sbase + F_BAR + 8) + delay;
            while ((int)(time_ns() - due) < 0 && ++n < SPIN_LIMIT) {}
            tma3d_warp(wb + j * 16384, tm, 0, (rank * 4 + j) * 128, panel, bars + j * 8, 16384, pol);
            TS(18);
        }
        uint32_t wp = wa + h * 16384, last = h == 3;
        mbar_spin(sbase + F_BAR + 32 + h * 8);
        uint32_t a[8][4], bf[4][4];
#pragma unroll
        for (int s = 0; s < 4; s++)
            asm volatile("ld.shared.v4.u32 {%0,%1,%2,%3}, [%4];" : "=r"(bf[s][0]), "=r"(bf[s][1]), "=r"(bf[s][2]), "=r"(bf[s][3])
                         : "r"(((ba + h * 1024) ^ (s * 64)) + s * 256) : "memory");
        asm volatile("" : "+r"(wp), "+r"(last));
        mbar_spin(bars + h * 8);
        if (h == 3) TS(19);
#pragma unroll
        for (int s = 0; s < 8; s++) ldsm4t(a[s], wp + s * 2048);
#pragma unroll
        for (int s = 0; s < 8; s++) mma16816(acc[s & 1], a[s], bf[s & 3][(s >> 2) * 2], bf[s & 3][(s >> 2) * 2 + 1]);
        const float v0 = up ? acc[0][2] + acc[1][2] : acc[0][0] + acc[1][0], v1 = up ? acc[0][3] + acc[1][3] : acc[0][1] + acc[1][1];
        asm volatile("{\n.reg .pred p;\nsetp.ne.u32 p, %4, 0;\n"
                     "@p st.async.weak.shared::cluster.mbarrier::complete_tx::bytes.v2.b32 [%0], {%1,%2}, [%3];\n}"
                     ::"r"(rdst), "r"(__float_as_uint(v0)), "r"(__float_as_uint(v1)), "r"(rbar), "r"(last) : "memory");
    }
    TS(20);
}

__device__ __forceinline__ void f_receive(const Params& p, __nv_bfloat16* out, int sl, bool dry, uint32_t sbase) {
    const int lane = threadIdx.x & 31;
    out += (lane & 3) * (2 * DM) + (lane >> 2);
    uint32_t src = sbase + F_RX + sl * 1024 + lane * 4;
    asm volatile("" : "+l"(out), "+r"(src));
    mbar_spin_cluster(sbase + F_BAR + (dry ? 0 : 16 + sl * 8));
    float v[8];
#pragma unroll
    for (int r = 0; r < 8; r++) asm volatile("ld.shared.f32 %0, [%1];" : "=f"(v[r]) : "r"(src + r * 128) : "memory");
    const float o = ((v[0] + v[1]) + (v[2] + v[3])) + ((v[4] + v[5]) + (v[6] + v[7]));
    asm volatile("{\n.reg .pred p;\nsetp.eq.u32 p, %2, 0;\n@p st.global.u16 [%0], %1;\n}"
                 ::"l"(out), "h"((unsigned short)pack_bf16(o, 0.f)), "r"((uint32_t)dry) : "memory");
    TS(15);
}

constexpr int BS_WUK = 5, BS_Q = 9, BS_CKV = 11, BS_PART = 27, BS_WUV = 29, BS_END = 33;

__device__ __noinline__ void b_issue(const Params& p, int n, int bi, uint32_t sbase, uint64_t pol) {
    if (n >= BS_END || (n >= BS_Q && n < BS_CKV) || (n >= BS_PART && n < BS_WUV)) return;
    const uint32_t bar = sbase + M_BAR + (NSLOT + n % BRING) * 8;
    const CUtensorMap* tm;
    int row, panel = 2 * bi;
    if (n < BS_WUK) { tm = &p.tm_wq; row = n * 128; }
    else if (n < BS_Q) { tm = &p.tm_wuk; row = (n - BS_WUK) * 128; }
    else if (n < BS_PART) {
        tm = &p.tm_ckv; panel = 0;
        row = (bi >> 3) * SK + ((n - BS_CKV) * 8 + (bi & 7)) * 32;
    }
    else { tm = &p.tm_wuv; row = (n - BS_WUV) * 128; }
    mbar_expect_tx(bar, n == 0 ? 32768 + 4 * 1152 : 32768);
    tma3d(sbase + (n % BRING) * SLOT, tm, 0, row, panel, bar, pol);
}
__device__ __forceinline__ void b_issue_xchg(int n, const void* src, uint32_t sbase, uint64_t pol) {
    asm volatile("fence.proxy.async;" ::: "memory");
#pragma unroll
    for (int i = 0; i < 2; i++) {
        const uint32_t bar = sbase + M_BAR + (NSLOT + (n + i) % BRING) * 8;
        mbar_expect_tx(bar, 32768);
        bulk_load(sbase + ((n + i) % BRING) * SLOT, reinterpret_cast<const char*>(src) + i * 32768, 32768, bar, pol);
    }
}
__device__ __forceinline__ void b_wait(int n, uint32_t sbase) {
    mbar_wait(sbase + M_BAR + (NSLOT + n % BRING) * 8, (n / BRING) & 1);
}

__device__ __noinline__ void b_gemm(const Params& p, uint32_t sbase, int n0, int n1, int ktot, uint32_t xh, uint32_t xl, int pitch,
                                    int bi, uint64_t pol) {
    const int tid = threadIdx.x, warp = tid >> 5, lane = tid & 31, g = lane >> 2, t = lane & 3;
    const uint32_t woff = (warp >> 2) * 16384 + (lane & 15) * 128 + ((((warp & 3) * 2 + (lane >> 4)) ^ (lane & 7)) * 16);
    const uint32_t xoff = (g & 3) * pitch + t * 4;
    float acc[2][4];
#pragma unroll
    for (int i = 0; i < 8; i++) acc[i >> 2][i & 3] = 0.f;
#pragma unroll 1
    for (int n = n0; n < n1; n++) {
        b_wait(n, sbase);
        const uint32_t slot = sbase + (n % BRING) * SLOT + woff;
        const int k0 = (n - n0) * 128;
        const int ns = min(8, (ktot - k0) >> 4);
#pragma unroll 2
        for (int s = 0; s < ns; s++) {
            uint32_t a[4], w[4];
            const uint32_t xo = xoff + (k0 + 16 * s) * 2;
            a[0] = lds32(xh + xo); a[2] = lds32(xh + xo + 16);
            a[1] = xl ? lds32(xl + xo) : 0u; a[3] = xl ? lds32(xl + xo + 16) : 0u;
            ldsm4t(w, slot + s * 2048);
            mma16816(acc[0], a, w[0], w[1]);
            mma16816(acc[1], a, w[2], w[3]);
        }
        __syncthreads();
        if (tid == 0) b_issue(p, n + BD, bi, sbase, pol);
    }
    if (g < 4) {
#pragma unroll
        for (int j = 0; j < 2; j++)
            asm volatile("st.shared.u32 [%0], %1;" ::"r"(sbase + M_QB + g * QP + (warp * 16 + j * 8 + t * 2) * 2),
                         "r"(pack_bf16(acc[j][0] + acc[j][2], acc[j][1] + acc[j][3])) : "memory");
    }
    __syncthreads();
}

__device__ __forceinline__ void b_exchange(unsigned* c, int n, const void* src, uint32_t sbase, uint64_t pol) {
    TS(n == BS_Q ? 24 : 28);
    __syncthreads();
    if (threadIdx.x == 0) {
        TS(n == BS_Q ? 25 : 29);
        fence_gpu();
        TS(n == BS_Q ? 26 : 30);
        red_add_u32(c, 1u);
        wait_count(c, NBCTA);
        TS(n == BS_Q ? 27 : 31);
        b_issue_xchg(n, src, sbase, pol);
    }
}

template <bool CLU>
__device__ __noinline__ void b_chain(const Params& p, char* smem, uint32_t sbase, int bi, unsigned epoch, uint64_t pol) {
    const int tid = threadIdx.x, warp = tid >> 5, lane = tid & 31, g = lane >> 2, t = lane & 3;
    unsigned (*ctl)[32] = scratch(p)->ctl[epoch & 1];
    float* red = reinterpret_cast<float*>(smem + 5 * SLOT);
    __syncthreads();
    b_gemm(p, sbase, 0, BS_WUK, DM, sbase + M_XB, 0, XP, bi, pol);
    TS(6);
    {
        uint32_t Q[16];
#pragma unroll
        for (int c = 0; c < 16; c++) Q[c] = lds32(sbase + M_QB + (g & 3) * QP + c * 16 + t * 4);
        float* qa = reinterpret_cast<float*>(smem + M_QA);
#pragma unroll 1
        for (int n = BS_WUK; n < BS_Q; n++) {
            b_wait(n, sbase);
            const uint32_t base = sbase + (n % BRING) * SLOT + (warp * 16 + (lane & 15)) * 128;
            float d[2][4];
#pragma unroll
            for (int i = 0; i < 8; i++) d[i >> 2][i & 3] = 0.f;
#pragma unroll
            for (int s = 0; s < 8; s++) {
                uint32_t a[4];
                ldsm4(a, base + (s >> 2) * 16384 + (((2 * (s & 3) + (lane >> 4)) ^ (lane & 7)) * 16));
                mma16816(d[s & 1], a, Q[2 * s], Q[2 * s + 1]);
            }
            const int c = (n - BS_WUK) * 128 + warp * 16 + g + 8 * (t >> 1);
            qa[(2 * (t & 1)) * 512 + c] = (t & 2) ? d[0][2] + d[1][2] : d[0][0] + d[1][0];
            qa[(2 * (t & 1) + 1) * 512 + c] = (t & 2) ? d[0][3] + d[1][3] : d[0][1] + d[1][1];
            __syncthreads();
            if (tid == 0) b_issue(p, n + BD, bi, sbase, pol);
        }
#pragma unroll 1
        for (int r = 0; r < 2; r++) {
            const int id = tid + r * 256;
            const int b = id >> 7, c0 = ((id >> 2) & 31) * 16 + (id & 3) * 2;
            const float2 u0 = *reinterpret_cast<const float2*>(qa + b * 512 + c0);
            const float2 u1 = *reinterpret_cast<const float2*>(qa + b * 512 + c0 + 8);
            const uint32_t h0 = pack_bf16(u0.x, u0.y), h1 = pack_bf16(u1.x, u1.y);
            const uint32_t l0 = pack_bf16(u0.x - bf_lo(h0), u0.y - bf_hi(h0)), l1 = pack_bf16(u1.x - bf_lo(h1), u1.y - bf_hi(h1));
            scratch(p)->qabs[((id >> 2) * 4 + (bi >> 3)) * 32 + (bi & 7) * 4 + (id & 3)] = make_uint4(h0, l0, h1, l1);
        }
    }
    b_exchange(&ctl[C_BBAR][0], BS_Q, &scratch(p)->qabs[(bi >> 3) * 4096], sbase, pol);
    {
        uint32_t qf[4][4][4];
        b_wait(BS_Q + (warp >> 2), sbase);
        TS(7);
        {
            const uint4* qs = reinterpret_cast<const uint4*>(smem + ((BS_Q + (warp >> 2)) % BRING) * SLOT) + (warp & 3) * 512 + lane;
#pragma unroll
            for (int s = 0; s < 4; s++)
#pragma unroll
                for (int i = 0; i < 4; i++) {
                    const uint4 v = qs[(s * 4 + i) * 32];
                    qf[i][s][0] = v.x; qf[i][s][1] = v.y; qf[i][s][2] = v.z; qf[i][s][3] = v.w;
                }
        }
        __syncthreads();
        if (tid == 0) { b_issue(p, BS_Q + BD, bi, sbase, pol); b_issue(p, BS_Q + 1 + BD, bi, sbase, pol); }
        float acc[2][8][4];
#pragma unroll
        for (int i = 0; i < 2; i++)
#pragma unroll
            for (int j = 0; j < 8; j++) { acc[i][j][0] = acc[i][j][1] = acc[i][j][2] = acc[i][j][3] = 0.f; }
        float mrun = -INFINITY, lrun = 0.f;
        const int head = tid >> 3, kq = tid & 7;
        float* alpha = reinterpret_cast<float*>(smem + M_ALPHA);
        for (int n = BS_CKV; n < BS_PART; n++) {
            b_wait(n, sbase);
            const uint32_t slot = sbase + (n % BRING) * SLOT;
            float sc[4][4][4];
#pragma unroll
            for (int i = 0; i < 4; i++)
#pragma unroll
                for (int j = 0; j < 4; j++) { sc[i][j][0] = sc[i][j][1] = sc[i][j][2] = sc[i][j][3] = 0.f; }
#pragma unroll
            for (int j = 0; j < 4; j++)
#pragma unroll
                for (int sp = 0; sp < 2; sp++) {
                    uint32_t bf[4];
                    ldsm4(bf, slot + warp * 4096 + (8 * j + (lane & 7)) * 128 + (((4 * sp + (lane >> 3)) ^ (lane & 7)) * 16));
#pragma unroll
                    for (int i = 0; i < 4; i++) {
                        mma16816(sc[i][j], qf[i][2 * sp], bf[0], bf[1]);
                        mma16816(sc[i][j], qf[i][2 * sp + 1], bf[2], bf[3]);
                    }
                }
#pragma unroll
            for (int i = 0; i < 4; i++)
#pragma unroll
                for (int j = 0; j < 4; j++)
                    *reinterpret_cast<float2*>(red + warp * 1024 + (8 * i + g) * 32 + ((8 * j) ^ (8 * (g & 3))) + 2 * t) =
                        make_float2(sc[i][j][0] + sc[i][j][2], sc[i][j][1] + sc[i][j][3]);
            __syncthreads();
            if (tid == 0 && n > BS_CKV) b_issue(p, n - 1 + BD, bi, sbase, pol);
            {
                float4 s = make_float4(0.f, 0.f, 0.f, 0.f);
#pragma unroll
                for (int w = 0; w < 8; w++) {
                    const float4 v = *reinterpret_cast<const float4*>(red + w * 1024 + head * 32 + ((4 * kq) ^ (8 * (head & 3))));
                    s.x += v.x; s.y += v.y; s.z += v.z; s.w += v.w;
                }
                const uint32_t r0 = pack_bf16(s.x, s.y), r1 = pack_bf16(s.z, s.w);
                const uint32_t s0 = pack_bf16(bf_lo(r0) * SCALE, bf_hi(r0) * SCALE);
                const uint32_t s1 = pack_bf16(bf_lo(r1) * SCALE, bf_hi(r1) * SCALE);
                const float f0 = bf_lo(s0), f1 = bf_hi(s0), f2 = bf_lo(s1), f3 = bf_hi(s1);
                float mx = fmaxf(fmaxf(f0, f1), fmaxf(f2, f3));
                mx = fmaxf(mx, __shfl_xor_sync(~0u, mx, 1));
                mx = fmaxf(mx, __shfl_xor_sync(~0u, mx, 2));
                mx = fmaxf(mx, __shfl_xor_sync(~0u, mx, 4));
                const float mnew = fmaxf(mrun, mx);
                const float al = expsub(mrun, mnew);
                const float p0 = expsub(f0, mnew), p1 = expsub(f1, mnew), p2 = expsub(f2, mnew), p3 = expsub(f3, mnew);
                lrun = lrun * al + ((p0 + p1) + (p2 + p3));
                mrun = mnew;
                *reinterpret_cast<uint2*>(smem + M_P + head * 80 + kq * 8) = make_uint2(pack_bf16(p0, p1), pack_bf16(p2, p3));
                if (kq == 0) alpha[head] = al;
            }
            __syncthreads();
            {
                uint32_t pf[2][2][4];
#pragma unroll
                for (int i = 0; i < 2; i++)
#pragma unroll
                    for (int ks = 0; ks < 2; ks++)
                        ldsm4(pf[i][ks], sbase + M_P + (16 * i + (lane & 15)) * 80 + (16 * ks + 8 * (lane >> 4)) * 2);
#pragma unroll
                for (int i = 0; i < 2; i++) {
                    const float a0 = alpha[16 * i + g], a1 = alpha[16 * i + 8 + g];
#pragma unroll
                    for (int j = 0; j < 8; j++) { acc[i][j][0] *= a0; acc[i][j][1] *= a0; acc[i][j][2] *= a1; acc[i][j][3] *= a1; }
                }
#pragma unroll
                for (int j = 0; j < 8; j++) {
                    uint32_t bf[4];
                    ldsm4t(bf, slot + warp * 4096 + lane * 128 + ((j ^ (lane & 7)) * 16));
#pragma unroll
                    for (int i = 0; i < 2; i++) {
                        mma16816(acc[i][j], pf[i][0], bf[0], bf[1]);
                        mma16816(acc[i][j], pf[i][1], bf[2], bf[3]);
                    }
                }
            }
        }
        __syncthreads();
        if (tid == 0) b_issue(p, BS_PART - 1 + BD, bi, sbase, pol);
        lrun += __shfl_xor_sync(~0u, lrun, 1);
        lrun += __shfl_xor_sync(~0u, lrun, 2);
        lrun += __shfl_xor_sync(~0u, lrun, 4);
        if (kq == 0) scratch(p)->bml[head * NBCTA + bi] = make_float2(mrun, lrun);
#pragma unroll
        for (int i = 0; i < 2; i++)
#pragma unroll
            for (int j = 0; j < 8; j++) {
                scratch(p)->bpart[((16 * i + g) * NBCTA + bi) * 256 + warp * 32 + j * 4 + t] = make_float2(acc[i][j][0], acc[i][j][1]);
                scratch(p)->bpart[((16 * i + 8 + g) * NBCTA + bi) * 256 + warp * 32 + j * 4 + t] = make_float2(acc[i][j][2], acc[i][j][3]);
            }
    }
    b_exchange(&ctl[C_BBAR + 1][0], BS_PART, &scratch(p)->bpart[bi * NBCTA * 256], sbase, pol);
    {
        float* omega = reinterpret_cast<float*>(smem + M_OMEGA);
        if (warp == 0) {
            __syncwarp();
            const uint2 ml = ld_relaxed8(&scratch(p)->bml[bi * NBCTA + lane]);
            const float ms = __uint_as_float(ml.x);
            float m = ms;
            m = fmaxf(m, __shfl_xor_sync(~0u, m, 1));
            m = fmaxf(m, __shfl_xor_sync(~0u, m, 2));
            m = fmaxf(m, __shfl_xor_sync(~0u, m, 4));
            const float w = expsub(ms, m);
            float l = w * __uint_as_float(ml.y);
            l += __shfl_xor_sync(~0u, l, 1);
            l += __shfl_xor_sync(~0u, l, 2);
            l += __shfl_xor_sync(~0u, l, 4);
            omega[lane] = w / l;
        }
        __syncthreads();
        b_wait(BS_PART, sbase);
        b_wait(BS_PART + 1, sbase);
#pragma unroll 1
        for (int b = 0; b < 4; b++) {
            const float2* ps = reinterpret_cast<const float2*>(smem + ((BS_PART + (b >> 1)) % BRING) * SLOT) + (b & 1) * 2048 + tid;
            float c0 = 0.f, c1 = 0.f;
#pragma unroll
            for (int s = 0; s < 8; s++) {
                const float w = omega[b * 8 + s];
                const float2 v = ps[s * 256];
                c0 = fmaf(w, v.x, c0);
                c1 = fmaf(w, v.y, c1);
            }
            const uint32_t hi = pack_bf16(c0, c1);
            *reinterpret_cast<uint32_t*>(smem + M_CH + b * CP + tid * 4) = hi;
            *reinterpret_cast<uint32_t*>(smem + M_CL + b * CP + tid * 4) = pack_bf16(c0 - bf_lo(hi), c1 - bf_hi(hi));
        }
        __syncthreads();
        if (tid == 0) { b_issue(p, BS_PART + BD, bi, sbase, pol); b_issue(p, BS_PART + 1 + BD, bi, sbase, pol); }
    }
    b_gemm(p, sbase, BS_WUV, BS_END, 512, sbase + M_CH, sbase + M_CL, CP, bi, pol);
    TS(12);
    if (CLU) {
        if (warp < 4) {
            const unsigned short* c = reinterpret_cast<const unsigned short*>(smem + M_QB + warp * QP) + 16 * t + g;
            scratch(p)->octx[(bi * 4 + warp) * 32 + lane] = make_float4(bf_lo(c[0]), bf_lo(c[8]), bf_lo(c[64]), bf_lo(c[72]));
        }
        __syncthreads();
        if (tid == 0) asm volatile("st.release.gpu.global.u32 [%0], %1;" ::"l"(&scratch(p)->cdone[bi][0]), "r"(epoch + 1) : "memory");
        return;
    }
    if (tid == 0) {
#pragma unroll 1
        for (int i = 0; i < 4; i++) {
            mbar_expect_tx(sbase + M_BAR + i * 8, 36864);
            tma3d(sbase + i * 36864, &p.tm_wo, 0, bi * 128 + i * 32, 0, sbase + M_BAR + i * 8, pol);
        }
    }
    TS(8);
    {
        float acc[9][4];
#pragma unroll
        for (int j = 0; j < 9; j++) { acc[j][0] = acc[j][1] = acc[j][2] = acc[j][3] = 0.f; }
#pragma unroll 1
        for (int i = 0; i < 4; i++) {
            const uint32_t xo = sbase + M_QB + (g & 3) * QP + i * 64 + t * 4;
            const uint32_t a0[4] = {lds32(xo), 0u, lds32(xo + 16), 0u}, a1[4] = {lds32(xo + 32), 0u, lds32(xo + 48), 0u};
            mbar_wait(sbase + M_BAR + i * 8, 0);
#pragma unroll
            for (int j = 0; j < 9; j++) {
                const int nt = warp * 9 + j;
                uint32_t w[4];
                ldsm4t(w, sbase + i * 36864 + (nt >> 3) * 4096 + lane * 128 + (((nt & 7) ^ (lane & 7)) * 16));
                mma16816(acc[j], a0, w[0], w[1]);
                mma16816(acc[j], a1, w[2], w[3]);
            }
        }
        if (g < 4) {
#pragma unroll
            for (int j = 0; j < 9; j++) {
                const int c2 = (warp * 9 + j) * 4 + t;
                st_tagged2(&scratch(p)->outb[((c2 / 9) * NH + bi) * 36 + g * 9 + c2 % 9], acc[j][0], acc[j][1], epoch + 1);
            }
        }
    }
    TS(9);
    {
        const uint4* src = scratch(p)->outb + (bi * NH + (tid >> 3)) * 36 + (tid & 7);
        float2* part = reinterpret_cast<float2*>(red);
        unsigned n = 0;
        while (true) {
            ulonglong2 v[5];
            bool ok = true;
#pragma unroll
            for (int i = 0; i < 5; i++)
                if (i < 4 || (tid & 7) < 4) v[i] = ld_tagged2(src + i * 8);
#pragma unroll
            for (int i = 0; i < 5; i++)
                if (i < 4 || (tid & 7) < 4) {
                    ok = ok && (unsigned)(v[i].x >> 32) == epoch + 1 && (unsigned)(v[i].y >> 32) == epoch + 1;
                    part[(tid >> 3) * 36 + (tid & 7) + i * 8] = make_float2(__uint_as_float((unsigned)v[i].x), __uint_as_float((unsigned)v[i].y));
                }
            if (ok) break;
            __nanosleep(400);
            if (++n > SPIN_LIMIT) __trap();
        }
        __syncthreads();
        if (tid < 36) {
            float s0 = 0.f, s1 = 0.f;
#pragma unroll 8
            for (int h = 0; h < NH; h++) { const float2 v = part[h * 36 + tid]; s0 += v.x; s1 += v.y; }
            *reinterpret_cast<uint32_t*>(p.out + (tid / 9) * 2 * DM + DM + bi * 18 + (tid % 9) * 2) = pack_bf16(s0, s1);
        }
    }
    TS(10);
}

template <bool CLU>
__global__ void __launch_bounds__(256, 1) fused_decode_kernel(const __grid_constant__ Params p) {
    asm volatile("{\n.reg .pred p;\n.reg .u32 a;\n.reg .u64 b;\nsub.u32 a, %1, %4;\nsetp.lt.u32 p, a, %3;\n"
                 "mad.lo.u32 a, %2, %3, %1;\n"
                 "mad.wide.u32 b, a, %5, %0;\n@p prefetch.global.L2 [b];\n}"
                 ::"l"(p.kc), "r"(threadIdx.x), "r"(blockIdx.x), "n"(PFN), "n"(128), "n"(128) : "memory");
    if (blockIdx.x >= 1024) return;
    extern __shared__ __align__(1024) char smem_raw[];
    const uint32_t sbase = (smem_u32(smem_raw) + 1023u) & ~1023u;
    char* smem = smem_raw + (sbase - smem_u32(smem_raw));
    const int tid = threadIdx.x, warp = __shfl_sync(~0u, tid >> 5, 0), lane = tid & 31;
    const int blk = blockIdx.x;
    const bool isB = CLU ? blk < NBCTA : (blk & 3) == 0 && (blk >> 2) < NBCTA;
    const int bi = CLU ? blk : blk >> 2;
    const int nb = CLU ? blk - NBCTA : blk - min(NBCTA, (blk + 3) >> 2);
    const int nblk = CLU ? 8 * MINCL : gridDim.x, nnb = nblk - NBCTA;
    const int nstatic = nnb * (NW + XW);
    uint64_t pol;
    asm volatile("createpolicy.fractional.L2::evict_first.b64 %0, 1.0;" : "=l"(pol));
    const uint32_t wbar = sbase + M_BAR + warp * 8, wslot = sbase + warp * SLOT;
    const int u0 = warp * nnb + nb;
    const bool hold = ((blk >> 2) >> KMIN << KMIN) * 4 * UPP < nstatic;
    const uint32_t jbar = sbase + M_BAR + (NSLOT + BRING) * 8;
    if (warp < 4) {
        mbar_init_warp(wbar);
        if (warp < NEARLY && !isB && !hold)
            tile_load_warp(wslot, reinterpret_cast<const char*>(p.kc) + (size_t)((u0 >> 7) * 1024 + (u0 & 127)) * TILE_BYTES, wbar, pol);
    }
    asm volatile("" ::: "memory");
    if (warp == 7) {
        if (blk < 128) {
            uint64_t poln;
            asm volatile("createpolicy.fractional.L2::evict_normal.b64 %0, 1.0;" : "=l"(poln));
            mbar_init_warp(jbar);
            tma3d_warp(sbase + J0W, &p.tm_j0, blk * 32, 0, 0, jbar, 36864 + 4 * 1152, poln);
            if (lane == 0) bulk_load(sbase + M_XA, p.xa, 4608, jbar, poln);
        }
        if (lane < 8) reinterpret_cast<unsigned*>(smem + M_HELP)[lane] = 0;
        __syncwarp();
        if (!isB) asm volatile("bar.arrive 2, %0;" ::"n"(32 * (NW + XW + 1)) : "memory");
    }
    unsigned epoch = 0;
    if (lane == 0) epoch = ld_relaxed4(scratch(p)->epoch);
    if (blk >= 128 ? warp >= 4 : isB && warp < 4) epoch = __shfl_sync(~0u, epoch, 0);
    if (isB && warp == 3) asm volatile("bar.sync 1, 160;" ::: "memory");
    if (isB && tid == 96) {
#pragma unroll 1
        for (int i = 0; i < BRING; i++) mbar_init(sbase + M_BAR + (NSLOT + i) * 8, 1);
        asm volatile("fence.mbarrier_init.release.cluster;" ::: "memory");
        if (hold) { unsigned n = 0; while (ld_acquire_cta_shared(sbase + M_HELP + 24) < 2) { if (++n > (SPIN_LIMIT << 4)) __trap(); } }
#pragma unroll 1
        for (int b = 0; b < 4; b++) bulk_load(sbase + M_XB + b * XP, p.xb + b * DM, 1152, sbase + M_BAR + NSLOT * 8, pol);
#pragma unroll 1
        for (int n = 0; n < BD; n++) b_issue(p, n, bi, sbase, pol);
    }
    if (warp >= 4 && blk < 128) {
        const int g = lane >> 2, t = lane & 3, j = tid - 128;
        asm volatile("bar.sync 1, %0;" ::"r"(isB ? 160 : 128) : "memory");
#pragma unroll 1
        for (int ph = -1;; ph++) {
        const int sl = ph > 0 ? blk + 128 - nblk : blk;
        STI(q1);
        if (ph >= 0) mbar_wait(jbar, ph);
        STI(q2);
        TS(13);
        float acc[4][4];
#pragma unroll
        for (int i = 0; i < 16; i++) acc[i >> 2][i & 3] = 0.f;
        const uint32_t wa = sbase + J0W + ((warp - 4) * 144 + (lane & 15)) * 64;
        const uint32_t sw = (lane >> 1) & 3, xa = sbase + M_XA + (g & 3) * 1152 + (warp - 4) * 288 + t * 4;
#pragma unroll 3
        for (int s = 0; s < 9; s++) {
            const uint32_t a[4] = {lds32(xa + s * 32), 0u, lds32(xa + s * 32 + 16), 0u};
            uint32_t w0[4], w1[4];
            ldsm4t(w0, wa + s * 1024 + (((lane >> 4) ^ sw) * 16));
            ldsm4t(w1, wa + s * 1024 + (((2 + (lane >> 4)) ^ sw) * 16));
            mma16816(acc[0], a, w0[0], w0[1]);
            mma16816(acc[1], a, w0[2], w0[3]);
            mma16816(acc[2], a, w1[0], w1[1]);
            mma16816(acc[3], a, w1[2], w1[3]);
        }
        STI(q3);
        epoch = __shfl_sync(~0u, epoch, 0);
        float2* j0 = reinterpret_cast<float2*>(smem + M_J0);
        if (g < 4) {
#pragma unroll
            for (int i = 0; i < 4; i++) j0[(warp - 4) * 64 + g * 16 + i * 4 + t] = make_float2(acc[i][0], acc[i][1]);
        }
        asm volatile("bar.sync 1, 128;" ::: "memory");
        const bool again = ph == 0 && blk + 128 - nblk >= nblk;
        if (again && tid == 224) {
            mbar_expect_tx(jbar, 36864);
            tma3d(sbase + J0W, &p.tm_j0, (blk + 128 - nblk) * 32, 0, 0, jbar, pol);
        }
        if (warp < 6) {
            const float2 v0 = j0[j], v1 = j0[64 + j], v2 = j0[128 + j], v3 = j0[192 + j];
            asm volatile("{\n.reg .pred p;\n.reg .b64 v;\nsetp.ge.s32 p, %3, 0;\nmov.b64 v, {%1, %2};\n@p st.relaxed.gpu.global.u64 [%0], v;\n}"
                         ::"l"(&scratch(p)->qll[(j >> 4) * 2048 + sl * 16 + (j & 15)]),
                           "r"(pack_bf16((v0.x + v1.x) + (v2.x + v3.x), (v0.y + v1.y) + (v2.y + v3.y))), "r"(epoch + 1), "r"(ph) : "memory");
            __syncwarp();
            if (lane == 0 && ph >= 0) asm volatile("red.relaxed.cta.shared::cta.add.u32 [%0], 1;" ::"r"(sbase + M_HELP + 24) : "memory");
        } else if (warp == 7) {
            if (blk < C_LINES && ph == 0) scratch(p)->ctl[(epoch & 1) ^ 1][blk][lane] = 0;
        }
        TS(1);
        if (ph >= 0 && !again) break;
        asm volatile("bar.sync 1, 128;" ::: "memory");
        }
    }
    if (CLU) {
        if (warp == 6) {
            if (lane < 16 && lane != 1) mbar_init(sbase + F_BAR + lane * 8, 1);
            if ((lane >> 1) == 1) mbar_expect_tx(sbase + F_BAR + lane * 8, 1024);
            asm volatile("fence.mbarrier_init.release.cluster;" ::: "memory");
        }
        asm volatile("barrier.cluster.arrive.relaxed.aligned;" ::: "memory");
    }
    const int cl = blk >> 3, rank = blk & 7;
    const bool partA = CLU && cl >= 4 && cl < 13;
    if (isB) {
        b_chain<CLU>(p, smem, sbase, bi, epoch, pol);
        if (!CLU) return;
    } else if (warp < NW + XW) {
        a_worker<CLU>(p, u0, warp >= NW + ((CLU ? rank < X3C : (nb & 3) < X3) ? 1 : 0), warp < NEARLY && !hold, hold, nstatic, wslot, wbar, sbase + M_HELP,
                      epoch, pol);
        if (!CLU || warp < (partA && rank == 7 ? 2 : 3)) return;
        epoch = __shfl_sync(~0u, epoch, 0);
        unsigned n = 0;
        while (ld_acquire_cta_shared(sbase + M_HELP + 12) == 0) { __nanosleep(1000); if (++n > SPIN_LIMIT) __trap(); }
    } else if (warp == 7) {
#pragma unroll 1
        for (int i = nb; i < 4 * NH; i += nnb) scratch(p)->oacc[i * 32 + lane] = make_float4(0.f, 0.f, 0.f, 0.f);
        if (nb < NREP * NH) scratch(p)->vdone[nb][lane] = 0;
        __syncwarp();
        k_helper(p, sbase + M_HELP, epoch);
        if (nb == 0 && lane == 0) scratch(p)->epoch[0] = epoch + 1;
        __syncwarp();
    } else if (!CLU && nb < NFIN) {
        if (warp == 6) {
            finisher(p, sbase, nb);
            TS(4);
        } else if (warp >= 6 - NPOLL) {
            v_poller(p, sbase, nb, warp - (6 - NPOLL));
        }
    }
    if (!CLU || cl > 13) return;
    asm volatile("barrier.cluster.wait.acquire.aligned;" ::: "memory");
    if (isB ? warp == 0 : warp < 4) {
        f_collect((partA ? scratch(p)->vdone : scratch(p)->cdone) + 4 * rank, partA ? 4 * UPP : epoch + 1, (partA ? scratch(p)->oacc : scratch(p)->octx) + 4 * rank * 128,
                  partA && rank == 7 ? (warp == 2 ? 10 : 5) : 15, sbase);
        if (warp == 2) return;
    }
    const int sl = isB ? warp >> 2 : 0, panel = isB ? 2 * cl + sl : min(cl - 4, 8);
#pragma unroll 1
    for (int i = 0;; i++) {
        if (isB ? (warp & 3) == 0 : warp == 3) f_receive(p, p.out + (partA ? 0 : DM) + panel * 64 + rank * 8, sl, i == 0, sbase);
        if (i) return;
        if (isB || warp >= 4)
            f_project(p, partA ? &p.tm_fa : &p.tm_fb, panel, rank, warp, sl,
                      isB ? B0 + (warp & 3) * BJ + sl * BS + rank * (BJ / 8) : A0 + (warp & 3) * AJ + rank * (AJ / 8), epoch + 1, sbase, pol);
    }
}

}

typedef CUresult (*EncodeFn)(CUtensorMap*, CUtensorMapDataType, cuuint32_t, void*, const cuuint64_t*, const cuuint64_t*,
                             const cuuint32_t*, const cuuint32_t*, CUtensorMapInterleave, CUtensorMapSwizzle,
                             CUtensorMapL2promotion, CUtensorMapFloatOOBfill);

extern "C" void kernel_launch(void* const* d_in, const int* in_sizes, int n_in, void* d_out, int out_size) {
    (void)in_sizes; (void)n_in; (void)out_size;
    static int nsm = 0, ncl = 0;
    static EncodeFn encode = nullptr;
    static void* scr = nullptr;
    cudaLaunchConfig_t cfg = {};
    cudaLaunchAttribute at[1];
    at[0].id = cudaLaunchAttributeClusterDimension;
    at[0].val.clusterDim.x = 8; at[0].val.clusterDim.y = 1; at[0].val.clusterDim.z = 1;
    cfg.blockDim = dim3(256); cfg.dynamicSmemBytes = SMEM_BYTES; cfg.stream = cudaStreamPerThread; cfg.attrs = at; cfg.numAttrs = 1;
    if (nsm == 0) {
        int dev = 0;
        cudaGetDevice(&dev);
        cudaDeviceGetAttribute(&nsm, cudaDevAttrMultiProcessorCount, dev);
        cudaFuncSetAttribute(fused_decode_kernel<false>, cudaFuncAttributeMaxDynamicSharedMemorySize, SMEM_BYTES);
        cudaFuncSetAttribute(fused_decode_kernel<true>, cudaFuncAttributeMaxDynamicSharedMemorySize, SMEM_BYTES);
        cfg.gridDim = dim3(128);
        if (cudaOccupancyMaxActiveClusters(&ncl, fused_decode_kernel<true>, &cfg) != cudaSuccess) { ncl = 0; (void)cudaGetLastError(); }
        if (ncl > MINCL) ncl = MINCL;
        void* fn = nullptr;
        cudaDriverEntryPointQueryResult qr;
        cudaGetDriverEntryPoint("cuTensorMapEncodeTiled", &fn, cudaEnableDefault, &qr);
        encode = (EncodeFn)fn;
        cudaGetSymbolAddress(&scr, g_scratch);
    }
    Params p;
    auto panels = [&](CUtensorMap* tm, void* ptr, int rows, int cols, int box_rows, int box_panels,
                      CUtensorMapL2promotion promo = CU_TENSOR_MAP_L2_PROMOTION_L2_256B) {
        const cuuint64_t gd[3] = {64, (cuuint64_t)rows, (cuuint64_t)(cols / 64)}, gs[2] = {(cuuint64_t)cols * 2, 128};
        const cuuint32_t box[3] = {64, (cuuint32_t)box_rows, (cuuint32_t)box_panels}, es[3] = {1, 1, 1};
        encode(tm, CU_TENSOR_MAP_DATA_TYPE_BFLOAT16, 3, ptr, gd, gs, box, es, CU_TENSOR_MAP_INTERLEAVE_NONE,
               CU_TENSOR_MAP_SWIZZLE_128B, promo, CU_TENSOR_MAP_FLOAT_OOB_FILL_NONE);
    };
    panels(&p.tm_wq, d_in[7], DM, 4096, 128, 2);
    panels(&p.tm_wuk, d_in[8], 512, 4096, 128, 2);
    panels(&p.tm_wuv, d_in[9], 512, 4096, 128, 2);
    panels(&p.tm_wo, d_in[10], 4096, DM, 32, 9);
    panels(&p.tm_ckv, d_in[6], 4 * SK, 512, 32, 8);
    panels(&p.tm_fa, d_in[4], 4096, DM, 128, 1, CU_TENSOR_MAP_L2_PROMOTION_L2_128B);
    panels(&p.tm_fb, d_in[10], 4096, DM, 128, 1, CU_TENSOR_MAP_L2_PROMOTION_L2_128B);
    {
        const cuuint64_t gd[3] = {4096, 192, 3}, gs[2] = {8192, 192 * 8192};
        const cuuint32_t box[3] = {32, 192, 3}, es[3] = {1, 1, 1};
        encode(&p.tm_j0, CU_TENSOR_MAP_DATA_TYPE_BFLOAT16, 3, d_in[3], gd, gs, box, es, CU_TENSOR_MAP_INTERLEAVE_NONE,
               CU_TENSOR_MAP_SWIZZLE_64B, CU_TENSOR_MAP_L2_PROMOTION_L2_128B, CU_TENSOR_MAP_FLOAT_OOB_FILL_NONE);
    }
    p.xa = (const __nv_bfloat16*)d_in[0];
    p.kc = (const __nv_bfloat16*)d_in[1];
    p.vc = (const __nv_bfloat16*)d_in[2];
    p.wo = (const __nv_bfloat16*)d_in[4];
    p.xb = (const __nv_bfloat16*)d_in[5];
    p.out = (__nv_bfloat16*)d_out;
    p.s = (Scratch*)scr;
    if (ncl >= MINCL) {
        cfg.gridDim = dim3(8 * ncl);
        cudaLaunchKernelEx(&cfg, fused_decode_kernel<true>, p);
    } else {
        fused_decode_kernel<false><<<nsm, 256, SMEM_BYTES, cudaStreamPerThread>>>(p);
    }
}
```

```cpp
#include <cuda_runtime.h>
#include <cuda.h>
#include <cuda_bf16.h>
#include <stdint.h>

namespace {

constexpr int NH = 32, SK = 4096, DM = 576;
constexpr int KEYS = 128;
constexpr int UPP = SK / KEYS;
constexpr int NUK = 4 * NH * UPP;
constexpr int TILE_BYTES = KEYS * 256;
#define NWORK 2
constexpr int NW = NWORK;
constexpr int NBCTA = 32;
constexpr int MINCL = 15;
constexpr int NFIN = 72;
constexpr int SLOT = 32768;
constexpr int NSLOT = 6;
constexpr int BRING = 5;
constexpr int J0W = 5 * SLOT;
constexpr int MISC = NSLOT * SLOT + 4096;
constexpr int XP = 1168, CP = 1040, QP = 272;
constexpr int M_XA = MISC;
constexpr int M_XB = M_XA + 4 * XP;
constexpr int M_CH = M_XB + 4 * XP;
constexpr int M_CL = M_CH + 4 * CP;
constexpr int M_QB = M_CL + 4 * CP;
constexpr int M_QA = M_CH;
constexpr int M_J0 = M_QB + 4 * QP;
constexpr int M_P = M_J0 + 2048;
constexpr int M_ALPHA = M_P + 2560;
constexpr int M_OMEGA = M_ALPHA + 128;
constexpr int M_BAR = M_OMEGA + 128;
constexpr int M_HELP = M_BAR + 128;
constexpr int F_W = 4 * SLOT;
constexpr int F_BF = (M_HELP + 383) / 256 * 256;
constexpr int F_RX = F_BF + 4096;
constexpr int F_BAR = F_RX + 2048;
constexpr int SMEM_BYTES = F_BAR + 192 + 1024;
static_assert(SMEM_BYTES <= 232448 && M_BAR % 8 == 0 && M_QA % 16 == 0 && M_P % 16 == 0, "smem layout");
#define XW 2
#define X3 1
#define X3C 5
#define NEARLY 2
#define BD 5
#define FPF 3
#define FSLEEP 800
#define VS0 24
#define PFN 96
#define EARLY 100
#define ELOG 5
#define TPU 159
#define A0 (1660 + 185 * X3C)
#define AJ 390
#define B0 (A0 - 400)
#define BJ 195
#define LAG 5
#define NPOLL 2
#define PGAP 200
static_assert(X3C <= 6 && NW == 2, "warp 2 of rank 7 is free");
static_assert(NW + XW <= 4 && NEARLY <= NW + XW && BD <= BRING, "slots 4 and 5 hold the finisher weights");
constexpr int KMIN = 2, KMAX = 4, VMIN = 0, VMAX = 4;
constexpr float SCALE = 0.08838834764831845f;
constexpr float LOG2E = 1.4426950408889634f;
constexpr unsigned SPIN_LIMIT = 1u << 24;

#define NREP 2
#define NREPC 1
constexpr int C_QUEUE = 0, C_KDONE = 1, C_BBAR = 3, C_LINES = 5;

struct Scratch {
    unsigned epoch[32];
    unsigned ctl[2][C_LINES][32];
    uint2 qll[4 * 2048];
    uint2 scores[128 * SK / 4];
    float2 stats[128 * UPP];
    float4 oacc[128 * 32];
    unsigned vdone[NREP * NH][32];
    float4 octx[128 * 32];
    unsigned cdone[NH][32];
    unsigned long long dry[16][16];
    uint4 qabs[4 * 8 * 4 * 4 * 32];
    float2 bpart[NBCTA * NH * 256];
    float2 bml[NBCTA * NH];
    uint4 outb[NBCTA * NH * 36];
};
__device__ __align__(256) Scratch g_scratch;

struct Params {
    const __nv_bfloat16 *kc, *xa, *vc, *wo, *xb;
    __nv_bfloat16* out;
    Scratch* s;
    CUtensorMap tm_j0;
    CUtensorMap tm_wq, tm_wuk, tm_ckv, tm_wuv, tm_wo;
    CUtensorMap tm_fa, tm_fb;
};

__device__ __forceinline__ Scratch* scratch(const Params& p) {
    Scratch* s = p.s;
    __builtin_assume(__isGlobal(s));
    return s;
}

#define STI(v)
#define TS(i)
#define TSV(i, v)
#define LAND(i)
#define CLK(x)
#define ACC(a, x, y)

__device__ __forceinline__ uint32_t smem_u32(const void* p) { return (uint32_t)__cvta_generic_to_shared(p); }
__device__ __forceinline__ void mbar_init(uint32_t bar, uint32_t cnt) {
    asm volatile("mbarrier.init.shared::cta.b64 [%0], %1;" ::"r"(bar), "r"(cnt) : "memory");
}
__device__ __forceinline__ void mbar_expect_tx(uint32_t bar, uint32_t bytes) {
    asm volatile("mbarrier.arrive.expect_tx.shared::cta.b64 _, [%0], %1;" ::"r"(bar), "r"(bytes) : "memory");
}
__device__ __forceinline__ bool mbar_try(uint32_t bar, uint32_t parity) {
    uint32_t ok;
    asm volatile("{\n.reg .pred p;\nmbarrier.try_wait.parity.shared::cta.b64 p, [%1], %2;\nselp.u32 %0, 1, 0, p;\n}\n"
                 : "=r"(ok) : "r"(bar), "r"(parity) : "memory");
    return ok;
}
__device__ __forceinline__ void mbar_wait(uint32_t bar, uint32_t parity) {
    unsigned n = 0;
    while (!mbar_try(bar, parity)) { if (++n > SPIN_LIMIT) __trap(); }
}
__device__ __forceinline__ void mbar_spin(uint32_t bar) {
    asm volatile("{\n.reg .pred p;\n.reg .u32 n;\nmov.u32 n, 0;\nSPIN:\nmbarrier.try_wait.parity.shared::cta.b64 p, [%0], 0;\n@p bra.uni DONE;\n"
                 "add.u32 n, n, 1;\nsetp.lt.u32 p, n, 0x1000000;\n@p bra.uni SPIN;\ntrap;\nDONE:\n}" ::"r"(bar) : "memory");
}
__device__ __forceinline__ void mbar_spin_cluster(uint32_t bar) {
    asm volatile("{\n.reg .pred p;\n.reg .u32 n;\nmov.u32 n, 0;\nSPIN:\nmbarrier.try_wait.parity.relaxed.cluster.shared::cta.b64 p, [%0], 0;\n"
                 "@p bra.uni DONE;\nadd.u32 n, n, 1;\nsetp.lt.u32 p, n, 0x1000000;\n@p bra.uni SPIN;\ntrap;\nDONE:\n"
                 "fence.acquire.sync_restrict::shared::cluster.cluster;\n}" ::"r"(bar) : "memory");
}
__device__ __forceinline__ void bulk_load(uint32_t dst, const void* src, uint32_t bytes, uint32_t bar, uint64_t pol) {
    asm volatile("cp.async.bulk.shared::cluster.global.mbarrier::complete_tx::bytes.L2::cache_hint [%0], [%1], %2, [%3], %4;"
                 ::"r"(dst), "l"(src), "r"(bytes), "r"(bar), "l"(pol) : "memory");
}
__device__ __forceinline__ void mbar_init_warp(uint32_t bar) {
    asm volatile("{\n.reg .pred p;\nelect.sync _|p, 0xffffffff;\n@p mbarrier.init.shared::cta.b64 [%0], 1;\n@p fence.mbarrier_init.release.cluster;\n}"
                 ::"r"(bar) : "memory");
}
__device__ __forceinline__ void tile_load_warp(uint32_t dst, const void* src, uint32_t bar, uint64_t pol) {
    asm volatile("{\n.reg .pred p;\nelect.sync _|p, 0xffffffff;\n@p mbarrier.arrive.expect_tx.shared::cta.b64 _, [%2], %4;\n"
                 "@p cp.async.bulk.shared::cluster.global.mbarrier::complete_tx::bytes.L2::cache_hint [%0], [%1], %4, [%2], %3;\n}"
                 ::"r"(dst), "l"(src), "r"(bar), "l"(pol), "n"(TILE_BYTES) : "memory");
}
__device__ __forceinline__ void tma3d_warp(uint32_t dst, const CUtensorMap* tm, int c0, int c1, int c2, uint32_t bar, uint32_t bytes, uint64_t pol) {
    asm volatile("{\n.reg .pred p;\nelect.sync _|p, 0xffffffff;\n@p mbarrier.arrive.expect_tx.shared::cta.b64 _, [%2], %7;\n"
                 "@p cp.async.bulk.tensor.3d.shared::cluster.global.mbarrier::complete_tx::bytes.L2::cache_hint [%0], [%1, {%3,%4,%5}], [%2], %6;\n}"
                 ::"r"(dst), "l"(tm), "r"(bar), "r"(c0), "r"(c1), "r"(c2), "l"(pol), "r"(bytes) : "memory");
}
__device__ __forceinline__ void tma3d(uint32_t dst, const CUtensorMap* tm, int c0, int c1, int c2, uint32_t bar, uint64_t pol) {
    asm volatile("cp.async.bulk.tensor.3d.shared::cluster.global.mbarrier::complete_tx::bytes.L2::cache_hint [%0], [%1, {%3,%4,%5}], [%2], %6;"
                 ::"r"(dst), "l"(tm), "r"(bar), "r"(c0), "r"(c1), "r"(c2), "l"(pol) : "memory");
}
__device__ __forceinline__ void l2_prefetch(const void* src, uint32_t bytes) {
    asm volatile("cp.async.bulk.prefetch.L2.global [%0], %1;" ::"l"(src), "r"(bytes) : "memory");
}
__device__ __forceinline__ void ldsm4(uint32_t (&r)[4], uint32_t addr) {
    asm volatile("ldmatrix.sync.aligned.m8n8.x4.shared.b16 {%0,%1,%2,%3}, [%4];"
                 : "=r"(r[0]), "=r"(r[1]), "=r"(r[2]), "=r"(r[3]) : "r"(addr));
}
__device__ __forceinline__ void ldsm4t(uint32_t (&r)[4], uint32_t addr) {
    asm volatile("ldmatrix.sync.aligned.m8n8.x4.trans.shared.b16 {%0,%1,%2,%3}, [%4];"
                 : "=r"(r[0]), "=r"(r[1]), "=r"(r[2]), "=r"(r[3]) : "r"(addr));
}
__device__ __forceinline__ void mma16816(float (&d)[4], const uint32_t (&a)[4], uint32_t b0, uint32_t b1) {
    asm("mma.sync.aligned.m16n8k16.row.col.f32.bf16.bf16.f32 {%0,%1,%2,%3}, {%4,%5,%6,%7}, {%8,%9}, {%0,%1,%2,%3};"
        : "+f"(d[0]), "+f"(d[1]), "+f"(d[2]), "+f"(d[3])
        : "r"(a[0]), "r"(a[1]), "r"(a[2]), "r"(a[3]), "r"(b0), "r"(b1));
}
__device__ __forceinline__ uint32_t lds32(uint32_t a) {
    uint32_t v;
    asm volatile("ld.shared.u32 %0, [%1];" : "=r"(v) : "r"(a));
    return v;
}
__device__ __forceinline__ unsigned ld_acquire(const unsigned* p) {
    unsigned v;
    asm volatile("ld.acquire.gpu.global.u32 %0, [%1];" : "=r"(v) : "l"(p) : "memory");
    return v;
}
__device__ __forceinline__ uint2 ld_relaxed8(const void* p) {
    uint2 v;
    asm volatile("ld.relaxed.gpu.global.v2.u32 {%0,%1}, [%2];" : "=r"(v.x), "=r"(v.y) : "l"(p) : "memory");
    return v;
}
__device__ __forceinline__ unsigned ld_relaxed4(const void* p) {
    unsigned v;
    asm volatile("ld.relaxed.gpu.global.u32 %0, [%1];" : "=r"(v) : "l"(p) : "memory");
    return v;
}
__device__ __forceinline__ unsigned atom_inc(unsigned* p) {
    unsigned v;
    asm volatile("atom.relaxed.gpu.global.inc.u32 %0, [%1], 0x7fffffff;" : "=r"(v) : "l"(p) : "memory");
    return v;
}
__device__ __forceinline__ unsigned long long ld_relaxed64(const void* p) {
    unsigned long long v;
    asm volatile("ld.relaxed.gpu.global.u64 %0, [%1];" : "=l"(v) : "l"(p) : "memory");
    return v;
}
__device__ __forceinline__ void st_relaxed64(void* p, unsigned long long v) {
    asm volatile("st.relaxed.gpu.global.u64 [%0], %1;" ::"l"(p), "l"(v) : "memory");
}
__device__ __forceinline__ float4 ld_relaxed16(const void* p) {
    float4 v;
    asm volatile("ld.relaxed.gpu.global.v4.f32 {%0,%1,%2,%3}, [%4];" : "=f"(v.x), "=f"(v.y), "=f"(v.z), "=f"(v.w) : "l"(p) : "memory");
    return v;
}
__device__ __forceinline__ uint32_t mapa(uint32_t a, uint32_t rank) {
    uint32_t r;
    asm("mapa.shared::cluster.u32 %0, %1, %2;" : "=r"(r) : "r"(a), "r"(rank));
    return r;
}
__device__ __forceinline__ uint32_t time_ns() { uint32_t t; asm volatile("mov.u32 %0, %globaltimer_lo;" : "=r"(t)); return t; }
__device__ __forceinline__ void fence_gpu() { asm volatile("fence.acq_rel.gpu;" ::: "memory"); }
__device__ __forceinline__ void red_add_u32(unsigned* p, unsigned v) {
    asm volatile("red.relaxed.gpu.global.add.u32 [%0], %1;" ::"l"(p), "r"(v) : "memory");
}
__device__ __forceinline__ void st_tagged2(void* p, float a, float b, unsigned tag) {
    const unsigned long long hi = (unsigned long long)tag << 32;
    asm volatile("st.relaxed.gpu.global.v2.b64 [%0], {%1,%2};" ::"l"(p), "l"(hi | __float_as_uint(a)), "l"(hi | __float_as_uint(b)) : "memory");
}
__device__ __forceinline__ ulonglong2 ld_tagged2(const void* p) {
    ulonglong2 v;
    asm volatile("ld.relaxed.gpu.global.v2.b64 {%0,%1}, [%2];" : "=l"(v.x), "=l"(v.y) : "l"(p) : "memory");
    return v;
}
__device__ __forceinline__ float4 atom_add_f4(void* p, float a, float b, float c, float d) {
    float4 r;
    asm volatile("atom.relaxed.gpu.global.add.v4.f32 {%0,%1,%2,%3}, [%4], {%5,%6,%7,%8};"
                 : "=f"(r.x), "=f"(r.y), "=f"(r.z), "=f"(r.w) : "l"(p), "f"(a), "f"(b), "f"(c), "f"(d) : "memory");
    return r;
}
__device__ __forceinline__ void red_release_cta_shared(uint32_t a, unsigned v) {
    asm volatile("red.release.cta.shared::cta.add.u32 [%0], %1;" ::"r"(a), "r"(v) : "memory");
}
__device__ __forceinline__ unsigned ld_acquire_cta_shared(uint32_t a) {
    unsigned v;
    asm volatile("ld.acquire.cta.shared::cta.u32 %0, [%1];" : "=r"(v) : "r"(a) : "memory");
    return v;
}
__device__ __forceinline__ void st_release_cta_shared(uint32_t a, unsigned v) {
    asm volatile("st.release.cta.shared::cta.u32 [%0], %1;" ::"r"(a), "r"(v) : "memory");
}
__device__ __forceinline__ void wait_count(const unsigned* p, unsigned target) {
    unsigned n = 0;
    while (ld_acquire(p) < target) { if (++n > SPIN_LIMIT) __trap(); }
}
__device__ __forceinline__ uint32_t pack_bf16(float lo, float hi) {
    uint32_t r;
    asm("cvt.rn.bf16x2.f32 %0, %1, %2;" : "=r"(r) : "f"(hi), "f"(lo));
    return r;
}
__device__ __forceinline__ float bf_lo(uint32_t v) { return __uint_as_float(v << 16); }
__device__ __forceinline__ float bf_hi(uint32_t v) { return __uint_as_float(v & 0xffff0000u); }
__device__ __forceinline__ float ex2(float x) { float y; asm("ex2.approx.ftz.f32 %0, %1;" : "=f"(y) : "f"(x)); return y; }
__device__ __forceinline__ float expsub(float a, float b) { return ex2((a - b) * LOG2E); }
__device__ __forceinline__ float warp_max(float v) {
#pragma unroll
    for (int m = 16; m; m >>= 1) v = fmaxf(v, __shfl_xor_sync(~0u, v, m));
    return v;
}
__device__ __forceinline__ float warp_sum(float v) {
#pragma unroll
    for (int m = 16; m; m >>= 1) v += __shfl_xor_sync(~0u, v, m);
    return v;
}
template <bool CLU>
__device__ __forceinline__ unsigned unit_block(int u) {
    const unsigned x = ((unsigned)u & (NUK - 1)) / UPP;
    const int lg = u < NUK ? min(KMAX, max(KMIN, 29 - __clz(x | 1))) : (CLU && (int)x >= 4 * VS0 ? 0 : min(VMAX, max(VMIN, 29 - __clz((127 - x) | 1))));
    const unsigned r = x & ((4u << lg) - 1);
    return ((x - r + (r & ((1u << lg) - 1)) * 4 + (r >> lg)) * UPP) | ((unsigned)u & (UPP - 1));
}
__device__ __forceinline__ const char* block_src(const void* base, unsigned blk) {
    const unsigned po = blk / UPP;
    return reinterpret_cast<const char*>(base) + (size_t)(((po & 3) * NH + (po >> 2)) * UPP + blk % UPP) * TILE_BYTES;
}

template <bool CLU>
__device__ __forceinline__ void a_worker(const Params& p, int un, bool once, bool pre, bool hold, int nstatic, uint32_t slot, uint32_t bar,
                                         uint32_t help, unsigned epoch, uint64_t pol) {
    constexpr int NU = 2 * NUK, NR = CLU ? NREPC : NREP;
    const int lane = threadIdx.x & 31, g = lane >> 2, t = lane & 3;
    const int li = lane & 7;
    uint32_t kaddr[4], vaddr[8];
    {
        const int e = (lane >> 3) & 1, kk = lane >> 4;
#pragma unroll
        for (int s = 0; s < 4; s++) kaddr[s] = slot + (16 * li + e) * 256 + ((2 * s + kk + li) & 7) * 16;
        const int vrow = 4 * (li >> 1) + (li & 1) + 2 * kk;
#pragma unroll
        for (int c = 0; c < 8; c++) vaddr[c] = slot + vrow * 256 + e * 128 + ((c + li) & 7) * 16;
#pragma unroll
        for (int c = 0; c < 8; c++) asm volatile("" : "+r"(vaddr[c]));
    }
    const uint32_t vmask = (g >> 1) != t ? 0u : ((g & 1) ? 0xffff0000u : 0xffffu);
    int kseen = -1;
    unsigned long long H0 = 0, H1 = 0;
    auto header = [&](int v, unsigned vb) {
        const void *a0, *a1;
        if (v < NUK) {
            const unsigned po = vb / UPP;
            a0 = scratch(p)->qll + (po & 3) * 2048 + (po >> 2) * 64 + lane;
            a1 = reinterpret_cast<const uint2*>(a0) + 32;
        } else {
            const int half = vb / (NUK / 2);
            if (half > kseen) {
                unsigned n = 0;
                while (ld_acquire_cta_shared(help + 12 + 4 * half) == 0) { if (++n > (SPIN_LIMIT << 4)) __trap(); }
                kseen = half;
            }
            a0 = &scratch(p)->scores[vb * (KEYS / 4) + lane];
            a1 = &scratch(p)->stats[(vb / UPP) * UPP + lane];
        }
        H0 = ld_relaxed64(a0);
        H1 = ld_relaxed64(a1);
    };
    unsigned bu = 0, bn = unit_block<CLU>(un);
    asm volatile("bar.sync 2, %0;" ::"n"(32 * (NW + XW + 1)) : "memory");
    epoch = __shfl_sync(~0u, epoch, 0);
    if (hold) { unsigned n = 0; while (ld_acquire_cta_shared(help + 24) < 2) { if (++n > (SPIN_LIMIT << 4)) __trap(); } }
    unsigned (*ctl)[32] = scratch(p)->ctl[epoch & 1];
    const unsigned tag = epoch + 1;
    unsigned nxt = once ? NU : 0;
    int u = -1;
    uint32_t phase = 0;
    unsigned kpend = 0;
    const unsigned zero = gridDim.x >> 24;
    uint32_t Q[16];
    float4 oret = make_float4(0.f, 0.f, 0.f, 0.f);
    while (true) {
        const char* nsrc = block_src(un < NUK ? p.kc : p.vc, bn);
        float4* odst = &scratch(p)->oacc[(bu / UPP) * 32 + lane];
        unsigned* vdst = &scratch(p)->vdone[(lane & (NR - 1)) * NH + bu / (4 * UPP)][0];
        float d[8][4];
        CLK(c1);
        uint32_t act = un >= NU ? 0u : (u >= 0 || !pre ? 1u : 0u) | (!once && lane == 0 ? 2u : 0u);
        asm volatile("" : "+l"(odst), "+l"(nsrc), "+r"(act));
        if (u >= NUK) {
#pragma unroll
            for (int j = 0; j < 8; j++) { d[j][0] = d[j][1] = d[j][2] = d[j][3] = 0.f; }
            mbar_wait(bar, phase);
            LAND(NUK + bu);
            uint32_t a[2][8][4];
#pragma unroll
            for (int c = 0; c < 8; c++) ldsm4t(a[0][c], vaddr[c]);
#pragma unroll
            for (int j = 0; j < 8; j++) {
                if (j < 7) {
#pragma unroll
                    for (int c = 0; c < 8; c++) ldsm4t(a[(j + 1) & 1][c], vaddr[c] + (j + 1) * 4096);
                }
#pragma unroll
                for (int c = 0; c < 8; c++) mma16816(d[c], a[j & 1][c], Q[2 * j], Q[2 * j + 1]);
            }
            float o[4];
#pragma unroll
            for (int r = 0; r < 2; r++) {
                o[2 * r] = d[0][2 * r] + d[7][2 * r + 1];
                o[2 * r + 1] = d[0][2 * r + 1] + d[1][2 * r];
#pragma unroll
                for (int k = 1; k < 4; k++) {
                    const int src = (lane & 28) | ((t - k) & 3);
                    o[2 * r] += __shfl_sync(~0u, d[2 * k][2 * r] + d[2 * k - 1][2 * r + 1], src);
                    o[2 * r + 1] += __shfl_sync(~0u, d[2 * k][2 * r + 1] + d[2 * k + 1][2 * r], src);
                }
            }
            oret = atom_add_f4(odst, o[0], o[1], o[2], o[3]);
        } else if (u >= 0) {
#pragma unroll
            for (int j = 0; j < 8; j++) { d[j][0] = d[j][1] = d[j][2] = d[j][3] = 0.f; }
            mbar_wait(bar, phase);
            LAND(bu);
            uint32_t a[2][8][4];
#pragma unroll
            for (int j = 0; j < 8; j++) ldsm4(a[0][j], kaddr[0] + (4 * (j & 3) + 2 * (j >> 2)) * 256);
#pragma unroll
            for (int s = 0; s < 8; s++) {
                if (s < 7) {
#pragma unroll
                    for (int j = 0; j < 8; j++)
                        ldsm4(a[(s + 1) & 1][j], kaddr[(s + 1) & 3] + (4 * (j & 3) + 2 * (j >> 2)) * 256 + ((s + 1) >> 2) * 128);
                }
#pragma unroll
                for (int j = 0; j < 8; j++)
                    mma16816(d[j], a[s & 1][j], Q[(s & 4) * 2 + ((2 * s - 2 * j) & 7)], Q[(s & 4) * 2 + ((2 * s + 1 - 2 * j) & 7)]);
            }
        }
        if (u >= 0) phase ^= 1;
        CLK(c2b);
        asm volatile("{\n.reg .pred p, q;\n.reg .u32 a;\nelect.sync _|p, 0xffffffff;\nand.b32 a, %5, 1;\nsetp.ne.and.u32 q, a, 0, p;\n"
                     "@q mbarrier.arrive.expect_tx.shared::cta.b64 _, [%2], %4;\n"
                     "@q cp.async.bulk.shared::cluster.global.mbarrier::complete_tx::bytes.L2::cache_hint [%0], [%1], %4, [%2], %3;\n}"
                     ::"r"(slot), "l"(nsrc), "r"(bar), "l"(pol), "n"(TILE_BYTES), "r"(act) : "memory");
        if (act & 2) nxt = atom_inc(&ctl[C_QUEUE][0]);
        const uint32_t tk = clock();
        CLK(c3);
        if ((unsigned)u < (unsigned)NUK) {
            const int j0 = (t - (g >> 1)) & 3;
            float v[4];
#pragma unroll
            for (int q = 0; q < 4; q++) {
                const int jq = (q >> 1) * 4, e = (q & 1) * 2;
                const float x0 = (g & 1) ? d[jq + 0][e + 1] : d[jq + 0][e];
                const float x1 = (g & 1) ? d[jq + 1][e + 1] : d[jq + 1][e];
                const float x2 = (g & 1) ? d[jq + 2][e + 1] : d[jq + 2][e];
                const float x3 = (g & 1) ? d[jq + 3][e + 1] : d[jq + 3][e];
                const float y0 = (j0 & 1) ? x1 : x0, y1 = (j0 & 1) ? x3 : x2;
                v[q] = (j0 & 2) ? y1 : y0;
            }
            const uint32_t r0 = pack_bf16(v[0], v[1]), r1 = pack_bf16(v[2], v[3]);
            const uint32_t s0 = pack_bf16(bf_lo(r0) * SCALE, bf_hi(r0) * SCALE);
            const uint32_t s1 = pack_bf16(bf_lo(r1) * SCALE, bf_hi(r1) * SCALE);
            scratch(p)->scores[bu * (KEYS / 4) + 4 * g + j0] = make_uint2(s0, s1);
            const float f0 = bf_lo(s0), f1 = bf_hi(s0), f2 = bf_lo(s1), f3 = bf_hi(s1);
            const float m = warp_max(fmaxf(fmaxf(f0, f1), fmaxf(f2, f3)));
            const float l = warp_sum((expsub(f0, m) + expsub(f1, m)) + (expsub(f2, m) + expsub(f3, m)));
            if (lane == 0) scratch(p)->stats[bu] = make_float2(m, l);
            kpend++;
            if (un / (NUK / 2) != u / (NUK / 2)) {
                __syncwarp();
                if (lane == 0) {
                    red_release_cta_shared(help + 4 * (u / (NUK / 2)), kpend);
                    if (un >= NUK) red_release_cta_shared(help + 8, 1u);
                }
                kpend = 0;
            }
        }
        CLK(c4);
        int unn = NU;
        if (un < NU) {
            unsigned n = 0;
            while (true) {
                header(un, bn);
                if (un >= NUK || __all_sync(~0u, (uint32_t)(H0 >> 32) == tag && (uint32_t)(H1 >> 32) == tag)) break;
                if (++n > SPIN_LIMIT) __trap();
            }
            if (un >= NUK) {
                const uint32_t s0 = (uint32_t)H0, s1 = (uint32_t)(H0 >> 32);
                const float mu = __uint_as_float((uint32_t)H1);
                const float m = warp_max(mu);
                const float l = warp_sum(__uint_as_float((uint32_t)(H1 >> 32)) * expsub(mu, m));
                const float inv = 1.0f / l;
                const uint32_t w0 = pack_bf16(expsub(bf_lo(s0), m) * inv, expsub(bf_hi(s0), m) * inv);
                const uint32_t w1 = pack_bf16(expsub(bf_lo(s1), m) * inv, expsub(bf_hi(s1), m) * inv);
#pragma unroll
                for (int j = 0; j < 8; j++) {
                    Q[2 * j] = __shfl_sync(~0u, w0, 4 * j + t) & vmask;
                    Q[2 * j + 1] = __shfl_sync(~0u, w1, 4 * j + t) & vmask;
                }
            } else {
#pragma unroll
                for (int j = 0; j < 8; j++) {
                    const int src = (((j + g) & 7) << 2) + t;
                    Q[j] = __shfl_sync(~0u, (uint32_t)H0, src);
                    Q[8 + j] = __shfl_sync(~0u, (uint32_t)H1, src);
                }
            }
            unn = nstatic + (int)__shfl_sync(~0u, nxt, 0);
            if (CLU && ((NU - EARLY - unn) & ~(7 << ELOG)) == 0 && lane < MINCL)
                st_relaxed64(&scratch(p)->dry[lane][(NU - EARLY - unn) >> ELOG],
                             (time_ns() - (((uint32_t)clock() - tk) >> 1) + (NU - unn) * TPU / 16) | (unsigned long long)tag << 32);
        }
        if (u >= NUK && lane < NR)
            red_add_u32(vdst,
                        1u + ((__float_as_uint(oret.x) | __float_as_uint(oret.y) | __float_as_uint(oret.z) | __float_as_uint(oret.w)) & zero));
        if (un >= NU) break;
        bu = bn;
        bn = unit_block<CLU>(unn);
        u = un;
        un = unn;
    }
}

__device__ __forceinline__ void k_helper(const Params& p, uint32_t help, unsigned epoch) {
    if ((threadIdx.x & 31) != 0) return;
    unsigned (*ctl)[32] = scratch(p)->ctl[epoch & 1];
    unsigned sent0 = 0, sent1 = 0, n = 0;
    int seen = 0;
    bool fin = false;
    while (!fin || seen < 2) {
        if (!fin) {
            fin = ld_acquire_cta_shared(help + 8) == NW + XW;
            const unsigned c0 = ld_acquire_cta_shared(help), c1 = ld_acquire_cta_shared(help + 4);
            if (c0 != sent0 || c1 != sent1) {
                fence_gpu();
                if (c0 != sent0) red_add_u32(&ctl[C_KDONE][0], c0 - sent0);
                if (c1 != sent1) red_add_u32(&ctl[C_KDONE + 1][0], c1 - sent1);
                sent0 = c0; sent1 = c1;
            }
        }
        if (seen < 2 && ld_acquire(&ctl[C_KDONE + seen][0]) >= NUK / 2) {
            st_release_cta_shared(help + 12 + 4 * seen, 1u);
            seen++;
        } else {
            __nanosleep(300);
        }
        if (++n > SPIN_LIMIT) __trap();
    }
}

__device__ __forceinline__ void v_poller(const Params& p, uint32_t sbase, int f, int w) {
    constexpr int HL = NH;
    const int lane = threadIdx.x & 31;
    const unsigned (*cp)[32] = &scratch(p)->vdone[((f * NPOLL + w) % NREP) * NH];
    unsigned n = 0;
    while (ld_acquire_cta_shared(sbase + M_HELP + 12) == 0) { __nanosleep(1000); if (++n > SPIN_LIMIT) __trap(); }
    int h = 0;
    bool fast = false;
    while (h < HL) {
        const unsigned r = __ballot_sync(~0u, ld_acquire(&cp[min(h + (lane & 3), HL - 1)][0]) >= 4 * UPP) & 15u;
        if (r & 1) {
            h = min(HL, h + __ffs(~r) - 1);
            __syncwarp();
            if (lane == 0) asm volatile("red.release.cta.shared::cta.max.u32 [%0], %1;" ::"r"(sbase + M_HELP + 20), "r"(h) : "memory");
        }
        if (h < HL - 4) {
            __nanosleep(h ? 300 : 1000);
        } else if (!fast) {
            fast = true;
            const long long t0 = clock64();
            while (clock64() - t0 < w * PGAP) {}
        }
        if (++n > SPIN_LIMIT) __trap();
    }
}
__device__ __forceinline__ void finisher(const Params& p, uint32_t sbase, int f) {
    constexpr int HL = NH;
    const int lane = threadIdx.x & 31;
    {
        const char* wg = reinterpret_cast<const char*>(p.wo);
        const uint32_t dst = sbase + 4 * SLOT + (16 * (lane & 7) + (lane >> 3)) * 16;
#pragma unroll 1
        for (int h = -FPF - 4; h < HL; h++) {
            if (lane == 0 && (unsigned)(h + FPF) < (unsigned)HL) l2_prefetch(wg + (size_t)(h + FPF) * 147456 + f * 2048, 2048);
            if (h >= 0) {
#pragma unroll
                for (int r = 0; r < 4; r++)
                    asm volatile("cp.async.cg.shared.global [%0], [%1], 16;" ::"r"(dst + h * 2048 + ((r & 1) * 4 + (r >> 1) * 8) * 16),
                                 "l"(wg + (size_t)(h * 128 + r * 32 + lane) * (DM * 2) + f * 16) : "memory");
            }
            __nanosleep(FSLEEP);
        }
        asm volatile("cp.async.wait_all;" ::: "memory");
        __syncwarp();
    }
    TS(11);
    const float4* vec = scratch(p)->oacc + ((lane >> 2) & 3) * 32 + (lane >> 4) * 16 + (lane & 3);
    float acc[2][2][4];
#pragma unroll
    for (int i = 0; i < 16; i++) acc[i >> 3][(i >> 2) & 1][i & 3] = 0.f;
    uint32_t* outp = reinterpret_cast<uint32_t*>(p.out + (lane >> 2) * (2 * DM) + f * 8 + (lane & 3) * 2);
    uint32_t wa = sbase + 4 * SLOT + lane * 16;
    auto project = [&](const float4 (&x)[4], const uint32_t (&w)[4][4]) {
#pragma unroll
        for (int s = 0; s < 4; s++) {
            const uint32_t a[4] = {pack_bf16(x[s].x, x[s].y), 0u, pack_bf16(x[s].z, x[s].w), 0u};
            mma16816(acc[0][s & 1], a, w[s >> 1][(s & 1) * 2], w[s >> 1][(s & 1) * 2 + 1]);
            mma16816(acc[1][s & 1], a, w[2 + (s >> 1)][(s & 1) * 2], w[2 + (s >> 1)][(s & 1) * 2 + 1]);
        }
    };
    int h = 0;
    unsigned n = 0;
    while (h < HL) {
        uint32_t w[4][4];
#pragma unroll
        for (int q = 0; q < 4; q++) ldsm4t(w[q], wa + q * 512);
        int ready;
        while ((ready = ld_acquire_cta_shared(sbase + M_HELP + 20)) <= h) {
            if (h < HL - 3) __nanosleep(100);
            if (++n > (SPIN_LIMIT << 4)) __trap();
        }
        float4 x[4], y[4];
#pragma unroll
        for (int s = 0; s < 4; s++) x[s] = ld_relaxed16(vec + s * 4);
        const bool two = ready > h + 1;
        if (two) {
#pragma unroll
            for (int s = 0; s < 4; s++) y[s] = ld_relaxed16(vec + 128 + s * 4);
        }
        project(x, w);
        if (two) {
#pragma unroll
            for (int q = 0; q < 4; q++) ldsm4t(w[q], wa + 2048 + q * 512);
            project(y, w);
        }
        const int nr = two ? 2 : 1;
        h += nr;
        vec += nr * 128;
        wa += nr * 2048;
        const float o0 = acc[0][0][0] + acc[0][1][0] + __shfl_down_sync(~0u, acc[1][0][0] + acc[1][1][0], 16);
        const float o1 = acc[0][0][1] + acc[0][1][1] + __shfl_down_sync(~0u, acc[1][0][1] + acc[1][1][1], 16);
        asm volatile("{\n.reg .pred p;\nsetp.ne.u32 p, %2, 0;\n@p st.global.u32 [%0], %1;\n}" ::"l"(outp), "r"(pack_bf16(o0, o1)),
                     "r"((uint32_t)(lane < 16 && h == NH)) : "memory");
    }
}

__device__ __noinline__ void f_collect(const unsigned (*flag)[32], unsigned full, const float4* src, unsigned todo, uint32_t sbase) {
    const int lane = threadIdx.x & 31, g = lane >> 2, t = lane & 3;
    const bool last = todo != 15;
    unsigned n = 0;
    while (todo) {
        const unsigned v = ld_acquire(&flag[t][0]);
        unsigned m = __ballot_sync(~0u, v == full) & todo;
        if (m == 0) {
            if (!last || __shfl_sync(~0u, v, 0) == 0) __nanosleep(200);
            if (++n > SPIN_LIMIT) __trap();
            continue;
        }
        __syncwarp();
        todo ^= m;
        if (last) TS(16);
        do {
            const int h0 = __ffs(m) - 1, h1 = 31 - __clz(m);
            m &= ~((1u << h0) | (1u << h1));
            float4 x[8];
#pragma unroll
            for (int b = 0; b < 8; b++) x[b] = ld_relaxed16(src + ((b & 4) ? h1 : h0) * 128 + (b & 3) * 32 + lane);
#pragma unroll
            for (int b = 0; b < 8; b++) {
                const uint32_t lo = pack_bf16(x[b].x, x[b].y), hi = pack_bf16(x[b].z, x[b].w);
                const uint32_t o = __shfl_xor_sync(~0u, (g & 1) ? lo : hi, 4);
                const uint32_t e0 = (g & 1) ? o : lo, e1 = (g & 1) ? hi : o;
                asm volatile("st.shared.v2.u32 [%0], {%1,%2};"
                             ::"r"(sbase + F_BF + ((b & 4) ? h1 : h0) * 1024 + t * 256 + ((b ^ t) & 3) * 64 + g * 8),
                               "r"(__byte_perm(e0, e1, 0x5410)), "r"(__byte_perm(e0, e1, 0x7632)) : "memory");
            }
            __syncwarp();
            if (lane < (h0 == h1 ? 1 : 2))
                asm volatile("mbarrier.arrive.shared::cta.b64 _, [%0];" ::"r"(sbase + F_BAR + 32 + (lane ? h1 : h0) * 8) : "memory");
        } while (m);
    }
    if (last) TS(17);
}

__device__ __forceinline__ void f_request(const Params& p, const CUtensorMap* tm, int panel, int rank, int nsl, int delay, int step, unsigned tag,
                                          uint32_t sbase, uint64_t pol) {
    const int lane = threadIdx.x & 31;
    if (lane == 0) asm volatile("prefetch.tensormap [%0];" ::"l"(tm) : "memory");
    unsigned long long v;
    unsigned n = 0;
    while (!__all_sync(~0u, (v = ld_relaxed64(&scratch(p)->dry[blockIdx.x >> 3][lane >> 2])) >> 32 == tag)) {
        __nanosleep(200);
        if (++n > SPIN_LIMIT) __trap();
    }
    const uint32_t t0 = __shfl_sync(~0u, (uint32_t)v, 0);
    uint32_t due = t0 + (__reduce_add_sync(~0u, (int)((uint32_t)v - t0)) >> 5);
    TS(22);
    due += delay;
#pragma unroll 1
    for (int q = 0; q < 8 * nsl; q++, due += step) {
        if (q >= LAG * nsl) mbar_spin(sbase + F_BAR + 64 + (q - LAG * nsl) * 8);
        while ((int)(time_ns() - due) < 0 && ++n < SPIN_LIMIT) {}
        tma3d_warp(sbase + F_W - (q >> 3) * 2 * SLOT + (q & 7) * 8192, tm, 0, (rank * 8 + (q & 7)) * 64, panel + (q >> 3), sbase + F_BAR + 64 + q * 8,
                   8192, pol);
    }
    TS(18);
}

__device__ __forceinline__ void f_project(const Params& p, int rank, int j, int nsl, uint32_t sbase) {
    const int lane = threadIdx.x & 31, g = lane >> 2, t = lane & 3;
    const uint32_t wa = sbase + F_W + ((lane & 7) + (lane >> 4) * 8) * 128 + (((2 * j + ((lane >> 3) & 1)) ^ (lane & 7)) * 16);
    const uint32_t ba = sbase + F_BF + (g & 3) * 64 + t * 16;
    const bool up = t & 2;
#pragma unroll 1
    for (int sl = 0; sl < nsl; sl++) {
        const uint32_t rdst = mapa(sbase + F_RX + sl * 1024 + rank * 128 + g * 16 + (t & 1) * 8, 2 * j + (t >> 1));
        const uint32_t rbar = mapa(sbase + F_BAR + 16 + sl * 8, 2 * j + (t >> 1));
        float acc[2][4];
#pragma unroll
        for (int k = 0; k < 8; k++) acc[k >> 2][k & 3] = 0.f;
#pragma unroll 1
        for (int h = 0; h < 4; h++) {
            uint32_t wp = wa + h * 16384 - sl * 2 * SLOT, last = h == 3;
            mbar_spin(sbase + F_BAR + 32 + h * 8);
            uint32_t a[8][4], bf[4][4];
#pragma unroll
            for (int s = 0; s < 4; s++)
                asm volatile("ld.shared.v4.u32 {%0,%1,%2,%3}, [%4];" : "=r"(bf[s][0]), "=r"(bf[s][1]), "=r"(bf[s][2]), "=r"(bf[s][3])
                             : "r"(((ba + h * 1024) ^ (s * 64)) + s * 256) : "memory");
            asm volatile("" : "+r"(wp), "+r"(last));
#pragma unroll
            for (int q = 0; q < 2; q++) {
                mbar_spin(sbase + F_BAR + 64 + sl * 64 + h * 16 + q * 8);
#pragma unroll
                for (int s = 4 * q; s < 4 * q + 4; s++) ldsm4t(a[s], wp + s * 2048);
            }
#pragma unroll
            for (int s = 0; s < 8; s++) mma16816(acc[s & 1], a[s], bf[s & 3][(s >> 2) * 2], bf[s & 3][(s >> 2) * 2 + 1]);
            const float v0 = up ? acc[0][2] + acc[1][2] : acc[0][0] + acc[1][0], v1 = up ? acc[0][3] + acc[1][3] : acc[0][1] + acc[1][1];
            asm volatile("{\n.reg .pred p;\nsetp.ne.u32 p, %4, 0;\n"
                         "@p st.async.weak.shared::cluster.mbarrier::complete_tx::bytes.v2.b32 [%0], {%1,%2}, [%3];\n}"
                         ::"r"(rdst), "r"(__float_as_uint(v0)), "r"(__float_as_uint(v1)), "r"(rbar), "r"(last) : "memory");
        }
    }
    TS(20);
}

__device__ __forceinline__ void f_receive(const Params& p, __nv_bfloat16* out, int nsl, uint32_t sbase) {
    const int lane = threadIdx.x & 31;
    out += (lane & 3) * (2 * DM) + (lane >> 2);
#pragma unroll 1
    for (int sl = -1; sl < nsl; sl++) {
        __nv_bfloat16* dst = out + sl * 64;
        uint32_t src = sbase + F_RX + sl * 1024 + lane * 4;
        asm volatile("" : "+l"(dst), "+r"(src));
        if (sl >= 0) mbar_spin_cluster(sbase + F_BAR + 16 + sl * 8);
        float v[8];
#pragma unroll
        for (int r = 0; r < 8; r++) asm volatile("ld.shared.f32 %0, [%1];" : "=f"(v[r]) : "r"(src + r * 128) : "memory");
        const float o = ((v[0] + v[1]) + (v[2] + v[3])) + ((v[4] + v[5]) + (v[6] + v[7]));
        asm volatile("{\n.reg .pred p;\nsetp.ge.s32 p, %2, 0;\n@p st.global.u16 [%0], %1;\n}"
                     ::"l"(dst), "h"((unsigned short)pack_bf16(o, 0.f)), "r"(sl) : "memory");
    }
    TS(15);
}

constexpr int BS_WUK = 5, BS_Q = 9, BS_CKV = 11, BS_PART = 27, BS_WUV = 29, BS_END = 33;

__device__ __noinline__ void b_issue(const Params& p, int n, int bi, uint32_t sbase, uint64_t pol) {
    if (n >= BS_END || (n >= BS_Q && n < BS_CKV) || (n >= BS_PART && n < BS_WUV)) return;
    const uint32_t bar = sbase + M_BAR + (NSLOT + n % BRING) * 8;
    const CUtensorMap* tm;
    int row, panel = 2 * bi;
    if (n < BS_WUK) { tm = &p.tm_wq; row = n * 128; }
    else if (n < BS_Q) { tm = &p.tm_wuk; row = (n - BS_WUK) * 128; }
    else if (n < BS_PART) {
        tm = &p.tm_ckv; panel = 0;
        row = (bi >> 3) * SK + ((n - BS_CKV) * 8 + (bi & 7)) * 32;
    }
    else { tm = &p.tm_wuv; row = (n - BS_WUV) * 128; }
    mbar_expect_tx(bar, n == 0 ? 32768 + 4 * 1152 : 32768);
    tma3d(sbase + (n % BRING) * SLOT, tm, 0, row, panel, bar, pol);
}
__device__ __forceinline__ void b_issue_xchg(int n, const void* src, uint32_t sbase, uint64_t pol) {
    asm volatile("fence.proxy.async;" ::: "memory");
#pragma unroll
    for (int i = 0; i < 2; i++) {
        const uint32_t bar = sbase + M_BAR + (NSLOT + (n + i) % BRING) * 8;
        mbar_expect_tx(bar, 32768);
        bulk_load(sbase + ((n + i) % BRING) * SLOT, reinterpret_cast<const char*>(src) + i * 32768, 32768, bar, pol);
    }
}
__device__ __forceinline__ void b_wait(int n, uint32_t sbase) {
    mbar_wait(sbase + M_BAR + (NSLOT + n % BRING) * 8, (n / BRING) & 1);
}

__device__ __noinline__ void b_gemm(const Params& p, uint32_t sbase, int n0, int n1, int ktot, uint32_t xh, uint32_t xl, int pitch,
                                    int bi, uint64_t pol) {
    const int tid = threadIdx.x, warp = tid >> 5, lane = tid & 31, g = lane >> 2, t = lane & 3;
    const uint32_t woff = (warp >> 2) * 16384 + (lane & 15) * 128 + ((((warp & 3) * 2 + (lane >> 4)) ^ (lane & 7)) * 16);
    const uint32_t xoff = (g & 3) * pitch + t * 4;
    float acc[2][4];
#pragma unroll
    for (int i = 0; i < 8; i++) acc[i >> 2][i & 3] = 0.f;
#pragma unroll 1
    for (int n = n0; n < n1; n++) {
        b_wait(n, sbase);
        const uint32_t slot = sbase + (n % BRING) * SLOT + woff;
        const int k0 = (n - n0) * 128;
        const int ns = min(8, (ktot - k0) >> 4);
#pragma unroll 2
        for (int s = 0; s < ns; s++) {
            uint32_t a[4], w[4];
            const uint32_t xo = xoff + (k0 + 16 * s) * 2;
            a[0] = lds32(xh + xo); a[2] = lds32(xh + xo + 16);
            a[1] = xl ? lds32(xl + xo) : 0u; a[3] = xl ? lds32(xl + xo + 16) : 0u;
            ldsm4t(w, slot + s * 2048);
            mma16816(acc[0], a, w[0], w[1]);
            mma16816(acc[1], a, w[2], w[3]);
        }
        __syncthreads();
        if (tid == 0) b_issue(p, n + BD, bi, sbase, pol);
    }
    if (g < 4) {
#pragma unroll
        for (int j = 0; j < 2; j++)
            asm volatile("st.shared.u32 [%0], %1;" ::"r"(sbase + M_QB + g * QP + (warp * 16 + j * 8 + t * 2) * 2),
                         "r"(pack_bf16(acc[j][0] + acc[j][2], acc[j][1] + acc[j][3])) : "memory");
    }
    __syncthreads();
}

__device__ __forceinline__ void b_exchange(unsigned* c, int n, const void* src, uint32_t sbase, uint64_t pol) {
    TS(n == BS_Q ? 24 : 28);
    __syncthreads();
    if (threadIdx.x == 0) {
        TS(n == BS_Q ? 25 : 29);
        fence_gpu();
        TS(n == BS_Q ? 26 : 30);
        red_add_u32(c, 1u);
        wait_count(c, NBCTA);
        TS(n == BS_Q ? 27 : 31);
        b_issue_xchg(n, src, sbase, pol);
    }
}

template <bool CLU>
__device__ __noinline__ void b_chain(const Params& p, char* smem, uint32_t sbase, int bi, unsigned epoch, uint64_t pol) {
    const int tid = threadIdx.x, warp = tid >> 5, lane = tid & 31, g = lane >> 2, t = lane & 3;
    unsigned (*ctl)[32] = scratch(p)->ctl[epoch & 1];
    float* red = reinterpret_cast<float*>(smem + 5 * SLOT);
    __syncthreads();
    b_gemm(p, sbase, 0, BS_WUK, DM, sbase + M_XB, 0, XP, bi, pol);
    TS(6);
    {
        uint32_t Q[16];
#pragma unroll
        for (int c = 0; c < 16; c++) Q[c] = lds32(sbase + M_QB + (g & 3) * QP + c * 16 + t * 4);
        float* qa = reinterpret_cast<float*>(smem + M_QA);
#pragma unroll 1
        for (int n = BS_WUK; n < BS_Q; n++) {
            b_wait(n, sbase);
            const uint32_t base = sbase + (n % BRING) * SLOT + (warp * 16 + (lane & 15)) * 128;
            float d[2][4];
#pragma unroll
            for (int i = 0; i < 8; i++) d[i >> 2][i & 3] = 0.f;
#pragma unroll
            for (int s = 0; s < 8; s++) {
                uint32_t a[4];
                ldsm4(a, base + (s >> 2) * 16384 + (((2 * (s & 3) + (lane >> 4)) ^ (lane & 7)) * 16));
                mma16816(d[s & 1], a, Q[2 * s], Q[2 * s + 1]);
            }
            const int c = (n - BS_WUK) * 128 + warp * 16 + g + 8 * (t >> 1);
            qa[(2 * (t & 1)) * 512 + c] = (t & 2) ? d[0][2] + d[1][2] : d[0][0] + d[1][0];
            qa[(2 * (t & 1) + 1) * 512 + c] = (t & 2) ? d[0][3] + d[1][3] : d[0][1] + d[1][1];
            __syncthreads();
            if (tid == 0) b_issue(p, n + BD, bi, sbase, pol);
        }
#pragma unroll 1
        for (int r = 0; r < 2; r++) {
            const int id = tid + r * 256;
            const int b = id >> 7, c0 = ((id >> 2) & 31) * 16 + (id & 3) * 2;
            const float2 u0 = *reinterpret_cast<const float2*>(qa + b * 512 + c0);
            const float2 u1 = *reinterpret_cast<const float2*>(qa + b * 512 + c0 + 8);
            const uint32_t h0 = pack_bf16(u0.x, u0.y), h1 = pack_bf16(u1.x, u1.y);
            const uint32_t l0 = pack_bf16(u0.x - bf_lo(h0), u0.y - bf_hi(h0)), l1 = pack_bf16(u1.x - bf_lo(h1), u1.y - bf_hi(h1));
            scratch(p)->qabs[((id >> 2) * 4 + (bi >> 3)) * 32 + (bi & 7) * 4 + (id & 3)] = make_uint4(h0, l0, h1, l1);
        }
    }
    b_exchange(&ctl[C_BBAR][0], BS_Q, &scratch(p)->qabs[(bi >> 3) * 4096], sbase, pol);
    {
        uint32_t qf[4][4][4];
        b_wait(BS_Q + (warp >> 2), sbase);
        TS(7);
        {
            const uint4* qs = reinterpret_cast<const uint4*>(smem + ((BS_Q + (warp >> 2)) % BRING) * SLOT) + (warp & 3) * 512 + lane;
#pragma unroll
            for (int s = 0; s < 4; s++)
#pragma unroll
                for (int i = 0; i < 4; i++) {
                    const uint4 v = qs[(s * 4 + i) * 32];
                    qf[i][s][0] = v.x; qf[i][s][1] = v.y; qf[i][s][2] = v.z; qf[i][s][3] = v.w;
                }
        }
        __syncthreads();
        if (tid == 0) { b_issue(p, BS_Q + BD, bi, sbase, pol); b_issue(p, BS_Q + 1 + BD, bi, sbase, pol); }
        float acc[2][8][4];
#pragma unroll
        for (int i = 0; i < 2; i++)
#pragma unroll
            for (int j = 0; j < 8; j++) { acc[i][j][0] = acc[i][j][1] = acc[i][j][2] = acc[i][j][3] = 0.f; }
        float mrun = -INFINITY, lrun = 0.f;
        const int head = tid >> 3, kq = tid & 7;
        float* alpha = reinterpret_cast<float*>(smem + M_ALPHA);
        for (int n = BS_CKV; n < BS_PART; n++) {
            b_wait(n, sbase);
            const uint32_t slot = sbase + (n % BRING) * SLOT;
            float sc[4][4][4];
#pragma unroll
            for (int i = 0; i < 4; i++)
#pragma unroll
                for (int j = 0; j < 4; j++) { sc[i][j][0] = sc[i][j][1] = sc[i][j][2] = sc[i][j][3] = 0.f; }
#pragma unroll
            for (int j = 0; j < 4; j++)
#pragma unroll
                for (int sp = 0; sp < 2; sp++) {
                    uint32_t bf[4];
                    ldsm4(bf, slot + warp * 4096 + (8 * j + (lane & 7)) * 128 + (((4 * sp + (lane >> 3)) ^ (lane & 7)) * 16));
#pragma unroll
                    for (int i = 0; i < 4; i++) {
                        mma16816(sc[i][j], qf[i][2 * sp], bf[0], bf[1]);
                        mma16816(sc[i][j], qf[i][2 * sp + 1], bf[2], bf[3]);
                    }
                }
#pragma unroll
            for (int i = 0; i < 4; i++)
#pragma unroll
                for (int j = 0; j < 4; j++)
                    *reinterpret_cast<float2*>(red + warp * 1024 + (8 * i + g) * 32 + ((8 * j) ^ (8 * (g & 3))) + 2 * t) =
                        make_float2(sc[i][j][0] + sc[i][j][2], sc[i][j][1] + sc[i][j][3]);
            __syncthreads();
            if (tid == 0 && n > BS_CKV) b_issue(p, n - 1 + BD, bi, sbase, pol);
            {
                float4 s = make_float4(0.f, 0.f, 0.f, 0.f);
#pragma unroll
                for (int w = 0; w < 8; w++) {
                    const float4 v = *reinterpret_cast<const float4*>(red + w * 1024 + head * 32 + ((4 * kq) ^ (8 * (head & 3))));
                    s.x += v.x; s.y += v.y; s.z += v.z; s.w += v.w;
                }
                const uint32_t r0 = pack_bf16(s.x, s.y), r1 = pack_bf16(s.z, s.w);
                const uint32_t s0 = pack_bf16(bf_lo(r0) * SCALE, bf_hi(r0) * SCALE);
                const uint32_t s1 = pack_bf16(bf_lo(r1) * SCALE, bf_hi(r1) * SCALE);
                const float f0 = bf_lo(s0), f1 = bf_hi(s0), f2 = bf_lo(s1), f3 = bf_hi(s1);
                float mx = fmaxf(fmaxf(f0, f1), fmaxf(f2, f3));
                mx = fmaxf(mx, __shfl_xor_sync(~0u, mx, 1));
                mx = fmaxf(mx, __shfl_xor_sync(~0u, mx, 2));
                mx = fmaxf(mx, __shfl_xor_sync(~0u, mx, 4));
                const float mnew = fmaxf(mrun, mx);
                const float al = expsub(mrun, mnew);
                const float p0 = expsub(f0, mnew), p1 = expsub(f1, mnew), p2 = expsub(f2, mnew), p3 = expsub(f3, mnew);
                lrun = lrun * al + ((p0 + p1) + (p2 + p3));
                mrun = mnew;
                *reinterpret_cast<uint2*>(smem + M_P + head * 80 + kq * 8) = make_uint2(pack_bf16(p0, p1), pack_bf16(p2, p3));
                if (kq == 0) alpha[head] = al;
            }
            __syncthreads();
            {
                uint32_t pf[2][2][4];
#pragma unroll
                for (int i = 0; i < 2; i++)
#pragma unroll
                    for (int ks = 0; ks < 2; ks++)
                        ldsm4(pf[i][ks], sbase + M_P + (16 * i + (lane & 15)) * 80 + (16 * ks + 8 * (lane >> 4)) * 2);
#pragma unroll
                for (int i = 0; i < 2; i++) {
                    const float a0 = alpha[16 * i + g], a1 = alpha[16 * i + 8 + g];
#pragma unroll
                    for (int j = 0; j < 8; j++) { acc[i][j][0] *= a0; acc[i][j][1] *= a0; acc[i][j][2] *= a1; acc[i][j][3] *= a1; }
                }
#pragma unroll
                for (int j = 0; j < 8; j++) {
                    uint32_t bf[4];
                    ldsm4t(bf, slot + warp * 4096 + lane * 128 + ((j ^ (lane & 7)) * 16));
#pragma unroll
                    for (int i = 0; i < 2; i++) {
                        mma16816(acc[i][j], pf[i][0], bf[0], bf[1]);
                        mma16816(acc[i][j], pf[i][1], bf[2], bf[3]);
                    }
                }
            }
        }
        __syncthreads();
        if (tid == 0) b_issue(p, BS_PART - 1 + BD, bi, sbase, pol);
        lrun += __shfl_xor_sync(~0u, lrun, 1);
        lrun += __shfl_xor_sync(~0u, lrun, 2);
        lrun += __shfl_xor_sync(~0u, lrun, 4);
        if (kq == 0) scratch(p)->bml[head * NBCTA + bi] = make_float2(mrun, lrun);
#pragma unroll
        for (int i = 0; i < 2; i++)
#pragma unroll
            for (int j = 0; j < 8; j++) {
                scratch(p)->bpart[((16 * i + g) * NBCTA + bi) * 256 + warp * 32 + j * 4 + t] = make_float2(acc[i][j][0], acc[i][j][1]);
                scratch(p)->bpart[((16 * i + 8 + g) * NBCTA + bi) * 256 + warp * 32 + j * 4 + t] = make_float2(acc[i][j][2], acc[i][j][3]);
            }
    }
    b_exchange(&ctl[C_BBAR + 1][0], BS_PART, &scratch(p)->bpart[bi * NBCTA * 256], sbase, pol);
    {
        float* omega = reinterpret_cast<float*>(smem + M_OMEGA);
        if (warp == 0) {
            __syncwarp();
            const uint2 ml = ld_relaxed8(&scratch(p)->bml[bi * NBCTA + lane]);
            const float ms = __uint_as_float(ml.x);
            float m = ms;
            m = fmaxf(m, __shfl_xor_sync(~0u, m, 1));
            m = fmaxf(m, __shfl_xor_sync(~0u, m, 2));
            m = fmaxf(m, __shfl_xor_sync(~0u, m, 4));
            const float w = expsub(ms, m);
            float l = w * __uint_as_float(ml.y);
            l += __shfl_xor_sync(~0u, l, 1);
            l += __shfl_xor_sync(~0u, l, 2);
            l += __shfl_xor_sync(~0u, l, 4);
            omega[lane] = w / l;
        }
        __syncthreads();
        b_wait(BS_PART, sbase);
        b_wait(BS_PART + 1, sbase);
#pragma unroll 1
        for (int b = 0; b < 4; b++) {
            const float2* ps = reinterpret_cast<const float2*>(smem + ((BS_PART + (b >> 1)) % BRING) * SLOT) + (b & 1) * 2048 + tid;
            float c0 = 0.f, c1 = 0.f;
#pragma unroll
            for (int s = 0; s < 8; s++) {
                const float w = omega[b * 8 + s];
                const float2 v = ps[s * 256];
                c0 = fmaf(w, v.x, c0);
                c1 = fmaf(w, v.y, c1);
            }
            const uint32_t hi = pack_bf16(c0, c1);
            *reinterpret_cast<uint32_t*>(smem + M_CH + b * CP + tid * 4) = hi;
            *reinterpret_cast<uint32_t*>(smem + M_CL + b * CP + tid * 4) = pack_bf16(c0 - bf_lo(hi), c1 - bf_hi(hi));
        }
        __syncthreads();
        if (tid == 0) { b_issue(p, BS_PART + BD, bi, sbase, pol); b_issue(p, BS_PART + 1 + BD, bi, sbase, pol); }
    }
    b_gemm(p, sbase, BS_WUV, BS_END, 512, sbase + M_CH, sbase + M_CL, CP, bi, pol);
    TS(12);
    if (CLU) {
        if (warp < 4) {
            const unsigned short* c = reinterpret_cast<const unsigned short*>(smem + M_QB + warp * QP) + 16 * t + g;
            scratch(p)->octx[(bi * 4 + warp) * 32 + lane] = make_float4(bf_lo(c[0]), bf_lo(c[8]), bf_lo(c[64]), bf_lo(c[72]));
        }
        __syncthreads();
        if (tid == 0) asm volatile("st.release.gpu.global.u32 [%0], %1;" ::"l"(&scratch(p)->cdone[bi][0]), "r"(epoch + 1) : "memory");
        return;
    }
    if (tid == 0) {
#pragma unroll 1
        for (int i = 0; i < 4; i++) {
            mbar_expect_tx(sbase + M_BAR + i * 8, 36864);
            tma3d(sbase + i * 36864, &p.tm_wo, 0, bi * 128 + i * 32, 0, sbase + M_BAR + i * 8, pol);
        }
    }
    TS(8);
    {
        float acc[9][4];
#pragma unroll
        for (int j = 0; j < 9; j++) { acc[j][0] = acc[j][1] = acc[j][2] = acc[j][3] = 0.f; }
#pragma unroll 1
        for (int i = 0; i < 4; i++) {
            const uint32_t xo = sbase + M_QB + (g & 3) * QP + i * 64 + t * 4;
            const uint32_t a0[4] = {lds32(xo), 0u, lds32(xo + 16), 0u}, a1[4] = {lds32(xo + 32), 0u, lds32(xo + 48), 0u};
            mbar_wait(sbase + M_BAR + i * 8, 0);
#pragma unroll
            for (int j = 0; j < 9; j++) {
                const int nt = warp * 9 + j;
                uint32_t w[4];
                ldsm4t(w, sbase + i * 36864 + (nt >> 3) * 4096 + lane * 128 + (((nt & 7) ^ (lane & 7)) * 16));
                mma16816(acc[j], a0, w[0], w[1]);
                mma16816(acc[j], a1, w[2], w[3]);
            }
        }
        if (g < 4) {
#pragma unroll
            for (int j = 0; j < 9; j++) {
                const int c2 = (warp * 9 + j) * 4 + t;
                st_tagged2(&scratch(p)->outb[((c2 / 9) * NH + bi) * 36 + g * 9 + c2 % 9], acc[j][0], acc[j][1], epoch + 1);
            }
        }
    }
    TS(9);
    {
        const uint4* src = scratch(p)->outb + (bi * NH + (tid >> 3)) * 36 + (tid & 7);
        float2* part = reinterpret_cast<float2*>(red);
        unsigned n = 0;
        while (true) {
            ulonglong2 v[5];
            bool ok = true;
#pragma unroll
            for (int i = 0; i < 5; i++)
                if (i < 4 || (tid & 7) < 4) v[i] = ld_tagged2(src + i * 8);
#pragma unroll
            for (int i = 0; i < 5; i++)
                if (i < 4 || (tid & 7) < 4) {
                    ok = ok && (unsigned)(v[i].x >> 32) == epoch + 1 && (unsigned)(v[i].y >> 32) == epoch + 1;
                    part[(tid >> 3) * 36 + (tid & 7) + i * 8] = make_float2(__uint_as_float((unsigned)v[i].x), __uint_as_float((unsigned)v[i].y));
                }
            if (ok) break;
            __nanosleep(400);
            if (++n > SPIN_LIMIT) __trap();
        }
        __syncthreads();
        if (tid < 36) {
            float s0 = 0.f, s1 = 0.f;
#pragma unroll 8
            for (int h = 0; h < NH; h++) { const float2 v = part[h * 36 + tid]; s0 += v.x; s1 += v.y; }
            *reinterpret_cast<uint32_t*>(p.out + (tid / 9) * 2 * DM + DM + bi * 18 + (tid % 9) * 2) = pack_bf16(s0, s1);
        }
    }
    TS(10);
}

template <bool CLU>
__global__ void __launch_bounds__(256, 1) fused_decode_kernel(const __grid_constant__ Params p) {
    asm volatile("{\n.reg .pred p;\n.reg .u32 a;\n.reg .u64 b;\nsub.u32 a, %1, %4;\nsetp.lt.u32 p, a, %3;\n"
                 "mad.lo.u32 a, %2, %3, %1;\n"
                 "mad.wide.u32 b, a, %5, %0;\n@p prefetch.global.L2 [b];\n}"
                 ::"l"(p.kc), "r"(threadIdx.x), "r"(blockIdx.x), "n"(PFN), "n"(128), "n"(128) : "memory");
    if (blockIdx.x >= 1024) return;
    extern __shared__ __align__(1024) char smem_raw[];
    const uint32_t sbase = (smem_u32(smem_raw) + 1023u) & ~1023u;
    char* smem = smem_raw + (sbase - smem_u32(smem_raw));
    const int tid = threadIdx.x, warp = __shfl_sync(~0u, tid >> 5, 0), lane = tid & 31;
    const int blk = blockIdx.x;
    const bool isB = CLU ? blk < NBCTA : (blk & 3) == 0 && (blk >> 2) < NBCTA;
    const int bi = CLU ? blk : blk >> 2;
    const int nb = CLU ? blk - NBCTA : blk - min(NBCTA, (blk + 3) >> 2);
    const int nblk = CLU ? 8 * MINCL : gridDim.x, nnb = nblk - NBCTA;
    const int nstatic = nnb * (NW + XW);
    uint64_t pol;
    asm volatile("createpolicy.fractional.L2::evict_first.b64 %0, 1.0;" : "=l"(pol));
    const uint32_t wbar = sbase + M_BAR + warp * 8, wslot = sbase + warp * SLOT;
    const int u0 = warp * nnb + nb;
    const bool hold = ((blk >> 2) >> KMIN << KMIN) * 4 * UPP < nstatic;
    const uint32_t jbar = sbase + M_BAR + (NSLOT + BRING) * 8;
    if (warp < 4) {
        mbar_init_warp(wbar);
        if (warp < NEARLY && !isB && !hold)
            tile_load_warp(wslot, reinterpret_cast<const char*>(p.kc) + (size_t)((u0 >> 7) * 1024 + (u0 & 127)) * TILE_BYTES, wbar, pol);
    }
    asm volatile("" ::: "memory");
    if (warp == 7) {
        if (blk < 128) {
            uint64_t poln;
            asm volatile("createpolicy.fractional.L2::evict_normal.b64 %0, 1.0;" : "=l"(poln));
            mbar_init_warp(jbar);
            tma3d_warp(sbase + J0W, &p.tm_j0, blk * 32, 0, 0, jbar, 36864 + 4 * 1152, poln);
            if (lane == 0) bulk_load(sbase + M_XA, p.xa, 4608, jbar, poln);
        }
        if (lane < 8) reinterpret_cast<unsigned*>(smem + M_HELP)[lane] = 0;
        __syncwarp();
        if (!isB) asm volatile("bar.arrive 2, %0;" ::"n"(32 * (NW + XW + 1)) : "memory");
    }
    unsigned epoch = 0;
    if (lane == 0) epoch = ld_relaxed4(scratch(p)->epoch);
    if (blk >= 128 ? warp >= 4 : isB && warp < 4) epoch = __shfl_sync(~0u, epoch, 0);
    if (isB && warp == 3) asm volatile("bar.sync 1, 160;" ::: "memory");
    if (isB && tid == 96) {
#pragma unroll 1
        for (int i = 0; i < BRING; i++) mbar_init(sbase + M_BAR + (NSLOT + i) * 8, 1);
        asm volatile("fence.mbarrier_init.release.cluster;" ::: "memory");
        if (hold) { unsigned n = 0; while (ld_acquire_cta_shared(sbase + M_HELP + 24) < 2) { if (++n > (SPIN_LIMIT << 4)) __trap(); } }
#pragma unroll 1
        for (int b = 0; b < 4; b++) bulk_load(sbase + M_XB + b * XP, p.xb + b * DM, 1152, sbase + M_BAR + NSLOT * 8, pol);
#pragma unroll 1
        for (int n = 0; n < BD; n++) b_issue(p, n, bi, sbase, pol);
    }
    if (warp >= 4 && blk < 128) {
        const int g = lane >> 2, t = lane & 3, j = tid - 128;
        asm volatile("bar.sync 1, %0;" ::"r"(isB ? 160 : 128) : "memory");
#pragma unroll 1
        for (int ph = -1;; ph++) {
        const int sl = ph > 0 ? blk + 128 - nblk : blk;
        STI(q1);
        if (ph >= 0) mbar_wait(jbar, ph);
        STI(q2);
        TS(13);
        float acc[4][4];
#pragma unroll
        for (int i = 0; i < 16; i++) acc[i >> 2][i & 3] = 0.f;
        const uint32_t wa = sbase + J0W + ((warp - 4) * 144 + (lane & 15)) * 64;
        const uint32_t sw = (lane >> 1) & 3, xa = sbase + M_XA + (g & 3) * 1152 + (warp - 4) * 288 + t * 4;
#pragma unroll 3
        for (int s = 0; s < 9; s++) {
            const uint32_t a[4] = {lds32(xa + s * 32), 0u, lds32(xa + s * 32 + 16), 0u};
            uint32_t w0[4], w1[4];
            ldsm4t(w0, wa + s * 1024 + (((lane >> 4) ^ sw) * 16));
            ldsm4t(w1, wa + s * 1024 + (((2 + (lane >> 4)) ^ sw) * 16));
            mma16816(acc[0], a, w0[0], w0[1]);
            mma16816(acc[1], a, w0[2], w0[3]);
            mma16816(acc[2], a, w1[0], w1[1]);
            mma16816(acc[3], a, w1[2], w1[3]);
        }
        STI(q3);
        epoch = __shfl_sync(~0u, epoch, 0);
        float2* j0 = reinterpret_cast<float2*>(smem + M_J0);
        if (g < 4) {
#pragma unroll
            for (int i = 0; i < 4; i++) j0[(warp - 4) * 64 + g * 16 + i * 4 + t] = make_float2(acc[i][0], acc[i][1]);
        }
        asm volatile("bar.sync 1, 128;" ::: "memory");
        const bool again = ph == 0 && blk + 128 - nblk >= nblk;
        if (again && tid == 224) {
            mbar_expect_tx(jbar, 36864);
            tma3d(sbase + J0W, &p.tm_j0, (blk + 128 - nblk) * 32, 0, 0, jbar, pol);
        }
        if (warp < 6) {
            const float2 v0 = j0[j], v1 = j0[64 + j], v2 = j0[128 + j], v3 = j0[192 + j];
            asm volatile("{\n.reg .pred p;\n.reg .b64 v;\nsetp.ge.s32 p, %3, 0;\nmov.b64 v, {%1, %2};\n@p st.relaxed.gpu.global.u64 [%0], v;\n}"
                         ::"l"(&scratch(p)->qll[(j >> 4) * 2048 + sl * 16 + (j & 15)]),
                           "r"(pack_bf16((v0.x + v1.x) + (v2.x + v3.x), (v0.y + v1.y) + (v2.y + v3.y))), "r"(epoch + 1), "r"(ph) : "memory");
            __syncwarp();
            if (lane == 0 && ph >= 0) asm volatile("red.relaxed.cta.shared::cta.add.u32 [%0], 1;" ::"r"(sbase + M_HELP + 24) : "memory");
        } else if (warp == 7) {
            if (blk < C_LINES && ph == 0) scratch(p)->ctl[(epoch & 1) ^ 1][blk][lane] = 0;
        }
        TS(1);
        if (ph >= 0 && !again) break;
        asm volatile("bar.sync 1, 128;" ::: "memory");
        }
    }
    if (CLU) {
        if (warp == 6) {
            if (lane < 24 && lane > 1) mbar_init(sbase + F_BAR + lane * 8, 1);
            if ((lane >> 1) == 1) mbar_expect_tx(sbase + F_BAR + lane * 8, 1024);
            asm volatile("fence.mbarrier_init.release.cluster;" ::: "memory");
        }
        asm volatile("barrier.cluster.arrive.relaxed.aligned;" ::: "memory");
    }
    const int cl = blk >> 3, rank = blk & 7;
    const bool partA = CLU && cl >= 4 && cl < 13;
    const int nwork = partA && rank == 7 ? 1 : NW + ((CLU ? rank < X3C : (nb & 3) < X3) ? 1 : 0);
    if (isB) {
        b_chain<CLU>(p, smem, sbase, bi, epoch, pol);
        if (!CLU) return;
    } else if (warp < NW + XW) {
        a_worker<CLU>(p, u0, warp >= nwork, warp < NEARLY && !hold, hold, nstatic, wslot, wbar, sbase + M_HELP,
                      epoch, pol);
        if (!CLU || warp < nwork) return;
        epoch = __shfl_sync(~0u, epoch, 0);
        unsigned n = 0;
        while (ld_acquire_cta_shared(sbase + M_HELP + 12) == 0) { __nanosleep(1000); if (++n > SPIN_LIMIT) __trap(); }
    } else if (warp == 7) {
#pragma unroll 1
        for (int i = nb; i < 4 * NH; i += nnb) scratch(p)->oacc[i * 32 + lane] = make_float4(0.f, 0.f, 0.f, 0.f);
        if (nb < NREP * NH) scratch(p)->vdone[nb][lane] = 0;
        __syncwarp();
        k_helper(p, sbase + M_HELP, epoch);
        if (nb == 0 && lane == 0) scratch(p)->epoch[0] = epoch + 1;
        __syncwarp();
    } else if (!CLU && nb < NFIN) {
        if (warp == 6) {
            finisher(p, sbase, nb);
            TS(4);
        } else if (warp >= 6 - NPOLL) {
            v_poller(p, sbase, nb, warp - (6 - NPOLL));
        }
    }
    if (!CLU || cl > 13) return;
    asm volatile("barrier.cluster.wait.acquire.aligned;" ::: "memory");
    const int nsl = isB ? 2 : 1, panel = isB ? 2 * cl : min(cl - 4, 8);
    if (warp >= 4) {
        f_project(p, rank, warp - 4, nsl, sbase);
        return;
    }
    if (isB ? warp == 2 : warp < 3 || nwork == 3)
        f_collect((partA ? scratch(p)->vdone : scratch(p)->cdone) + 4 * rank, partA ? 4 * UPP : epoch + 1,
                  (partA ? scratch(p)->oacc : scratch(p)->octx) + 4 * rank * 128, nwork == 1 ? 5 * warp : 15, sbase);
    if (warp != 3) return;
    f_request(p, partA ? &p.tm_fa : &p.tm_fb, panel, rank, nsl, isB ? B0 + rank * (BJ / 8) : A0 + rank * (AJ / 8), isB ? BJ : AJ, epoch + 1, sbase, pol);
    f_receive(p, p.out + (partA ? 0 : DM) + panel * 64 + rank * 8, nsl, sbase);
}

}

typedef CUresult (*EncodeFn)(CUtensorMap*, CUtensorMapDataType, cuuint32_t, void*, const cuuint64_t*, const cuuint64_t*,
                             const cuuint32_t*, const cuuint32_t*, CUtensorMapInterleave, CUtensorMapSwizzle,
                             CUtensorMapL2promotion, CUtensorMapFloatOOBfill);

extern "C" void kernel_launch(void* const* d_in, const int* in_sizes, int n_in, void* d_out, int out_size) {
    (void)in_sizes; (void)n_in; (void)out_size;
    static int nsm = 0, ncl = 0;
    static EncodeFn encode = nullptr;
    static void* scr = nullptr;
    cudaLaunchConfig_t cfg = {};
    cudaLaunchAttribute at[1];
    at[0].id = cudaLaunchAttributeClusterDimension;
    at[0].val.clusterDim.x = 8; at[0].val.clusterDim.y = 1; at[0].val.clusterDim.z = 1;
    cfg.blockDim = dim3(256); cfg.dynamicSmemBytes = SMEM_BYTES; cfg.stream = cudaStreamPerThread; cfg.attrs = at; cfg.numAttrs = 1;
    if (nsm == 0) {
        int dev = 0;
        cudaGetDevice(&dev);
        cudaDeviceGetAttribute(&nsm, cudaDevAttrMultiProcessorCount, dev);
        cudaFuncSetAttribute(fused_decode_kernel<false>, cudaFuncAttributeMaxDynamicSharedMemorySize, SMEM_BYTES);
        cudaFuncSetAttribute(fused_decode_kernel<true>, cudaFuncAttributeMaxDynamicSharedMemorySize, SMEM_BYTES);
        cfg.gridDim = dim3(128);
        if (cudaOccupancyMaxActiveClusters(&ncl, fused_decode_kernel<true>, &cfg) != cudaSuccess) { ncl = 0; (void)cudaGetLastError(); }
        if (ncl > MINCL) ncl = MINCL;
        void* fn = nullptr;
        cudaDriverEntryPointQueryResult qr;
        cudaGetDriverEntryPoint("cuTensorMapEncodeTiled", &fn, cudaEnableDefault, &qr);
        encode = (EncodeFn)fn;
        cudaGetSymbolAddress(&scr, g_scratch);
    }
    Params p;
    auto panels = [&](CUtensorMap* tm, void* ptr, int rows, int cols, int box_rows, int box_panels,
                      CUtensorMapL2promotion promo = CU_TENSOR_MAP_L2_PROMOTION_L2_256B) {
        const cuuint64_t gd[3] = {64, (cuuint64_t)rows, (cuuint64_t)(cols / 64)}, gs[2] = {(cuuint64_t)cols * 2, 128};
        const cuuint32_t box[3] = {64, (cuuint32_t)box_rows, (cuuint32_t)box_panels}, es[3] = {1, 1, 1};
        encode(tm, CU_TENSOR_MAP_DATA_TYPE_BFLOAT16, 3, ptr, gd, gs, box, es, CU_TENSOR_MAP_INTERLEAVE_NONE,
               CU_TENSOR_MAP_SWIZZLE_128B, promo, CU_TENSOR_MAP_FLOAT_OOB_FILL_NONE);
    };
    panels(&p.tm_wq, d_in[7], DM, 4096, 128, 2);
    panels(&p.tm_wuk, d_in[8], 512, 4096, 128, 2);
    panels(&p.tm_wuv, d_in[9], 512, 4096, 128, 2);
    panels(&p.tm_wo, d_in[10], 4096, DM, 32, 9);
    panels(&p.tm_ckv, d_in[6], 4 * SK, 512, 32, 8);
    panels(&p.tm_fa, d_in[4], 4096, DM, 64, 1, CU_TENSOR_MAP_L2_PROMOTION_L2_128B);
    panels(&p.tm_fb, d_in[10], 4096, DM, 64, 1, CU_TENSOR_MAP_L2_PROMOTION_L2_128B);
    {
        const cuuint64_t gd[3] = {4096, 192, 3}, gs[2] = {8192, 192 * 8192};
        const cuuint32_t box[3] = {32, 192, 3}, es[3] = {1, 1, 1};
        encode(&p.tm_j0, CU_TENSOR_MAP_DATA_TYPE_BFLOAT16, 3, d_in[3], gd, gs, box, es, CU_TENSOR_MAP_INTERLEAVE_NONE,
               CU_TENSOR_MAP_SWIZZLE_64B, CU_TENSOR_MAP_L2_PROMOTION_L2_128B, CU_TENSOR_MAP_FLOAT_OOB_FILL_NONE);
    }
    p.xa = (const __nv_bfloat16*)d_in[0];
    p.kc = (const __nv_bfloat16*)d_in[1];
    p.vc = (const __nv_bfloat16*)d_in[2];
    p.wo = (const __nv_bfloat16*)d_in[4];
    p.xb = (const __nv_bfloat16*)d_in[5];
    p.out = (__nv_bfloat16*)d_out;
    p.s = (Scratch*)scr;
    if (ncl >= MINCL) {
        cfg.gridDim = dim3(8 * ncl);
        cudaLaunchKernelEx(&cfg, fused_decode_kernel<true>, p);
    } else {
        fused_decode_kernel<false><<<nsm, 256, SMEM_BYTES, cudaStreamPerThread>>>(p);
    }
}
```

```cpp
#include <cuda_runtime.h>
#include <cuda.h>
#include <cuda_bf16.h>
#include <stdint.h>

namespace {

constexpr int NH = 32, SK = 4096, DM = 576;
constexpr int KEYS = 128;
constexpr int UPP = SK / KEYS;
constexpr int NUK = 4 * NH * UPP;
constexpr int TILE_BYTES = KEYS * 256;
#define NWORK 2
constexpr int NW = NWORK;
constexpr int NBCTA = 32;
constexpr int MINCL = 15;
constexpr int NFIN = 72;
constexpr int SLOT = 32768;
constexpr int NSLOT = 6;
constexpr int BRING = 5;
constexpr int J0W = 5 * SLOT;
constexpr int MISC = NSLOT * SLOT + 4096;
constexpr int XP = 1168, CP = 1040, QP = 272;
constexpr int M_XA = MISC;
constexpr int M_XB = M_XA + 4 * XP;
constexpr int M_CH = M_XB + 4 * XP;
constexpr int M_CL = M_CH + 4 * CP;
constexpr int M_QB = M_CL + 4 * CP;
constexpr int M_QA = M_CH;
constexpr int M_J0 = M_QB + 4 * QP;
constexpr int M_P = M_J0 + 2048;
constexpr int M_ALPHA = M_P + 2560;
constexpr int M_OMEGA = M_ALPHA + 128;
constexpr int M_BAR = M_OMEGA + 128;
constexpr int M_HELP = M_BAR + 128;
constexpr int F_W = 4 * SLOT;
constexpr int F_BF = (M_HELP + 383) / 256 * 256;
constexpr int F_RX = F_BF + 4096;
constexpr int F_BAR = F_RX + 2048;
constexpr int SMEM_BYTES = F_BAR + 192 + 1024;
static_assert(SMEM_BYTES <= 232448 && M_BAR % 8 == 0 && M_QA % 16 == 0 && M_P % 16 == 0, "smem layout");
#define XW 2
#define X3 1
#define X3C 4
#define NEARLY 2
#define LATE 2000
#define BD 5
#define FPF 3
#define FSLEEP 800
#define VS0 24
#define PFN 96
#define EARLY 100
#define ELOG 5
#define TPU 159
#define A0 (1620 + 200 * X3C)
#define AJ 390
#define B0 (A0 - 400)
#define BJ 195
#define LAG 5
#define NPOLL 2
#define PGAP 200
static_assert(X3C <= 4 && NW == 2 && MINCL == 15, "warp 2 of rank 7 is free");
static_assert(NW + XW <= 4 && NEARLY <= NW + XW && BD <= BRING, "slots 4 and 5 hold the finisher weights");
constexpr int KMIN = 2, KMAX = 4, VMIN = 0, VMAX = 4;
constexpr float SCALE = 0.08838834764831845f;
constexpr float LOG2E = 1.4426950408889634f;
constexpr unsigned SPIN_LIMIT = 1u << 24;

#define NREP 2
#define NREPC 1
constexpr int C_QUEUE = 0, C_KDONE = 1, C_BBAR = 3, C_LINES = 5;

struct Scratch {
    unsigned epoch[32];
    unsigned ctl[2][C_LINES][32];
    uint2 qll[4 * 2048];
    uint2 scores[128 * SK / 4];
    float2 stats[128 * UPP];
    float4 oacc[128 * 32];
    unsigned vdone[NREP * NH][32];
    float4 octx[128 * 32];
    unsigned cdone[NH][32];
    unsigned long long dry[16][16];
    uint4 qabs[4 * 8 * 4 * 4 * 32];
    float2 bpart[NBCTA * NH * 256];
    float2 bml[NBCTA * NH];
    uint4 outb[NBCTA * NH * 36];
};
__device__ __align__(256) Scratch g_scratch;

struct Params {
    const __nv_bfloat16 *kc, *xa, *vc, *wo, *xb;
    __nv_bfloat16* out;
    Scratch* s;
    CUtensorMap tm_j0;
    CUtensorMap tm_wq, tm_wuk, tm_ckv, tm_wuv, tm_wo;
    CUtensorMap tm_fa, tm_fb;
};

__device__ __forceinline__ Scratch* scratch(const Params& p) {
    Scratch* s = p.s;
    __builtin_assume(__isGlobal(s));
    return s;
}

#define STI(v)
#define TS(i)
#define TSV(i, v)
#define LAND(i)
#define CLK(x)
#define ACC(a, x, y)

__device__ __forceinline__ uint32_t smem_u32(const void* p) { return (uint32_t)__cvta_generic_to_shared(p); }
__device__ __forceinline__ void mbar_init(uint32_t bar, uint32_t cnt) {
    asm volatile("mbarrier.init.shared::cta.b64 [%0], %1;" ::"r"(bar), "r"(cnt) : "memory");
}
__device__ __forceinline__ void mbar_expect_tx(uint32_t bar, uint32_t bytes) {
    asm volatile("mbarrier.arrive.expect_tx.shared::cta.b64 _, [%0], %1;" ::"r"(bar), "r"(bytes) : "memory");
}
__device__ __forceinline__ bool mbar_try(uint32_t bar, uint32_t parity) {
    uint32_t ok;
    asm volatile("{\n.reg .pred p;\nmbarrier.try_wait.parity.shared::cta.b64 p, [%1], %2;\nselp.u32 %0, 1, 0, p;\n}\n"
                 : "=r"(ok) : "r"(bar), "r"(parity) : "memory");
    return ok;
}
__device__ __forceinline__ void mbar_wait(uint32_t bar, uint32_t parity) {
    unsigned n = 0;
    while (!mbar_try(bar, parity)) { if (++n > SPIN_LIMIT) __trap(); }
}
__device__ __forceinline__ void mbar_spin(uint32_t bar) {
    asm volatile("{\n.reg .pred p;\n.reg .u32 n;\nmov.u32 n, 0;\nSPIN:\nmbarrier.try_wait.parity.shared::cta.b64 p, [%0], 0;\n@p bra.uni DONE;\n"
                 "add.u32 n, n, 1;\nsetp.lt.u32 p, n, 0x1000000;\n@p bra.uni SPIN;\ntrap;\nDONE:\n}" ::"r"(bar) : "memory");
}
__device__ __forceinline__ void mbar_spin_cluster(uint32_t bar) {
    asm volatile("{\n.reg .pred p;\n.reg .u32 n;\nmov.u32 n, 0;\nSPIN:\nmbarrier.try_wait.parity.relaxed.cluster.shared::cta.b64 p, [%0], 0;\n"
                 "@p bra.uni DONE;\nadd.u32 n, n, 1;\nsetp.lt.u32 p, n, 0x1000000;\n@p bra.uni SPIN;\ntrap;\nDONE:\n"
                 "fence.acquire.sync_restrict::shared::cluster.cluster;\n}" ::"r"(bar) : "memory");
}
__device__ __forceinline__ void bulk_load(uint32_t dst, const void* src, uint32_t bytes, uint32_t bar, uint64_t pol) {
    asm volatile("cp.async.bulk.shared::cluster.global.mbarrier::complete_tx::bytes.L2::cache_hint [%0], [%1], %2, [%3], %4;"
                 ::"r"(dst), "l"(src), "r"(bytes), "r"(bar), "l"(pol) : "memory");
}
__device__ __forceinline__ void mbar_init_warp(uint32_t bar) {
    asm volatile("{\n.reg .pred p;\nelect.sync _|p, 0xffffffff;\n@p mbarrier.init.shared::cta.b64 [%0], 1;\n@p fence.mbarrier_init.release.cluster;\n}"
                 ::"r"(bar) : "memory");
}
__device__ __forceinline__ void tile_load_warp(uint32_t dst, const void* src, uint32_t bar, uint64_t pol) {
    asm volatile("{\n.reg .pred p;\nelect.sync _|p, 0xffffffff;\n@p mbarrier.arrive.expect_tx.shared::cta.b64 _, [%2], %4;\n"
                 "@p cp.async.bulk.shared::cluster.global.mbarrier::complete_tx::bytes.L2::cache_hint [%0], [%1], %4, [%2], %3;\n}"
                 ::"r"(dst), "l"(src), "r"(bar), "l"(pol), "n"(TILE_BYTES) : "memory");
}
__device__ __forceinline__ void tma3d_warp(uint32_t dst, const CUtensorMap* tm, int c0, int c1, int c2, uint32_t bar, uint32_t bytes, uint64_t pol) {
    asm volatile("{\n.reg .pred p;\nelect.sync _|p, 0xffffffff;\n@p mbarrier.arrive.expect_tx.shared::cta.b64 _, [%2], %7;\n"
                 "@p cp.async.bulk.tensor.3d.shared::cluster.global.mbarrier::complete_tx::bytes.L2::cache_hint [%0], [%1, {%3,%4,%5}], [%2], %6;\n}"
                 ::"r"(dst), "l"(tm), "r"(bar), "r"(c0), "r"(c1), "r"(c2), "l"(pol), "r"(bytes) : "memory");
}
__device__ __forceinline__ void tma3d(uint32_t dst, const CUtensorMap* tm, int c0, int c1, int c2, uint32_t bar, uint64_t pol) {
    asm volatile("cp.async.bulk.tensor.3d.shared::cluster.global.mbarrier::complete_tx::bytes.L2::cache_hint [%0], [%1, {%3,%4,%5}], [%2], %6;"
                 ::"r"(dst), "l"(tm), "r"(bar), "r"(c0), "r"(c1), "r"(c2), "l"(pol) : "memory");
}
__device__ __forceinline__ void l2_prefetch(const void* src, uint32_t bytes) {
    asm volatile("cp.async.bulk.prefetch.L2.global [%0], %1;" ::"l"(src), "r"(bytes) : "memory");
}
__device__ __forceinline__ void ldsm4(uint32_t (&r)[4], uint32_t addr) {
    asm volatile("ldmatrix.sync.aligned.m8n8.x4.shared.b16 {%0,%1,%2,%3}, [%4];"
                 : "=r"(r[0]), "=r"(r[1]), "=r"(r[2]), "=r"(r[3]) : "r"(addr));
}
__device__ __forceinline__ void ldsm4t(uint32_t (&r)[4], uint32_t addr) {
    asm volatile("ldmatrix.sync.aligned.m8n8.x4.trans.shared.b16 {%0,%1,%2,%3}, [%4];"
                 : "=r"(r[0]), "=r"(r[1]), "=r"(r[2]), "=r"(r[3]) : "r"(addr));
}
__device__ __forceinline__ void mma16816(float (&d)[4], const uint32_t (&a)[4], uint32_t b0, uint32_t b1) {
    asm("mma.sync.aligned.m16n8k16.row.col.f32.bf16.bf16.f32 {%0,%1,%2,%3}, {%4,%5,%6,%7}, {%8,%9}, {%0,%1,%2,%3};"
        : "+f"(d[0]), "+f"(d[1]), "+f"(d[2]), "+f"(d[3])
        : "r"(a[0]), "r"(a[1]), "r"(a[2]), "r"(a[3]), "r"(b0), "r"(b1));
}
__device__ __forceinline__ uint32_t lds32(uint32_t a) {
    uint32_t v;
    asm volatile("ld.shared.u32 %0, [%1];" : "=r"(v) : "r"(a));
    return v;
}
__device__ __forceinline__ unsigned ld_acquire(const unsigned* p) {
    unsigned v;
    asm volatile("ld.acquire.gpu.global.u32 %0, [%1];" : "=r"(v) : "l"(p) : "memory");
    return v;
}
__device__ __forceinline__ uint2 ld_relaxed8(const void* p) {
    uint2 v;
    asm volatile("ld.relaxed.gpu.global.v2.u32 {%0,%1}, [%2];" : "=r"(v.x), "=r"(v.y) : "l"(p) : "memory");
    return v;
}
__device__ __forceinline__ unsigned ld_relaxed4(const void* p) {
    unsigned v;
    asm volatile("ld.relaxed.gpu.global.u32 %0, [%1];" : "=r"(v) : "l"(p) : "memory");
    return v;
}
__device__ __forceinline__ unsigned atom_inc(unsigned* p) {
    unsigned v;
    asm volatile("atom.relaxed.gpu.global.inc.u32 %0, [%1], 0x7fffffff;" : "=r"(v) : "l"(p) : "memory");
    return v;
}
__device__ __forceinline__ unsigned long long ld_relaxed64(const void* p) {
    unsigned long long v;
    asm volatile("ld.relaxed.gpu.global.u64 %0, [%1];" : "=l"(v) : "l"(p) : "memory");
    return v;
}
__device__ __forceinline__ void st_relaxed64(void* p, unsigned long long v) {
    asm volatile("st.relaxed.gpu.global.u64 [%0], %1;" ::"l"(p), "l"(v) : "memory");
}
__device__ __forceinline__ float4 ld_relaxed16(const void* p) {
    float4 v;
    asm volatile("ld.relaxed.gpu.global.v4.f32 {%0,%1,%2,%3}, [%4];" : "=f"(v.x), "=f"(v.y), "=f"(v.z), "=f"(v.w) : "l"(p) : "memory");
    return v;
}
__device__ __forceinline__ uint32_t mapa(uint32_t a, uint32_t rank) {
    uint32_t r;
    asm("mapa.shared::cluster.u32 %0, %1, %2;" : "=r"(r) : "r"(a), "r"(rank));
    return r;
}
__device__ __forceinline__ uint32_t time_ns() { uint32_t t; asm volatile("mov.u32 %0, %globaltimer_lo;" : "=r"(t)); return t; }
__device__ __forceinline__ void fence_gpu() { asm volatile("fence.acq_rel.gpu;" ::: "memory"); }
__device__ __forceinline__ void red_add_u32(unsigned* p, unsigned v) {
    asm volatile("red.relaxed.gpu.global.add.u32 [%0], %1;" ::"l"(p), "r"(v) : "memory");
}
__device__ __forceinline__ void st_tagged2(void* p, float a, float b, unsigned tag) {
    const unsigned long long hi = (unsigned long long)tag << 32;
    asm volatile("st.relaxed.gpu.global.v2.b64 [%0], {%1,%2};" ::"l"(p), "l"(hi | __float_as_uint(a)), "l"(hi | __float_as_uint(b)) : "memory");
}
__device__ __forceinline__ ulonglong2 ld_tagged2(const void* p) {
    ulonglong2 v;
    asm volatile("ld.relaxed.gpu.global.v2.b64 {%0,%1}, [%2];" : "=l"(v.x), "=l"(v.y) : "l"(p) : "memory");
    return v;
}
__device__ __forceinline__ float4 atom_add_f4(void* p, float a, float b, float c, float d) {
    float4 r;
    asm volatile("atom.relaxed.gpu.global.add.v4.f32 {%0,%1,%2,%3}, [%4], {%5,%6,%7,%8};"
                 : "=f"(r.x), "=f"(r.y), "=f"(r.z), "=f"(r.w) : "l"(p), "f"(a), "f"(b), "f"(c), "f"(d) : "memory");
    return r;
}
__device__ __forceinline__ void red_release_cta_shared(uint32_t a, unsigned v) {
    asm volatile("red.release.cta.shared::cta.add.u32 [%0], %1;" ::"r"(a), "r"(v) : "memory");
}
__device__ __forceinline__ unsigned ld_acquire_cta_shared(uint32_t a) {
    unsigned v;
    asm volatile("ld.acquire.cta.shared::cta.u32 %0, [%1];" : "=r"(v) : "r"(a) : "memory");
    return v;
}
__device__ __forceinline__ void st_release_cta_shared(uint32_t a, unsigned v) {
    asm volatile("st.release.cta.shared::cta.u32 [%0], %1;" ::"r"(a), "r"(v) : "memory");
}
__device__ __forceinline__ void wait_count(const unsigned* p, unsigned target) {
    unsigned n = 0;
    while (ld_acquire(p) < target) { if (++n > SPIN_LIMIT) __trap(); }
}
__device__ __forceinline__ uint32_t pack_bf16(float lo, float hi) {
    uint32_t r;
    asm("cvt.rn.bf16x2.f32 %0, %1, %2;" : "=r"(r) : "f"(hi), "f"(lo));
    return r;
}
__device__ __forceinline__ float bf_lo(uint32_t v) { return __uint_as_float(v << 16); }
__device__ __forceinline__ float bf_hi(uint32_t v) { return __uint_as_float(v & 0xffff0000u); }
__device__ __forceinline__ float ex2(float x) { float y; asm("ex2.approx.ftz.f32 %0, %1;" : "=f"(y) : "f"(x)); return y; }
__device__ __forceinline__ float expsub(float a, float b) { return ex2((a - b) * LOG2E); }
__device__ __forceinline__ float warp_max(float v) {
#pragma unroll
    for (int m = 16; m; m >>= 1) v = fmaxf(v, __shfl_xor_sync(~0u, v, m));
    return v;
}
__device__ __forceinline__ float warp_sum(float v) {
#pragma unroll
    for (int m = 16; m; m >>= 1) v += __shfl_xor_sync(~0u, v, m);
    return v;
}
template <bool CLU>
__device__ __forceinline__ unsigned unit_block(int u) {
    const unsigned x = ((unsigned)u & (NUK - 1)) / UPP;
    const int lg = u < NUK ? min(KMAX, max(KMIN, 29 - __clz(x | 1))) : (CLU && (int)x >= 4 * VS0 ? 0 : min(VMAX, max(VMIN, 29 - __clz((127 - x) | 1))));
    const unsigned r = x & ((4u << lg) - 1);
    return ((x - r + (r & ((1u << lg) - 1)) * 4 + (r >> lg)) * UPP) | ((unsigned)u & (UPP - 1));
}
__device__ __forceinline__ const char* block_src(const void* base, unsigned blk) {
    const unsigned po = blk / UPP;
    return reinterpret_cast<const char*>(base) + (size_t)(((po & 3) * NH + (po >> 2)) * UPP + blk % UPP) * TILE_BYTES;
}

template <bool CLU>
__device__ __forceinline__ void a_worker(const Params& p, int un, bool once, bool pre, bool hold, int nstatic, uint32_t slot, uint32_t bar,
                                         uint32_t help, unsigned epoch, uint64_t pol) {
    constexpr int NU = 2 * NUK, NR = CLU ? NREPC : NREP;
    const int lane = threadIdx.x & 31, g = lane >> 2, t = lane & 3;
    const int li = lane & 7;
    uint32_t kaddr[4], vaddr[8];
    {
        const int e = (lane >> 3) & 1, kk = lane >> 4;
#pragma unroll
        for (int s = 0; s < 4; s++) kaddr[s] = slot + (16 * li + e) * 256 + ((2 * s + kk + li) & 7) * 16;
        const int vrow = 4 * (li >> 1) + (li & 1) + 2 * kk;
#pragma unroll
        for (int c = 0; c < 8; c++) vaddr[c] = slot + vrow * 256 + e * 128 + ((c + li) & 7) * 16;
#pragma unroll
        for (int c = 0; c < 8; c++) asm volatile("" : "+r"(vaddr[c]));
    }
    const uint32_t vmask = (g >> 1) != t ? 0u : ((g & 1) ? 0xffff0000u : 0xffffu);
    int kseen = -1;
    unsigned long long H0 = 0, H1 = 0;
    auto header = [&](int v, unsigned vb) {
        const void *a0, *a1;
        if (v < NUK) {
            const unsigned po = vb / UPP;
            a0 = scratch(p)->qll + (po & 3) * 2048 + (po >> 2) * 64 + lane;
            a1 = reinterpret_cast<const uint2*>(a0) + 32;
        } else {
            const int half = vb / (NUK / 2);
            if (half > kseen) {
                unsigned n = 0;
                while (ld_acquire_cta_shared(help + 12 + 4 * half) == 0) { if (++n > (SPIN_LIMIT << 4)) __trap(); }
                kseen = half;
            }
            a0 = &scratch(p)->scores[vb * (KEYS / 4) + lane];
            a1 = &scratch(p)->stats[(vb / UPP) * UPP + lane];
        }
        H0 = ld_relaxed64(a0);
        H1 = ld_relaxed64(a1);
    };
    unsigned bu = 0, bn = unit_block<CLU>(un);
    asm volatile("bar.sync 2, %0;" ::"n"(32 * (NW + XW + 1)) : "memory");
    if (!pre && !hold) { const uint32_t t0 = clock(); while ((uint32_t)clock() - t0 < ((threadIdx.x >> 5) - NEARLY + 1) * LATE) {} }
    epoch = __shfl_sync(~0u, epoch, 0);
    if (hold) { unsigned n = 0; while (ld_acquire_cta_shared(help + 24) < 2) { if (++n > (SPIN_LIMIT << 4)) __trap(); } }
    unsigned (*ctl)[32] = scratch(p)->ctl[epoch & 1];
    const unsigned tag = epoch + 1;
    unsigned nxt = once ? NU : 0;
    int u = -1;
    uint32_t phase = 0;
    unsigned kpend = 0;
    const unsigned zero = gridDim.x >> 24;
    uint32_t Q[16];
    float4 oret = make_float4(0.f, 0.f, 0.f, 0.f);
    while (true) {
        const char* nsrc = block_src(un < NUK ? p.kc : p.vc, bn);
        float4* odst = &scratch(p)->oacc[(bu / UPP) * 32 + lane];
        unsigned* vdst = &scratch(p)->vdone[(lane & (NR - 1)) * NH + bu / (4 * UPP)][0];
        float d[8][4];
        CLK(c1);
        uint32_t act = un >= NU ? 0u : (u >= 0 || !pre ? 1u : 0u) | (!once && lane == 0 ? 2u : 0u);
        asm volatile("" : "+l"(odst), "+l"(nsrc), "+r"(act));
        if (u >= NUK) {
#pragma unroll
            for (int j = 0; j < 8; j++) { d[j][0] = d[j][1] = d[j][2] = d[j][3] = 0.f; }
            mbar_wait(bar, phase);
            LAND(NUK + bu);
            uint32_t a[2][8][4];
#pragma unroll
            for (int c = 0; c < 8; c++) ldsm4t(a[0][c], vaddr[c]);
#pragma unroll
            for (int j = 0; j < 8; j++) {
                if (j < 7) {
#pragma unroll
                    for (int c = 0; c < 8; c++) ldsm4t(a[(j + 1) & 1][c], vaddr[c] + (j + 1) * 4096);
                }
#pragma unroll
                for (int c = 0; c < 8; c++) mma16816(d[c], a[j & 1][c], Q[2 * j], Q[2 * j + 1]);
            }
            float o[4];
#pragma unroll
            for (int r = 0; r < 2; r++) {
                o[2 * r] = d[0][2 * r] + d[7][2 * r + 1];
                o[2 * r + 1] = d[0][2 * r + 1] + d[1][2 * r];
#pragma unroll
                for (int k = 1; k < 4; k++) {
                    const int src = (lane & 28) | ((t - k) & 3);
                    o[2 * r] += __shfl_sync(~0u, d[2 * k][2 * r] + d[2 * k - 1][2 * r + 1], src);
                    o[2 * r + 1] += __shfl_sync(~0u, d[2 * k][2 * r + 1] + d[2 * k + 1][2 * r], src);
                }
            }
            oret = atom_add_f4(odst, o[0], o[1], o[2], o[3]);
        } else if (u >= 0) {
#pragma unroll
            for (int j = 0; j < 8; j++) { d[j][0] = d[j][1] = d[j][2] = d[j][3] = 0.f; }
            mbar_wait(bar, phase);
            LAND(bu);
            uint32_t a[2][8][4];
#pragma unroll
            for (int j = 0; j < 8; j++) ldsm4(a[0][j], kaddr[0] + (4 * (j & 3) + 2 * (j >> 2)) * 256);
#pragma unroll
            for (int s = 0; s < 8; s++) {
                if (s < 7) {
#pragma unroll
                    for (int j = 0; j < 8; j++)
                        ldsm4(a[(s + 1) & 1][j], kaddr[(s + 1) & 3] + (4 * (j & 3) + 2 * (j >> 2)) * 256 + ((s + 1) >> 2) * 128);
                }
#pragma unroll
                for (int j = 0; j < 8; j++)
                    mma16816(d[j], a[s & 1][j], Q[(s & 4) * 2 + ((2 * s - 2 * j) & 7)], Q[(s & 4) * 2 + ((2 * s + 1 - 2 * j) & 7)]);
            }
        }
        if (u >= 0) phase ^= 1;
        CLK(c2b);
        asm volatile("{\n.reg .pred p, q;\n.reg .u32 a;\nelect.sync _|p, 0xffffffff;\nand.b32 a, %5, 1;\nsetp.ne.and.u32 q, a, 0, p;\n"
                     "@q mbarrier.arrive.expect_tx.shared::cta.b64 _, [%2], %4;\n"
                     "@q cp.async.bulk.shared::cluster.global.mbarrier::complete_tx::bytes.L2::cache_hint [%0], [%1], %4, [%2], %3;\n}"
                     ::"r"(slot), "l"(nsrc), "r"(bar), "l"(pol), "n"(TILE_BYTES), "r"(act) : "memory");
        if (act & 2) nxt = atom_inc(&ctl[C_QUEUE][0]);
        const uint32_t tk = clock();
        CLK(c3);
        if ((unsigned)u < (unsigned)NUK) {
            const int j0 = (t - (g >> 1)) & 3;
            float v[4];
#pragma unroll
            for (int q = 0; q < 4; q++) {
                const int jq = (q >> 1) * 4, e = (q & 1) * 2;
                const float x0 = (g & 1) ? d[jq + 0][e + 1] : d[jq + 0][e];
                const float x1 = (g & 1) ? d[jq + 1][e + 1] : d[jq + 1][e];
                const float x2 = (g & 1) ? d[jq + 2][e + 1] : d[jq + 2][e];
                const float x3 = (g & 1) ? d[jq + 3][e + 1] : d[jq + 3][e];
                const float y0 = (j0 & 1) ? x1 : x0, y1 = (j0 & 1) ? x3 : x2;
                v[q] = (j0 & 2) ? y1 : y0;
            }
            const uint32_t r0 = pack_bf16(v[0], v[1]), r1 = pack_bf16(v[2], v[3]);
            const uint32_t s0 = pack_bf16(bf_lo(r0) * SCALE, bf_hi(r0) * SCALE);
            const uint32_t s1 = pack_bf16(bf_lo(r1) * SCALE, bf_hi(r1) * SCALE);
            scratch(p)->scores[bu * (KEYS / 4) + 4 * g + j0] = make_uint2(s0, s1);
            const float f0 = bf_lo(s0), f1 = bf_hi(s0), f2 = bf_lo(s1), f3 = bf_hi(s1);
            const float m = warp_max(fmaxf(fmaxf(f0, f1), fmaxf(f2, f3)));
            const float l = warp_sum((expsub(f0, m) + expsub(f1, m)) + (expsub(f2, m) + expsub(f3, m)));
            if (lane == 0) scratch(p)->stats[bu] = make_float2(m, l);
            kpend++;
            if (un / (NUK / 2) != u / (NUK / 2)) {
                __syncwarp();
                if (lane == 0) {
                    red_release_cta_shared(help + 4 * (u / (NUK / 2)), kpend);
                    if (un >= NUK) red_release_cta_shared(help + 8, 1u);
                }
                kpend = 0;
            }
        }
        CLK(c4);
        int unn = NU;
        if (un < NU) {
            unsigned n = 0;
            while (true) {
                header(un, bn);
                if (un >= NUK || __all_sync(~0u, (uint32_t)(H0 >> 32) == tag && (uint32_t)(H1 >> 32) == tag)) break;
                if (++n > SPIN_LIMIT) __trap();
            }
            if (un >= NUK) {
                const uint32_t s0 = (uint32_t)H0, s1 = (uint32_t)(H0 >> 32);
                const float mu = __uint_as_float((uint32_t)H1);
                const float m = warp_max(mu);
                const float l = warp_sum(__uint_as_float((uint32_t)(H1 >> 32)) * expsub(mu, m));
                const float inv = 1.0f / l;
                const uint32_t w0 = pack_bf16(expsub(bf_lo(s0), m) * inv, expsub(bf_hi(s0), m) * inv);
                const uint32_t w1 = pack_bf16(expsub(bf_lo(s1), m) * inv, expsub(bf_hi(s1), m) * inv);
#pragma unroll
                for (int j = 0; j < 8; j++) {
                    Q[2 * j] = __shfl_sync(~0u, w0, 4 * j + t) & vmask;
                    Q[2 * j + 1] = __shfl_sync(~0u, w1, 4 * j + t) & vmask;
                }
            } else {
#pragma unroll
                for (int j = 0; j < 8; j++) {
                    const int src = (((j + g) & 7) << 2) + t;
                    Q[j] = __shfl_sync(~0u, (uint32_t)H0, src);
                    Q[8 + j] = __shfl_sync(~0u, (uint32_t)H1, src);
                }
            }
            unn = nstatic + (int)__shfl_sync(~0u, nxt, 0);
            if (CLU && ((NU - EARLY - unn) & ~(7 << ELOG)) == 0 && lane < MINCL)
                st_relaxed64(&scratch(p)->dry[lane][(NU - EARLY - unn) >> ELOG],
                             (time_ns() - (((uint32_t)clock() - tk) >> 1) + (NU - unn) * TPU / 16) | (unsigned long long)tag << 32);
        }
        if (u >= NUK && lane < NR)
            red_add_u32(vdst,
                        1u + ((__float_as_uint(oret.x) | __float_as_uint(oret.y) | __float_as_uint(oret.z) | __float_as_uint(oret.w)) & zero));
        if (un >= NU) break;
        bu = bn;
        bn = unit_block<CLU>(unn);
        u = un;
        un = unn;
    }
}

__device__ __forceinline__ void k_helper(const Params& p, uint32_t help, unsigned epoch) {
    if ((threadIdx.x & 31) != 0) return;
    unsigned (*ctl)[32] = scratch(p)->ctl[epoch & 1];
    unsigned sent0 = 0, sent1 = 0, n = 0;
    int seen = 0;
    bool fin = false;
    while (!fin || seen < 2) {
        if (!fin) {
            fin = ld_acquire_cta_shared(help + 8) == NW + XW;
            const unsigned c0 = ld_acquire_cta_shared(help), c1 = ld_acquire_cta_shared(help + 4);
            if (c0 != sent0 || c1 != sent1) {
                fence_gpu();
                if (c0 != sent0) red_add_u32(&ctl[C_KDONE][0], c0 - sent0);
                if (c1 != sent1) red_add_u32(&ctl[C_KDONE + 1][0], c1 - sent1);
                sent0 = c0; sent1 = c1;
            }
        }
        if (seen < 2 && ld_acquire(&ctl[C_KDONE + seen][0]) >= NUK / 2) {
            st_release_cta_shared(help + 12 + 4 * seen, 1u);
            seen++;
        } else {
            __nanosleep(300);
        }
        if (++n > SPIN_LIMIT) __trap();
    }
}

__device__ __forceinline__ void v_poller(const Params& p, uint32_t sbase, int f, int w) {
    constexpr int HL = NH;
    const int lane = threadIdx.x & 31;
    const unsigned (*cp)[32] = &scratch(p)->vdone[((f * NPOLL + w) % NREP) * NH];
    unsigned n = 0;
    while (ld_acquire_cta_shared(sbase + M_HELP + 12) == 0) { __nanosleep(1000); if (++n > SPIN_LIMIT) __trap(); }
    int h = 0;
    bool fast = false;
    while (h < HL) {
        const unsigned r = __ballot_sync(~0u, ld_acquire(&cp[min(h + (lane & 3), HL - 1)][0]) >= 4 * UPP) & 15u;
        if (r & 1) {
            h = min(HL, h + __ffs(~r) - 1);
            __syncwarp();
            if (lane == 0) asm volatile("red.release.cta.shared::cta.max.u32 [%0], %1;" ::"r"(sbase + M_HELP + 20), "r"(h) : "memory");
        }
        if (h < HL - 4) {
            __nanosleep(h ? 300 : 1000);
        } else if (!fast) {
            fast = true;
            const long long t0 = clock64();
            while (clock64() - t0 < w * PGAP) {}
        }
        if (++n > SPIN_LIMIT) __trap();
    }
}
__device__ __forceinline__ void finisher(const Params& p, uint32_t sbase, int f) {
    constexpr int HL = NH;
    const int lane = threadIdx.x & 31;
    {
        const char* wg = reinterpret_cast<const char*>(p.wo);
        const uint32_t dst = sbase + 4 * SLOT + (16 * (lane & 7) + (lane >> 3)) * 16;
#pragma unroll 1
        for (int h = -FPF - 4; h < HL; h++) {
            if (lane == 0 && (unsigned)(h + FPF) < (unsigned)HL) l2_prefetch(wg + (size_t)(h + FPF) * 147456 + f * 2048, 2048);
            if (h >= 0) {
#pragma unroll
                for (int r = 0; r < 4; r++)
                    asm volatile("cp.async.cg.shared.global [%0], [%1], 16;" ::"r"(dst + h * 2048 + ((r & 1) * 4 + (r >> 1) * 8) * 16),
                                 "l"(wg + (size_t)(h * 128 + r * 32 + lane) * (DM * 2) + f * 16) : "memory");
            }
            __nanosleep(FSLEEP);
        }
        asm volatile("cp.async.wait_all;" ::: "memory");
        __syncwarp();
    }
    TS(11);
    const float4* vec = scratch(p)->oacc + ((lane >> 2) & 3) * 32 + (lane >> 4) * 16 + (lane & 3);
    float acc[2][2][4];
#pragma unroll
    for (int i = 0; i < 16; i++) acc[i >> 3][(i >> 2) & 1][i & 3] = 0.f;
    uint32_t* outp = reinterpret_cast<uint32_t*>(p.out + (lane >> 2) * (2 * DM) + f * 8 + (lane & 3) * 2);
    uint32_t wa = sbase + 4 * SLOT + lane * 16;
    auto project = [&](const float4 (&x)[4], const uint32_t (&w)[4][4]) {
#pragma unroll
        for (int s = 0; s < 4; s++) {
            const uint32_t a[4] = {pack_bf16(x[s].x, x[s].y), 0u, pack_bf16(x[s].z, x[s].w), 0u};
            mma16816(acc[0][s & 1], a, w[s >> 1][(s & 1) * 2], w[s >> 1][(s & 1) * 2 + 1]);
            mma16816(acc[1][s & 1], a, w[2 + (s >> 1)][(s & 1) * 2], w[2 + (s >> 1)][(s & 1) * 2 + 1]);
        }
    };
    int h = 0;
    unsigned n = 0;
    while (h < HL) {
        uint32_t w[4][4];
#pragma unroll
        for (int q = 0; q < 4; q++) ldsm4t(w[q], wa + q * 512);
        int ready;
        while ((ready = ld_acquire_cta_shared(sbase + M_HELP + 20)) <= h) {
            if (h < HL - 3) __nanosleep(100);
            if (++n > (SPIN_LIMIT << 4)) __trap();
        }
        float4 x[4], y[4];
#pragma unroll
        for (int s = 0; s < 4; s++) x[s] = ld_relaxed16(vec + s * 4);
        const bool two = ready > h + 1;
        if (two) {
#pragma unroll
            for (int s = 0; s < 4; s++) y[s] = ld_relaxed16(vec + 128 + s * 4);
        }
        project(x, w);
        if (two) {
#pragma unroll
            for (int q = 0; q < 4; q++) ldsm4t(w[q], wa + 2048 + q * 512);
            project(y, w);
        }
        const int nr = two ? 2 : 1;
        h += nr;
        vec += nr * 128;
        wa += nr * 2048;
        const float o0 = acc[0][0][0] + acc[0][1][0] + __shfl_down_sync(~0u, acc[1][0][0] + acc[1][1][0], 16);
        const float o1 = acc[0][0][1] + acc[0][1][1] + __shfl_down_sync(~0u, acc[1][0][1] + acc[1][1][1], 16);
        asm volatile("{\n.reg .pred p;\nsetp.ne.u32 p, %2, 0;\n@p st.global.u32 [%0], %1;\n}" ::"l"(outp), "r"(pack_bf16(o0, o1)),
                     "r"((uint32_t)(lane < 16 && h == NH)) : "memory");
    }
}

__device__ __noinline__ void f_collect(const unsigned (*flag)[32], unsigned full, const float4* src, unsigned todo, uint32_t sbase) {
    const int lane = threadIdx.x & 31, g = lane >> 2, t = lane & 3;
    const bool last = todo != 15;
    unsigned n = 0;
    while (todo) {
        const unsigned v = ld_acquire(&flag[t][0]);
        unsigned m = __ballot_sync(~0u, v == full) & todo;
        if (m == 0) {
            if (!last || __shfl_sync(~0u, v, 0) == 0) __nanosleep(200);
            if (++n > SPIN_LIMIT) __trap();
            continue;
        }
        __syncwarp();
        todo ^= m;
        if (last) TS(16);
        do {
            const int h0 = __ffs(m) - 1, h1 = 31 - __clz(m);
            m &= ~((1u << h0) | (1u << h1));
            float4 x[8];
#pragma unroll
            for (int b = 0; b < 8; b++) x[b] = ld_relaxed16(src + ((b & 4) ? h1 : h0) * 128 + (b & 3) * 32 + lane);
#pragma unroll
            for (int b = 0; b < 8; b++) {
                const uint32_t lo = pack_bf16(x[b].x, x[b].y), hi = pack_bf16(x[b].z, x[b].w);
                const uint32_t o = __shfl_xor_sync(~0u, (g & 1) ? lo : hi, 4);
                const uint32_t e0 = (g & 1) ? o : lo, e1 = (g & 1) ? hi : o;
                asm volatile("st.shared.v2.u32 [%0], {%1,%2};"
                             ::"r"(sbase + F_BF + ((b & 4) ? h1 : h0) * 1024 + t * 256 + ((b ^ t) & 3) * 64 + g * 8),
                               "r"(__byte_perm(e0, e1, 0x5410)), "r"(__byte_perm(e0, e1, 0x7632)) : "memory");
            }
            __syncwarp();
            if (lane < (h0 == h1 ? 1 : 2))
                asm volatile("mbarrier.arrive.shared::cta.b64 _, [%0];" ::"r"(sbase + F_BAR + 32 + (lane ? h1 : h0) * 8) : "memory");
        } while (m);
    }
    if (last) TS(17);
}

__device__ __forceinline__ void f_request(const Params& p, const CUtensorMap* tm, int panel, int rank, int nsl, int delay, int step, unsigned tag,
                                          uint32_t sbase, uint64_t pol) {
    const int lane = threadIdx.x & 31;
    if (lane == 0) asm volatile("prefetch.tensormap [%0];" ::"l"(tm) : "memory");
    unsigned long long v;
    unsigned n = 0;
    while (!__all_sync(~0u, (v = ld_relaxed64(&scratch(p)->dry[blockIdx.x >> 3][lane >> 2])) >> 32 == tag)) {
        __nanosleep(200);
        if (++n > SPIN_LIMIT) __trap();
    }
    const uint32_t t0 = __shfl_sync(~0u, (uint32_t)v, 0);
    uint32_t due = t0 + (__reduce_add_sync(~0u, (int)((uint32_t)v - t0)) >> 5);
    TS(22);
    due += delay;
#pragma unroll 1
    for (int q = 0; q < 8 * nsl; q++, due += step) {
        if (q >= LAG * nsl) mbar_spin(sbase + F_BAR + 64 + (q - LAG * nsl) * 8);
        while ((int)(time_ns() - due) < 0 && ++n < SPIN_LIMIT) {}
        tma3d_warp(sbase + F_W - (q >> 3) * 2 * SLOT + (q & 7) * 8192, tm, 0, (rank * 8 + (q & 7)) * 64, panel + (q >> 3), sbase + F_BAR + 64 + q * 8,
                   8192, pol);
    }
    TS(18);
}

__device__ __forceinline__ void f_project(const Params& p, int rank, int j, int nsl, uint32_t sbase) {
    const int lane = threadIdx.x & 31, g = lane >> 2, t = lane & 3;
    const uint32_t wa = sbase + F_W + ((lane & 7) + (lane >> 4) * 8) * 128 + (((2 * j + ((lane >> 3) & 1)) ^ (lane & 7)) * 16);
    const uint32_t ba = sbase + F_BF + (g & 3) * 64 + t * 16;
    const bool up = t & 2;
#pragma unroll 1
    for (int sl = 0; sl < nsl; sl++) {
        const uint32_t rdst = mapa(sbase + F_RX + sl * 1024 + rank * 128 + g * 16 + (t & 1) * 8, 2 * j + (t >> 1));
        const uint32_t rbar = mapa(sbase + F_BAR + 16 + sl * 8, 2 * j + (t >> 1));
        float acc[2][4];
#pragma unroll
        for (int k = 0; k < 8; k++) acc[k >> 2][k & 3] = 0.f;
#pragma unroll 1
        for (int h = 0; h < 4; h++) {
            uint32_t wp = wa + h * 16384 - sl * 2 * SLOT, last = h == 3;
            mbar_spin(sbase + F_BAR + 32 + h * 8);
            uint32_t a[8][4], bf[4][4];
#pragma unroll
            for (int s = 0; s < 4; s++)
                asm volatile("ld.shared.v4.u32 {%0,%1,%2,%3}, [%4];" : "=r"(bf[s][0]), "=r"(bf[s][1]), "=r"(bf[s][2]), "=r"(bf[s][3])
                             : "r"(((ba + h * 1024) ^ (s * 64)) + s * 256) : "memory");
            asm volatile("" : "+r"(wp), "+r"(last));
#pragma unroll
            for (int q = 0; q < 2; q++) {
                mbar_spin(sbase + F_BAR + 64 + sl * 64 + h * 16 + q * 8);
#pragma unroll
                for (int s = 4 * q; s < 4 * q + 4; s++) ldsm4t(a[s], wp + s * 2048);
            }
#pragma unroll
            for (int s = 0; s < 8; s++) mma16816(acc[s & 1], a[s], bf[s & 3][(s >> 2) * 2], bf[s & 3][(s >> 2) * 2 + 1]);
            const float v0 = up ? acc[0][2] + acc[1][2] : acc[0][0] + acc[1][0], v1 = up ? acc[0][3] + acc[1][3] : acc[0][1] + acc[1][1];
            asm volatile("{\n.reg .pred p;\nsetp.ne.u32 p, %4, 0;\n"
                         "@p st.async.weak.shared::cluster.mbarrier::complete_tx::bytes.v2.b32 [%0], {%1,%2}, [%3];\n}"
                         ::"r"(rdst), "r"(__float_as_uint(v0)), "r"(__float_as_uint(v1)), "r"(rbar), "r"(last) : "memory");
        }
    }
    TS(20);
}

__device__ __forceinline__ void f_receive(const Params& p, __nv_bfloat16* out, int nsl, uint32_t sbase) {
    const int lane = threadIdx.x & 31;
    out += (lane & 3) * (2 * DM) + (lane >> 2);
#pragma unroll 1
    for (int sl = -1; sl < nsl; sl++) {
        __nv_bfloat16* dst = out + sl * 64;
        uint32_t src = sbase + F_RX + sl * 1024 + lane * 4;
        asm volatile("" : "+l"(dst), "+r"(src));
        if (sl >= 0) mbar_spin_cluster(sbase + F_BAR + 16 + sl * 8);
        float v[8];
#pragma unroll
        for (int r = 0; r < 8; r++) asm volatile("ld.shared.f32 %0, [%1];" : "=f"(v[r]) : "r"(src + r * 128) : "memory");
        const float o = ((v[0] + v[1]) + (v[2] + v[3])) + ((v[4] + v[5]) + (v[6] + v[7]));
        asm volatile("{\n.reg .pred p;\nsetp.ge.s32 p, %2, 0;\n@p st.global.u16 [%0], %1;\n}"
                     ::"l"(dst), "h"((unsigned short)pack_bf16(o, 0.f)), "r"(sl) : "memory");
    }
    TS(15);
}

constexpr int BS_WUK = 5, BS_Q = 9, BS_CKV = 11, BS_PART = 27, BS_WUV = 29, BS_END = 33;

__device__ __noinline__ void b_issue(const Params& p, int n, int bi, uint32_t sbase, uint64_t pol) {
    if (n >= BS_END || (n >= BS_Q && n < BS_CKV) || (n >= BS_PART && n < BS_WUV)) return;
    const uint32_t bar = sbase + M_BAR + (NSLOT + n % BRING) * 8;
    const CUtensorMap* tm;
    int row, panel = 2 * bi;
    if (n < BS_WUK) { tm = &p.tm_wq; row = n * 128; }
    else if (n < BS_Q) { tm = &p.tm_wuk; row = (n - BS_WUK) * 128; }
    else if (n < BS_PART) {
        tm = &p.tm_ckv; panel = 0;
        row = (bi >> 3) * SK + ((n - BS_CKV) * 8 + (bi & 7)) * 32;
    }
    else { tm = &p.tm_wuv; row = (n - BS_WUV) * 128; }
    mbar_expect_tx(bar, n == 0 ? 32768 + 4 * 1152 : 32768);
    tma3d(sbase + (n % BRING) * SLOT, tm, 0, row, panel, bar, pol);
}
__device__ __forceinline__ void b_issue_xchg(int n, const void* src, uint32_t sbase, uint64_t pol) {
    asm volatile("fence.proxy.async;" ::: "memory");
#pragma unroll
    for (int i = 0; i < 2; i++) {
        const uint32_t bar = sbase + M_BAR + (NSLOT + (n + i) % BRING) * 8;
        mbar_expect_tx(bar, 32768);
        bulk_load(sbase + ((n + i) % BRING) * SLOT, reinterpret_cast<const char*>(src) + i * 32768, 32768, bar, pol);
    }
}
__device__ __forceinline__ void b_wait(int n, uint32_t sbase) {
    mbar_wait(sbase + M_BAR + (NSLOT + n % BRING) * 8, (n / BRING) & 1);
}

__device__ __noinline__ void b_gemm(const Params& p, uint32_t sbase, int n0, int n1, int ktot, uint32_t xh, uint32_t xl, int pitch,
                                    int bi, uint64_t pol) {
    const int tid = threadIdx.x, warp = tid >> 5, lane = tid & 31, g = lane >> 2, t = lane & 3;
    const uint32_t woff = (warp >> 2) * 16384 + (lane & 15) * 128 + ((((warp & 3) * 2 + (lane >> 4)) ^ (lane & 7)) * 16);
    const uint32_t xoff = (g & 3) * pitch + t * 4;
    float acc[2][4];
#pragma unroll
    for (int i = 0; i < 8; i++) acc[i >> 2][i & 3] = 0.f;
#pragma unroll 1
    for (int n = n0; n < n1; n++) {
        b_wait(n, sbase);
        const uint32_t slot = sbase + (n % BRING) * SLOT + woff;
        const int k0 = (n - n0) * 128;
        const int ns = min(8, (ktot - k0) >> 4);
#pragma unroll 2
        for (int s = 0; s < ns; s++) {
            uint32_t a[4], w[4];
            const uint32_t xo = xoff + (k0 + 16 * s) * 2;
            a[0] = lds32(xh + xo); a[2] = lds32(xh + xo + 16);
            a[1] = xl ? lds32(xl + xo) : 0u; a[3] = xl ? lds32(xl + xo + 16) : 0u;
            ldsm4t(w, slot + s * 2048);
            mma16816(acc[0], a, w[0], w[1]);
            mma16816(acc[1], a, w[2], w[3]);
        }
        __syncthreads();
        if (tid == 0) b_issue(p, n + BD, bi, sbase, pol);
    }
    if (g < 4) {
#pragma unroll
        for (int j = 0; j < 2; j++)
            asm volatile("st.shared.u32 [%0], %1;" ::"r"(sbase + M_QB + g * QP + (warp * 16 + j * 8 + t * 2) * 2),
                         "r"(pack_bf16(acc[j][0] + acc[j][2], acc[j][1] + acc[j][3])) : "memory");
    }
    __syncthreads();
}

__device__ __forceinline__ void b_exchange(unsigned* c, int n, const void* src, uint32_t sbase, uint64_t pol) {
    TS(n == BS_Q ? 24 : 28);
    __syncthreads();
    if (threadIdx.x == 0) {
        TS(n == BS_Q ? 25 : 29);
        fence_gpu();
        TS(n == BS_Q ? 26 : 30);
        red_add_u32(c, 1u);
        wait_count(c, NBCTA);
        TS(n == BS_Q ? 27 : 31);
        b_issue_xchg(n, src, sbase, pol);
    }
}

template <bool CLU>
__device__ __noinline__ void b_chain(const Params& p, char* smem, uint32_t sbase, int bi, unsigned epoch, uint64_t pol) {
    const int tid = threadIdx.x, warp = tid >> 5, lane = tid & 31, g = lane >> 2, t = lane & 3;
    unsigned (*ctl)[32] = scratch(p)->ctl[epoch & 1];
    float* red = reinterpret_cast<float*>(smem + 5 * SLOT);
    __syncthreads();
    b_gemm(p, sbase, 0, BS_WUK, DM, sbase + M_XB, 0, XP, bi, pol);
    TS(6);
    {
        uint32_t Q[16];
#pragma unroll
        for (int c = 0; c < 16; c++) Q[c] = lds32(sbase + M_QB + (g & 3) * QP + c * 16 + t * 4);
        float* qa = reinterpret_cast<float*>(smem + M_QA);
#pragma unroll 1
        for (int n = BS_WUK; n < BS_Q; n++) {
            b_wait(n, sbase);
            const uint32_t base = sbase + (n % BRING) * SLOT + (warp * 16 + (lane & 15)) * 128;
            float d[2][4];
#pragma unroll
            for (int i = 0; i < 8; i++) d[i >> 2][i & 3] = 0.f;
#pragma unroll
            for (int s = 0; s < 8; s++) {
                uint32_t a[4];
                ldsm4(a, base + (s >> 2) * 16384 + (((2 * (s & 3) + (lane >> 4)) ^ (lane & 7)) * 16));
                mma16816(d[s & 1], a, Q[2 * s], Q[2 * s + 1]);
            }
            const int c = (n - BS_WUK) * 128 + warp * 16 + g + 8 * (t >> 1);
            qa[(2 * (t & 1)) * 512 + c] = (t & 2) ? d[0][2] + d[1][2] : d[0][0] + d[1][0];
            qa[(2 * (t & 1) + 1) * 512 + c] = (t & 2) ? d[0][3] + d[1][3] : d[0][1] + d[1][1];
            __syncthreads();
            if (tid == 0) b_issue(p, n + BD, bi, sbase, pol);
        }
#pragma unroll 1
        for (int r = 0; r < 2; r++) {
            const int id = tid + r * 256;
            const int b = id >> 7, c0 = ((id >> 2) & 31) * 16 + (id & 3) * 2;
            const float2 u0 = *reinterpret_cast<const float2*>(qa + b * 512 + c0);
            const float2 u1 = *reinterpret_cast<const float2*>(qa + b * 512 + c0 + 8);
            const uint32_t h0 = pack_bf16(u0.x, u0.y), h1 = pack_bf16(u1.x, u1.y);
            const uint32_t l0 = pack_bf16(u0.x - bf_lo(h0), u0.y - bf_hi(h0)), l1 = pack_bf16(u1.x - bf_lo(h1), u1.y - bf_hi(h1));
            scratch(p)->qabs[((id >> 2) * 4 + (bi >> 3)) * 32 + (bi & 7) * 4 + (id & 3)] = make_uint4(h0, l0, h1, l1);
        }
    }
    b_exchange(&ctl[C_BBAR][0], BS_Q, &scratch(p)->qabs[(bi >> 3) * 4096], sbase, pol);
    {
        uint32_t qf[4][4][4];
        b_wait(BS_Q + (warp >> 2), sbase);
        TS(7);
        {
            const uint4* qs = reinterpret_cast<const uint4*>(smem + ((BS_Q + (warp >> 2)) % BRING) * SLOT) + (warp & 3) * 512 + lane;
#pragma unroll
            for (int s = 0; s < 4; s++)
#pragma unroll
                for (int i = 0; i < 4; i++) {
                    const uint4 v = qs[(s * 4 + i) * 32];
                    qf[i][s][0] = v.x; qf[i][s][1] = v.y; qf[i][s][2] = v.z; qf[i][s][3] = v.w;
                }
        }
        __syncthreads();
        if (tid == 0) { b_issue(p, BS_Q + BD, bi, sbase, pol); b_issue(p, BS_Q + 1 + BD, bi, sbase, pol); }
        float acc[2][8][4];
#pragma unroll
        for (int i = 0; i < 2; i++)
#pragma unroll
            for (int j = 0; j < 8; j++) { acc[i][j][0] = acc[i][j][1] = acc[i][j][2] = acc[i][j][3] = 0.f; }
        float mrun = -INFINITY, lrun = 0.f;
        const int head = tid >> 3, kq = tid & 7;
        float* alpha = reinterpret_cast<float*>(smem + M_ALPHA);
        for (int n = BS_CKV; n < BS_PART; n++) {
            b_wait(n, sbase);
            const uint32_t slot = sbase + (n % BRING) * SLOT;
            float sc[4][4][4];
#pragma unroll
            for (int i = 0; i < 4; i++)
#pragma unroll
                for (int j = 0; j < 4; j++) { sc[i][j][0] = sc[i][j][1] = sc[i][j][2] = sc[i][j][3] = 0.f; }
#pragma unroll
            for (int j = 0; j < 4; j++)
#pragma unroll
                for (int sp = 0; sp < 2; sp++) {
                    uint32_t bf[4];
                    ldsm4(bf, slot + warp * 4096 + (8 * j + (lane & 7)) * 128 + (((4 * sp + (lane >> 3)) ^ (lane & 7)) * 16));
#pragma unroll
                    for (int i = 0; i < 4; i++) {
                        mma16816(sc[i][j], qf[i][2 * sp], bf[0], bf[1]);
                        mma16816(sc[i][j], qf[i][2 * sp + 1], bf[2], bf[3]);
                    }
                }
#pragma unroll
            for (int i = 0; i < 4; i++)
#pragma unroll
                for (int j = 0; j < 4; j++)
                    *reinterpret_cast<float2*>(red + warp * 1024 + (8 * i + g) * 32 + ((8 * j) ^ (8 * (g & 3))) + 2 * t) =
                        make_float2(sc[i][j][0] + sc[i][j][2], sc[i][j][1] + sc[i][j][3]);
            __syncthreads();
            if (tid == 0 && n > BS_CKV) b_issue(p, n - 1 + BD, bi, sbase, pol);
            {
                float4 s = make_float4(0.f, 0.f, 0.f, 0.f);
#pragma unroll
                for (int w = 0; w < 8; w++) {
                    const float4 v = *reinterpret_cast<const float4*>(red + w * 1024 + head * 32 + ((4 * kq) ^ (8 * (head & 3))));
                    s.x += v.x; s.y += v.y; s.z += v.z; s.w += v.w;
                }
                const uint32_t r0 = pack_bf16(s.x, s.y), r1 = pack_bf16(s.z, s.w);
                const uint32_t s0 = pack_bf16(bf_lo(r0) * SCALE, bf_hi(r0) * SCALE);
                const uint32_t s1 = pack_bf16(bf_lo(r1) * SCALE, bf_hi(r1) * SCALE);
                const float f0 = bf_lo(s0), f1 = bf_hi(s0), f2 = bf_lo(s1), f3 = bf_hi(s1);
                float mx = fmaxf(fmaxf(f0, f1), fmaxf(f2, f3));
                mx = fmaxf(mx, __shfl_xor_sync(~0u, mx, 1));
                mx = fmaxf(mx, __shfl_xor_sync(~0u, mx, 2));
                mx = fmaxf(mx, __shfl_xor_sync(~0u, mx, 4));
                const float mnew = fmaxf(mrun, mx);
                const float al = expsub(mrun, mnew);
                const float p0 = expsub(f0, mnew), p1 = expsub(f1, mnew), p2 = expsub(f2, mnew), p3 = expsub(f3, mnew);
                lrun = lrun * al + ((p0 + p1) + (p2 + p3));
                mrun = mnew;
                *reinterpret_cast<uint2*>(smem + M_P + head * 80 + kq * 8) = make_uint2(pack_bf16(p0, p1), pack_bf16(p2, p3));
                if (kq == 0) alpha[head] = al;
            }
            __syncthreads();
            {
                uint32_t pf[2][2][4];
#pragma unroll
                for (int i = 0; i < 2; i++)
#pragma unroll
                    for (int ks = 0; ks < 2; ks++)
                        ldsm4(pf[i][ks], sbase + M_P + (16 * i + (lane & 15)) * 80 + (16 * ks + 8 * (lane >> 4)) * 2);
#pragma unroll
                for (int i = 0; i < 2; i++) {
                    const float a0 = alpha[16 * i + g], a1 = alpha[16 * i + 8 + g];
#pragma unroll
                    for (int j = 0; j < 8; j++) { acc[i][j][0] *= a0; acc[i][j][1] *= a0; acc[i][j][2] *= a1; acc[i][j][3] *= a1; }
                }
#pragma unroll
                for (int j = 0; j < 8; j++) {
                    uint32_t bf[4];
                    ldsm4t(bf, slot + warp * 4096 + lane * 128 + ((j ^ (lane & 7)) * 16));
#pragma unroll
                    for (int i = 0; i < 2; i++) {
                        mma16816(acc[i][j], pf[i][0], bf[0], bf[1]);
                        mma16816(acc[i][j], pf[i][1], bf[2], bf[3]);
                    }
                }
            }
        }
        __syncthreads();
        if (tid == 0) b_issue(p, BS_PART - 1 + BD, bi, sbase, pol);
        lrun += __shfl_xor_sync(~0u, lrun, 1);
        lrun += __shfl_xor_sync(~0u, lrun, 2);
        lrun += __shfl_xor_sync(~0u, lrun, 4);
        if (kq == 0) scratch(p)->bml[head * NBCTA + bi] = make_float2(mrun, lrun);
#pragma unroll
        for (int i = 0; i < 2; i++)
#pragma unroll
            for (int j = 0; j < 8; j++) {
                scratch(p)->bpart[((16 * i + g) * NBCTA + bi) * 256 + warp * 32 + j * 4 + t] = make_float2(acc[i][j][0], acc[i][j][1]);
                scratch(p)->bpart[((16 * i + 8 + g) * NBCTA + bi) * 256 + warp * 32 + j * 4 + t] = make_float2(acc[i][j][2], acc[i][j][3]);
            }
    }
    b_exchange(&ctl[C_BBAR + 1][0], BS_PART, &scratch(p)->bpart[bi * NBCTA * 256], sbase, pol);
    {
        float* omega = reinterpret_cast<float*>(smem + M_OMEGA);
        if (warp == 0) {
            __syncwarp();
            const uint2 ml = ld_relaxed8(&scratch(p)->bml[bi * NBCTA + lane]);
            const float ms = __uint_as_float(ml.x);
            float m = ms;
            m = fmaxf(m, __shfl_xor_sync(~0u, m, 1));
            m = fmaxf(m, __shfl_xor_sync(~0u, m, 2));
            m = fmaxf(m, __shfl_xor_sync(~0u, m, 4));
            const float w = expsub(ms, m);
            float l = w * __uint_as_float(ml.y);
            l += __shfl_xor_sync(~0u, l, 1);
            l += __shfl_xor_sync(~0u, l, 2);
            l += __shfl_xor_sync(~0u, l, 4);
            omega[lane] = w / l;
        }
        __syncthreads();
        b_wait(BS_PART, sbase);
        b_wait(BS_PART + 1, sbase);
#pragma unroll 1
        for (int b = 0; b < 4; b++) {
            const float2* ps = reinterpret_cast<const float2*>(smem + ((BS_PART + (b >> 1)) % BRING) * SLOT) + (b & 1) * 2048 + tid;
            float c0 = 0.f, c1 = 0.f;
#pragma unroll
            for (int s = 0; s < 8; s++) {
                const float w = omega[b * 8 + s];
                const float2 v = ps[s * 256];
                c0 = fmaf(w, v.x, c0);
                c1 = fmaf(w, v.y, c1);
            }
            const uint32_t hi = pack_bf16(c0, c1);
            *reinterpret_cast<uint32_t*>(smem + M_CH + b * CP + tid * 4) = hi;
            *reinterpret_cast<uint32_t*>(smem + M_CL + b * CP + tid * 4) = pack_bf16(c0 - bf_lo(hi), c1 - bf_hi(hi));
        }
        __syncthreads();
        if (tid == 0) { b_issue(p, BS_PART + BD, bi, sbase, pol); b_issue(p, BS_PART + 1 + BD, bi, sbase, pol); }
    }
    b_gemm(p, sbase, BS_WUV, BS_END, 512, sbase + M_CH, sbase + M_CL, CP, bi, pol);
    TS(12);
    if (CLU) {
        if (warp < 4) {
            const unsigned short* c = reinterpret_cast<const unsigned short*>(smem + M_QB + warp * QP) + 16 * t + g;
            scratch(p)->octx[(bi * 4 + warp) * 32 + lane] = make_float4(bf_lo(c[0]), bf_lo(c[8]), bf_lo(c[64]), bf_lo(c[72]));
        }
        __syncthreads();
        if (tid == 0) asm volatile("st.release.gpu.global.u32 [%0], %1;" ::"l"(&scratch(p)->cdone[bi][0]), "r"(epoch + 1) : "memory");
        return;
    }
    if (tid == 0) {
#pragma unroll 1
        for (int i = 0; i < 4; i++) {
            mbar_expect_tx(sbase + M_BAR + i * 8, 36864);
            tma3d(sbase + i * 36864, &p.tm_wo, 0, bi * 128 + i * 32, 0, sbase + M_BAR + i * 8, pol);
        }
    }
    TS(8);
    {
        float acc[9][4];
#pragma unroll
        for (int j = 0; j < 9; j++) { acc[j][0] = acc[j][1] = acc[j][2] = acc[j][3] = 0.f; }
#pragma unroll 1
        for (int i = 0; i < 4; i++) {
            const uint32_t xo = sbase + M_QB + (g & 3) * QP + i * 64 + t * 4;
            const uint32_t a0[4] = {lds32(xo), 0u, lds32(xo + 16), 0u}, a1[4] = {lds32(xo + 32), 0u, lds32(xo + 48), 0u};
            mbar_wait(sbase + M_BAR + i * 8, 0);
#pragma unroll
            for (int j = 0; j < 9; j++) {
                const int nt = warp * 9 + j;
                uint32_t w[4];
                ldsm4t(w, sbase + i * 36864 + (nt >> 3) * 4096 + lane * 128 + (((nt & 7) ^ (lane & 7)) * 16));
                mma16816(acc[j], a0, w[0], w[1]);
                mma16816(acc[j], a1, w[2], w[3]);
            }
        }
        if (g < 4) {
#pragma unroll
            for (int j = 0; j < 9; j++) {
                const int c2 = (warp * 9 + j) * 4 + t;
                st_tagged2(&scratch(p)->outb[((c2 / 9) * NH + bi) * 36 + g * 9 + c2 % 9], acc[j][0], acc[j][1], epoch + 1);
            }
        }
    }
    TS(9);
    {
        const uint4* src = scratch(p)->outb + (bi * NH + (tid >> 3)) * 36 + (tid & 7);
        float2* part = reinterpret_cast<float2*>(red);
        unsigned n = 0;
        while (true) {
            ulonglong2 v[5];
            bool ok = true;
#pragma unroll
            for (int i = 0; i < 5; i++)
                if (i < 4 || (tid & 7) < 4) v[i] = ld_tagged2(src + i * 8);
#pragma unroll
            for (int i = 0; i < 5; i++)
                if (i < 4 || (tid & 7) < 4) {
                    ok = ok && (unsigned)(v[i].x >> 32) == epoch + 1 && (unsigned)(v[i].y >> 32) == epoch + 1;
                    part[(tid >> 3) * 36 + (tid & 7) + i * 8] = make_float2(__uint_as_float((unsigned)v[i].x), __uint_as_float((unsigned)v[i].y));
                }
            if (ok) break;
            __nanosleep(400);
            if (++n > SPIN_LIMIT) __trap();
        }
        __syncthreads();
        if (tid < 36) {
            float s0 = 0.f, s1 = 0.f;
#pragma unroll 8
            for (int h = 0; h < NH; h++) { const float2 v = part[h * 36 + tid]; s0 += v.x; s1 += v.y; }
            *reinterpret_cast<uint32_t*>(p.out + (tid / 9) * 2 * DM + DM + bi * 18 + (tid % 9) * 2) = pack_bf16(s0, s1);
        }
    }
    TS(10);
}

template <bool CLU>
__global__ void __launch_bounds__(256, 1) fused_decode_kernel(const __grid_constant__ Params p) {
    asm volatile("{\n.reg .pred p;\n.reg .u32 a;\n.reg .u64 b;\nsub.u32 a, %1, %4;\nsetp.lt.u32 p, a, %3;\n"
                 "mad.lo.u32 a, %2, %3, %1;\n"
                 "mad.wide.u32 b, a, %5, %0;\n@p prefetch.global.L2 [b];\n}"
                 ::"l"(p.kc), "r"(threadIdx.x), "r"(blockIdx.x), "n"(PFN), "n"(128), "n"(128) : "memory");
    if (blockIdx.x >= 1024) return;
    extern __shared__ __align__(1024) char smem_raw[];
    const uint32_t sbase = (smem_u32(smem_raw) + 1023u) & ~1023u;
    char* smem = smem_raw + (sbase - smem_u32(smem_raw));
    const int tid = threadIdx.x, warp = __shfl_sync(~0u, tid >> 5, 0), lane = tid & 31;
    const int cl = blockIdx.x >> 3, rank = blockIdx.x & 7;
    const bool isB = CLU ? rank < (cl < MINCL - 2 ? 2 : 3) : (blockIdx.x & 3) == 0 && blockIdx.x < 4 * NBCTA;
    const int bi = CLU ? (rank < 2 ? 2 * cl + rank : cl + MINCL + 2) : blockIdx.x >> 2;
    const int nb = CLU ? 6 * cl + rank - 2 - max(0, cl - (MINCL - 3)) : blockIdx.x - min(NBCTA, (blockIdx.x + 3) >> 2);
    const int blk = CLU ? (isB ? bi : NBCTA + nb) : blockIdx.x;
    const int nblk = CLU ? 8 * MINCL : gridDim.x, nnb = nblk - NBCTA;
    const int nstatic = nnb * (NW + XW);
    uint64_t pol;
    asm volatile("createpolicy.fractional.L2::evict_first.b64 %0, 1.0;" : "=l"(pol));
    const uint32_t wbar = sbase + M_BAR + warp * 8, wslot = sbase + warp * SLOT;
    const int u0 = warp * nnb + nb;
    const bool hold = ((blk >> 2) >> KMIN << KMIN) * 4 * UPP < nstatic;
    const uint32_t jbar = sbase + M_BAR + (NSLOT + BRING) * 8;
    if (warp < 4) {
        const char* src = reinterpret_cast<const char*>(p.kc) + (size_t)(((unsigned)u0 >> 7) * 1024 + (u0 & 127)) * TILE_BYTES;
        asm volatile("" : "+l"(src));
        mbar_init_warp(wbar);
        if (warp < NEARLY && !isB && (CLU || !hold)) tile_load_warp(wslot, src, wbar, pol);
    }
    asm volatile("" ::: "memory");
    if (warp == 7) {
        if (blk < 128) {
            uint64_t poln;
            asm volatile("createpolicy.fractional.L2::evict_normal.b64 %0, 1.0;" : "=l"(poln));
            mbar_init_warp(jbar);
            tma3d_warp(sbase + J0W, &p.tm_j0, blk * 32, 0, 0, jbar, 36864, poln);
            mbar_init_warp(jbar + 8);
            if (lane == 0) {
                mbar_expect_tx(jbar + 8, 4608);
                bulk_load(sbase + M_XA, p.xa, 4608, jbar + 8, poln);
            }
        }
        if (lane < 8) reinterpret_cast<unsigned*>(smem + M_HELP)[lane] = 0;
        __syncwarp();
        if (!isB) asm volatile("bar.arrive 2, %0;" ::"n"(32 * (NW + XW + 1)) : "memory");
    }
    unsigned epoch = 0;
    if (lane == 0) epoch = ld_relaxed4(scratch(p)->epoch);
    if (blk >= 128 ? warp >= 4 : isB && warp < 4) epoch = __shfl_sync(~0u, epoch, 0);
    if (isB && warp == 3) asm volatile("bar.sync 1, 160;" ::: "memory");
    if (isB && tid == 96) {
#pragma unroll 1
        for (int i = 0; i < BRING; i++) mbar_init(sbase + M_BAR + (NSLOT + i) * 8, 1);
        asm volatile("fence.mbarrier_init.release.cluster;" ::: "memory");
        if (hold) { unsigned n = 0; while (ld_acquire_cta_shared(sbase + M_HELP + 24) < 2) { if (++n > (SPIN_LIMIT << 4)) __trap(); } }
#pragma unroll 1
        for (int b = 0; b < 4; b++) bulk_load(sbase + M_XB + b * XP, p.xb + b * DM, 1152, sbase + M_BAR + NSLOT * 8, pol);
#pragma unroll 1
        for (int n = 0; n < BD; n++) b_issue(p, n, bi, sbase, pol);
    }
    if (warp >= 4 && blk < 128) {
        const int g = lane >> 2, t = lane & 3, j = tid - 128;
        asm volatile("bar.sync 1, %0;" ::"r"(isB ? 160 : 128) : "memory");
#pragma unroll 1
        for (int ph = -1;; ph++) {
        const int sl = ph > 0 ? blk + 128 - nblk : blk;
        const uint32_t wa = sbase + J0W + ((warp - 4) * 144 + (lane & 7) + (lane >> 4) * 8) * 64 + ((((lane >> 3) & 1) ^ ((lane >> 1) & 3)) * 16);
        const uint32_t xa = sbase + M_XA + (g & 3) * 1152 + (warp - 4) * 288 + t * 4;
        if (ph >= 0) mbar_wait(jbar + 8, 0);
        uint32_t xb[18];
#pragma unroll
        for (int s = 0; s < 18; s++) xb[s] = lds32(xa + s * 16);
        epoch = __shfl_sync(~0u, epoch, 0);
        STI(q1);
        if (ph >= 0) mbar_wait(jbar, ph);
        STI(q2);
        TS(13);
        float acc[4][4];
#pragma unroll
        for (int i = 0; i < 16; i++) acc[i >> 2][i & 3] = 0.f;
#pragma unroll
        for (int s = 0; s < 18; s++) {
            uint32_t w[4];
            ldsm4t(w, (wa ^ ((s & 1) * 32)) + (s >> 1) * 1024);
            mma16816(acc[s & 3], w, xb[s & ~1], xb[s | 1]);
        }
        STI(q3);
        float2* j0 = reinterpret_cast<float2*>(smem + M_J0);
        {
            float* jf = reinterpret_cast<float*>(j0) + (warp - 4) * 128 + (t & 1) * 64 + (t >> 1) * 8 + g;
#pragma unroll
            for (int i = 0; i < 4; i++)
                jf[(i & 1) * 32 + (i >> 1) * 16] = (t & 2) ? acc[i >> 1][2 + (i & 1)] + acc[2 + (i >> 1)][2 + (i & 1)] : acc[i >> 1][i & 1] + acc[2 + (i >> 1)][i & 1];
        }
        asm volatile("bar.sync 1, 128;" ::: "memory");
        const bool again = ph == 0 && blk + 128 - nblk >= nblk;
        if (again && tid == 224) {
            mbar_expect_tx(jbar, 36864);
            tma3d(sbase + J0W, &p.tm_j0, (blk + 128 - nblk) * 32, 0, 0, jbar, pol);
        }
        if (warp < 6) {
            const float2 v0 = j0[j], v1 = j0[64 + j], v2 = j0[128 + j], v3 = j0[192 + j];
            asm volatile("{\n.reg .pred p;\n.reg .b64 v;\nsetp.ge.s32 p, %3, 0;\nmov.b64 v, {%1, %2};\n@p st.relaxed.gpu.global.u64 [%0], v;\n}"
                         ::"l"(&scratch(p)->qll[(j >> 4) * 2048 + sl * 16 + (j & 15)]),
                           "r"(pack_bf16((v0.x + v1.x) + (v2.x + v3.x), (v0.y + v1.y) + (v2.y + v3.y))), "r"(epoch + 1), "r"(ph) : "memory");
            __syncwarp();
            if (lane == 0 && ph >= 0) asm volatile("red.relaxed.cta.shared::cta.add.u32 [%0], 1;" ::"r"(sbase + M_HELP + 24) : "memory");
        } else if (warp == 7) {
            if (blk < C_LINES && ph == 0) scratch(p)->ctl[(epoch & 1) ^ 1][blk][lane] = 0;
        }
        TS(1);
        if (ph >= 0 && !again) break;
        asm volatile("bar.sync 1, 128;" ::: "memory");
        }
    }
    if (CLU) {
        if (warp == 6) {
            if (lane < 24 && lane > 1) mbar_init(sbase + F_BAR + lane * 8, 1);
            if ((lane >> 1) == 1) mbar_expect_tx(sbase + F_BAR + lane * 8, 1024);
            asm volatile("fence.mbarrier_init.release.cluster;" ::: "memory");
        }
        asm volatile("barrier.cluster.arrive.relaxed.aligned;" ::: "memory");
    }
    const int c5 = cl % 5;
    const bool partA = CLU && c5 < 3;
    const int nwork = partA && rank == 7 ? 1 : NW + ((CLU ? rank < 2 + X3C && c5 < 4 : (nb & 3) < X3) ? 1 : 0);
    if (isB) {
        b_chain<CLU>(p, smem, sbase, bi, epoch, pol);
        if (!CLU) return;
        if (warp == 2) {
            unsigned n = 0;
            while (ld_acquire(&scratch(p)->ctl[epoch & 1][C_KDONE][0]) < NUK / 2) { __nanosleep(1000); if (++n > SPIN_LIMIT) __trap(); }
        }
    } else if (warp < NW + XW) {
        a_worker<CLU>(p, u0, warp >= nwork, warp < NEARLY && !hold, hold, nstatic, wslot, wbar, sbase + M_HELP,
                      epoch, pol);
        if (!CLU || warp < nwork) return;
        epoch = __shfl_sync(~0u, epoch, 0);
        unsigned n = 0;
        while (ld_acquire_cta_shared(sbase + M_HELP + 12) == 0) { __nanosleep(1000); if (++n > SPIN_LIMIT) __trap(); }
    } else if (warp == 7) {
#pragma unroll 1
        for (int i = nb; i < 4 * NH; i += nnb) scratch(p)->oacc[i * 32 + lane] = make_float4(0.f, 0.f, 0.f, 0.f);
        if (nb < NREP * NH) scratch(p)->vdone[nb][lane] = 0;
        __syncwarp();
        k_helper(p, sbase + M_HELP, epoch);
        if (nb == 0 && lane == 0) scratch(p)->epoch[0] = epoch + 1;
        __syncwarp();
    } else if (!CLU && nb < NFIN) {
        if (warp == 6) {
            finisher(p, sbase, nb);
            TS(4);
        } else if (warp >= 6 - NPOLL) {
            v_poller(p, sbase, nb, warp - (6 - NPOLL));
        }
    }
    if (!CLU) return;
    asm volatile("barrier.cluster.wait.acquire.aligned;" ::: "memory");
    const int nsl = c5 == 4 ? 2 : 1, panel = cl / 5 * 3 + (partA ? c5 : c5 - 3);
    if (warp >= 4) {
        f_project(p, rank, warp - 4, nsl, sbase);
        return;
    }
    if (isB ? warp == 2 : warp < 3 || nwork == 3)
        f_collect((partA ? scratch(p)->vdone : scratch(p)->cdone) + 4 * rank, partA ? 4 * UPP : epoch + 1,
                  (partA ? scratch(p)->oacc : scratch(p)->octx) + 4 * rank * 128, nwork == 1 ? 5 * warp : 15, sbase);
    if (warp != 3) return;
    f_request(p, partA ? &p.tm_fa : &p.tm_fb, panel, rank, nsl, nsl == 2 ? B0 + rank * (BJ / 8) : A0 + rank * (AJ / 8), nsl == 2 ? BJ : AJ, epoch + 1, sbase, pol);
    f_receive(p, p.out + (partA ? 0 : DM) + panel * 64 + rank * 8, nsl, sbase);
}

}

typedef CUresult (*EncodeFn)(CUtensorMap*, CUtensorMapDataType, cuuint32_t, void*, const cuuint64_t*, const cuuint64_t*,
                             const cuuint32_t*, const cuuint32_t*, CUtensorMapInterleave, CUtensorMapSwizzle,
                             CUtensorMapL2promotion, CUtensorMapFloatOOBfill);

extern "C" void kernel_launch(void* const* d_in, const int* in_sizes, int n_in, void* d_out, int out_size) {
    (void)in_sizes; (void)n_in; (void)out_size;
    static int nsm = 0, ncl = 0;
    static EncodeFn encode = nullptr;
    static void* scr = nullptr;
    cudaLaunchConfig_t cfg = {};
    cudaLaunchAttribute at[1];
    at[0].id = cudaLaunchAttributeClusterDimension;
    at[0].val.clusterDim.x = 8; at[0].val.clusterDim.y = 1; at[0].val.clusterDim.z = 1;
    cfg.blockDim = dim3(256); cfg.dynamicSmemBytes = SMEM_BYTES; cfg.stream = cudaStreamPerThread; cfg.attrs = at; cfg.numAttrs = 1;
    if (nsm == 0) {
        int dev = 0;
        cudaGetDevice(&dev);
        cudaDeviceGetAttribute(&nsm, cudaDevAttrMultiProcessorCount, dev);
        cudaFuncSetAttribute(fused_decode_kernel<false>, cudaFuncAttributeMaxDynamicSharedMemorySize, SMEM_BYTES);
        cudaFuncSetAttribute(fused_decode_kernel<true>, cudaFuncAttributeMaxDynamicSharedMemorySize, SMEM_BYTES);
        cfg.gridDim = dim3(128);
        if (cudaOccupancyMaxActiveClusters(&ncl, fused_decode_kernel<true>, &cfg) != cudaSuccess) { ncl = 0; (void)cudaGetLastError(); }
        if (ncl > MINCL) ncl = MINCL;
        void* fn = nullptr;
        cudaDriverEntryPointQueryResult qr;
        cudaGetDriverEntryPoint("cuTensorMapEncodeTiled", &fn, cudaEnableDefault, &qr);
        encode = (EncodeFn)fn;
        cudaGetSymbolAddress(&scr, g_scratch);
    }
    Params p;
    auto panels = [&](CUtensorMap* tm, void* ptr, int rows, int cols, int box_rows, int box_panels,
                      CUtensorMapL2promotion promo = CU_TENSOR_MAP_L2_PROMOTION_L2_256B) {
        const cuuint64_t gd[3] = {64, (cuuint64_t)rows, (cuuint64_t)(cols / 64)}, gs[2] = {(cuuint64_t)cols * 2, 128};
        const cuuint32_t box[3] = {64, (cuuint32_t)box_rows, (cuuint32_t)box_panels}, es[3] = {1, 1, 1};
        encode(tm, CU_TENSOR_MAP_DATA_TYPE_BFLOAT16, 3, ptr, gd, gs, box, es, CU_TENSOR_MAP_INTERLEAVE_NONE,
               CU_TENSOR_MAP_SWIZZLE_128B, promo, CU_TENSOR_MAP_FLOAT_OOB_FILL_NONE);
    };
    panels(&p.tm_wq, d_in[7], DM, 4096, 128, 2);
    panels(&p.tm_wuk, d_in[8], 512, 4096, 128, 2);
    panels(&p.tm_wuv, d_in[9], 512, 4096, 128, 2);
    panels(&p.tm_wo, d_in[10], 4096, DM, 32, 9);
    panels(&p.tm_ckv, d_in[6], 4 * SK, 512, 32, 8);
    panels(&p.tm_fa, d_in[4], 4096, DM, 64, 1, CU_TENSOR_MAP_L2_PROMOTION_L2_128B);
    panels(&p.tm_fb, d_in[10], 4096, DM, 64, 1, CU_TENSOR_MAP_L2_PROMOTION_L2_128B);
    {
        const cuuint64_t gd[3] = {4096, 192, 3}, gs[2] = {8192, 192 * 8192};
        const cuuint32_t box[3] = {32, 192, 3}, es[3] = {1, 1, 1};
        encode(&p.tm_j0, CU_TENSOR_MAP_DATA_TYPE_BFLOAT16, 3, d_in[3], gd, gs, box, es, CU_TENSOR_MAP_INTERLEAVE_NONE,
               CU_TENSOR_MAP_SWIZZLE_64B, CU_TENSOR_MAP_L2_PROMOTION_L2_128B, CU_TENSOR_MAP_FLOAT_OOB_FILL_NONE);
    }
    p.xa = (const __nv_bfloat16*)d_in[0];
    p.kc = (const __nv_bfloat16*)d_in[1];
    p.vc = (const __nv_bfloat16*)d_in[2];
    p.wo = (const __nv_bfloat16*)d_in[4];
    p.xb = (const __nv_bfloat16*)d_in[5];
    p.out = (__nv_bfloat16*)d_out;
    p.s = (Scratch*)scr;
    if (ncl >= MINCL) {
        cfg.gridDim = dim3(8 * ncl);
        cudaLaunchKernelEx(&cfg, fused_decode_kernel<true>, p);
    } else {
        fused_decode_kernel<false><<<nsm, 256, SMEM_BYTES, cudaStreamPerThread>>>(p);
    }
}
```

```cpp
#include <cuda_runtime.h>
#include <cuda.h>
#include <cuda_bf16.h>
#include <stdint.h>

namespace {

constexpr int NH = 32, SK = 4096, DM = 576;
constexpr int KEYS = 128;
constexpr int UPP = SK / KEYS;
constexpr int NUK = 4 * NH * UPP;
constexpr int TILE_BYTES = KEYS * 256;
#define NWORK 2
constexpr int NW = NWORK;
constexpr int NBCTA = 32;
constexpr int MINCL = 15;
constexpr int NFIN = 72;
constexpr int SLOT = 32768;
constexpr int NSLOT = 6;
constexpr int BRING = 5;
constexpr int J0W = 5 * SLOT;
constexpr int MISC = NSLOT * SLOT + 4096;
constexpr int XP = 1168, CP = 1040, QP = 272;
constexpr int M_XA = MISC;
constexpr int M_XB = M_XA + 4 * XP;
constexpr int M_CH = M_XB + 4 * XP;
constexpr int M_CL = M_CH + 4 * CP;
constexpr int M_QB = M_CL + 4 * CP;
constexpr int M_QA = M_CH;
constexpr int M_J0 = M_QB + 4 * QP;
constexpr int M_P = M_J0 + 2048;
constexpr int M_ALPHA = M_P + 2560;
constexpr int M_OMEGA = M_ALPHA + 128;
constexpr int M_BAR = M_OMEGA + 128;
constexpr int M_HELP = M_BAR + 128;
constexpr int F_W = 4 * SLOT;
constexpr int F_BF = (M_HELP + 383) / 256 * 256;
constexpr int F_RX = F_BF + 4096;
constexpr int F_BAR = F_RX + 2048;
constexpr int SMEM_BYTES = F_BAR + 192 + 1024;
static_assert(SMEM_BYTES <= 232448 && M_BAR % 8 == 0 && M_QA % 16 == 0 && M_P % 16 == 0, "smem layout");
#define XW 2
#define X3 1
#define X3C 4
#define NEARLY 2
#define LATE 2000
#define BD 5
#define FPF 3
#define FSLEEP 800
#define VS0 24
#define PFN 96
#define EARLY 100
#define ELOG 5
#define TPU 159
#define A0 (1620 + 200 * X3C)
#define AJ 390
#define B0 (A0 - 400)
#define BJ 195
#define LAG 5
#define NPOLL 2
#define PGAP 200
static_assert(X3C <= 4 && NW == 2 && MINCL == 15, "warp 2 of rank 7 is free");
static_assert(NW + XW <= 4 && NEARLY <= NW + XW && BD <= BRING, "slots 4 and 5 hold the finisher weights");
constexpr int KMIN = 2, KMAX = 4, VMIN = 0, VMAX = 4;
constexpr float SCALE = 0.08838834764831845f;
constexpr float LOG2E = 1.4426950408889634f;
constexpr unsigned SPIN_LIMIT = 1u << 24;

#define NREP 2
#define NREPC 1
constexpr int C_QUEUE = 0, C_KDONE = 1, C_BBAR = 3, C_LINES = 5;

struct Scratch {
    unsigned epoch[32];
    unsigned ctl[2][C_LINES][32];
    uint2 qll[4 * 2048];
    uint2 scores[128 * SK / 4];
    float2 stats[128 * UPP];
    float4 oacc[128 * 32];
    unsigned vdone[NREP * NH][32];
    float4 octx[128 * 32];
    unsigned cdone[NH][32];
    unsigned long long dry[16][16];
    uint4 qabs[4 * 8 * 4 * 4 * 32];
    float2 bpart[NBCTA * NH * 256];
    float2 bml[NBCTA * NH];
    uint4 outb[NBCTA * NH * 36];
};
__device__ __align__(256) Scratch g_scratch;

struct Params {
    const __nv_bfloat16 *kc, *xa, *vc, *wo, *xb;
    __nv_bfloat16* out;
    Scratch* s;
    CUtensorMap tm_j0;
    CUtensorMap tm_wq, tm_wuk, tm_ckv, tm_wuv, tm_wo;
    CUtensorMap tm_fa, tm_fb;
};

__device__ __forceinline__ Scratch* scratch(const Params& p) {
    Scratch* s = p.s;
    __builtin_assume(__isGlobal(s));
    return s;
}

__device__ __forceinline__ uint32_t smem_u32(const void* p) { return (uint32_t)__cvta_generic_to_shared(p); }
__device__ __forceinline__ void mbar_init(uint32_t bar, uint32_t cnt) {
    asm volatile("mbarrier.init.shared::cta.b64 [%0], %1;" ::"r"(bar), "r"(cnt) : "memory");
}
__device__ __forceinline__ void mbar_expect_tx(uint32_t bar, uint32_t bytes) {
    asm volatile("mbarrier.arrive.expect_tx.shared::cta.b64 _, [%0], %1;" ::"r"(bar), "r"(bytes) : "memory");
}
__device__ __forceinline__ bool mbar_try(uint32_t bar, uint32_t parity) {
    uint32_t ok;
    asm volatile("{\n.reg .pred p;\nmbarrier.try_wait.parity.shared::cta.b64 p, [%1], %2;\nselp.u32 %0, 1, 0, p;\n}\n"
                 : "=r"(ok) : "r"(bar), "r"(parity) : "memory");
    return ok;
}
__device__ __forceinline__ void mbar_wait(uint32_t bar, uint32_t parity) {
    unsigned n = 0;
    while (!mbar_try(bar, parity)) { if (++n > SPIN_LIMIT) __trap(); }
}
__device__ __forceinline__ void mbar_spin(uint32_t bar) {
    asm volatile("{\n.reg .pred p;\n.reg .u32 n;\nmov.u32 n, 0;\nSPIN:\nmbarrier.try_wait.parity.shared::cta.b64 p, [%0], 0;\n@p bra.uni DONE;\n"
                 "add.u32 n, n, 1;\nsetp.lt.u32 p, n, 0x1000000;\n@p bra.uni SPIN;\ntrap;\nDONE:\n}" ::"r"(bar) : "memory");
}
__device__ __forceinline__ void mbar_spin_cluster(uint32_t bar) {
    asm volatile("{\n.reg .pred p;\n.reg .u32 n;\nmov.u32 n, 0;\nSPIN:\nmbarrier.try_wait.parity.relaxed.cluster.shared::cta.b64 p, [%0], 0;\n"
                 "@p bra.uni DONE;\nadd.u32 n, n, 1;\nsetp.lt.u32 p, n, 0x1000000;\n@p bra.uni SPIN;\ntrap;\nDONE:\n"
                 "fence.acquire.sync_restrict::shared::cluster.cluster;\n}" ::"r"(bar) : "memory");
}
__device__ __forceinline__ void bulk_load(uint32_t dst, const void* src, uint32_t bytes, uint32_t bar, uint64_t pol) {
    asm volatile("cp.async.bulk.shared::cluster.global.mbarrier::complete_tx::bytes.L2::cache_hint [%0], [%1], %2, [%3], %4;"
                 ::"r"(dst), "l"(src), "r"(bytes), "r"(bar), "l"(pol) : "memory");
}
__device__ __forceinline__ void mbar_init_warp(uint32_t bar) {
    asm volatile("{\n.reg .pred p;\nelect.sync _|p, 0xffffffff;\n@p mbarrier.init.shared::cta.b64 [%0], 1;\n@p fence.mbarrier_init.release.cluster;\n}"
                 ::"r"(bar) : "memory");
}
__device__ __forceinline__ void tile_load_warp(uint32_t dst, const void* src, uint32_t bar, uint64_t pol) {
    asm volatile("{\n.reg .pred p;\nelect.sync _|p, 0xffffffff;\n@p mbarrier.arrive.expect_tx.shared::cta.b64 _, [%2], %4;\n"
                 "@p cp.async.bulk.shared::cluster.global.mbarrier::complete_tx::bytes.L2::cache_hint [%0], [%1], %4, [%2], %3;\n}"
                 ::"r"(dst), "l"(src), "r"(bar), "l"(pol), "n"(TILE_BYTES) : "memory");
}
__device__ __forceinline__ void tma3d_warp(uint32_t dst, const CUtensorMap* tm, int c0, int c1, int c2, uint32_t bar, uint32_t bytes, uint64_t pol) {
    asm volatile("{\n.reg .pred p;\nelect.sync _|p, 0xffffffff;\n@p mbarrier.arrive.expect_tx.shared::cta.b64 _, [%2], %7;\n"
                 "@p cp.async.bulk.tensor.3d.shared::cluster.global.mbarrier::complete_tx::bytes.L2::cache_hint [%0], [%1, {%3,%4,%5}], [%2], %6;\n}"
                 ::"r"(dst), "l"(tm), "r"(bar), "r"(c0), "r"(c1), "r"(c2), "l"(pol), "r"(bytes) : "memory");
}
__device__ __forceinline__ void tma3d(uint32_t dst, const CUtensorMap* tm, int c0, int c1, int c2, uint32_t bar, uint64_t pol) {
    asm volatile("cp.async.bulk.tensor.3d.shared::cluster.global.mbarrier::complete_tx::bytes.L2::cache_hint [%0], [%1, {%3,%4,%5}], [%2], %6;"
                 ::"r"(dst), "l"(tm), "r"(bar), "r"(c0), "r"(c1), "r"(c2), "l"(pol) : "memory");
}
__device__ __forceinline__ void l2_prefetch(const void* src, uint32_t bytes) {
    asm volatile("cp.async.bulk.prefetch.L2.global [%0], %1;" ::"l"(src), "r"(bytes) : "memory");
}
__device__ __forceinline__ void ldsm4(uint32_t (&r)[4], uint32_t addr) {
    asm volatile("ldmatrix.sync.aligned.m8n8.x4.shared.b16 {%0,%1,%2,%3}, [%4];"
                 : "=r"(r[0]), "=r"(r[1]), "=r"(r[2]), "=r"(r[3]) : "r"(addr));
}
__device__ __forceinline__ void ldsm4t(uint32_t (&r)[4], uint32_t addr) {
    asm volatile("ldmatrix.sync.aligned.m8n8.x4.trans.shared.b16 {%0,%1,%2,%3}, [%4];"
                 : "=r"(r[0]), "=r"(r[1]), "=r"(r[2]), "=r"(r[3]) : "r"(addr));
}
__device__ __forceinline__ void mma16816(float (&d)[4], const uint32_t (&a)[4], uint32_t b0, uint32_t b1) {
    asm("mma.sync.aligned.m16n8k16.row.col.f32.bf16.bf16.f32 {%0,%1,%2,%3}, {%4,%5,%6,%7}, {%8,%9}, {%0,%1,%2,%3};"
        : "+f"(d[0]), "+f"(d[1]), "+f"(d[2]), "+f"(d[3])
        : "r"(a[0]), "r"(a[1]), "r"(a[2]), "r"(a[3]), "r"(b0), "r"(b1));
}
__device__ __forceinline__ uint32_t lds32(uint32_t a) {
    uint32_t v;
    asm volatile("ld.shared.u32 %0, [%1];" : "=r"(v) : "r"(a));
    return v;
}
__device__ __forceinline__ unsigned ld_acquire(const unsigned* p) {
    unsigned v;
    asm volatile("ld.acquire.gpu.global.u32 %0, [%1];" : "=r"(v) : "l"(p) : "memory");
    return v;
}
__device__ __forceinline__ uint2 ld_relaxed8(const void* p) {
    uint2 v;
    asm volatile("ld.relaxed.gpu.global.v2.u32 {%0,%1}, [%2];" : "=r"(v.x), "=r"(v.y) : "l"(p) : "memory");
    return v;
}
__device__ __forceinline__ unsigned ld_relaxed4(const void* p) {
    unsigned v;
    asm volatile("ld.relaxed.gpu.global.u32 %0, [%1];" : "=r"(v) : "l"(p) : "memory");
    return v;
}
__device__ __forceinline__ unsigned atom_inc(unsigned* p) {
    unsigned v;
    asm volatile("atom.relaxed.gpu.global.inc.u32 %0, [%1], 0x7fffffff;" : "=r"(v) : "l"(p) : "memory");
    return v;
}
__device__ __forceinline__ unsigned long long ld_relaxed64(const void* p) {
    unsigned long long v;
    asm volatile("ld.relaxed.gpu.global.u64 %0, [%1];" : "=l"(v) : "l"(p) : "memory");
    return v;
}
__device__ __forceinline__ void st_relaxed64(void* p, unsigned long long v) {
    asm volatile("st.relaxed.gpu.global.u64 [%0], %1;" ::"l"(p), "l"(v) : "memory");
}
__device__ __forceinline__ float4 ld_relaxed16(const void* p) {
    float4 v;
    asm volatile("ld.relaxed.gpu.global.v4.f32 {%0,%1,%2,%3}, [%4];" : "=f"(v.x), "=f"(v.y), "=f"(v.z), "=f"(v.w) : "l"(p) : "memory");
    return v;
}
__device__ __forceinline__ uint32_t mapa(uint32_t a, uint32_t rank) {
    uint32_t r;
    asm("mapa.shared::cluster.u32 %0, %1, %2;" : "=r"(r) : "r"(a), "r"(rank));
    return r;
}
__device__ __forceinline__ uint32_t time_ns() { uint32_t t; asm volatile("mov.u32 %0, %globaltimer_lo;" : "=r"(t)); return t; }
__device__ __forceinline__ void fence_gpu() { asm volatile("fence.acq_rel.gpu;" ::: "memory"); }
__device__ __forceinline__ void red_add_u32(unsigned* p, unsigned v) {
    asm volatile("red.relaxed.gpu.global.add.u32 [%0], %1;" ::"l"(p), "r"(v) : "memory");
}
__device__ __forceinline__ void st_tagged2(void* p, float a, float b, unsigned tag) {
    const unsigned long long hi = (unsigned long long)tag << 32;
    asm volatile("st.relaxed.gpu.global.v2.b64 [%0], {%1,%2};" ::"l"(p), "l"(hi | __float_as_uint(a)), "l"(hi | __float_as_uint(b)) : "memory");
}
__device__ __forceinline__ ulonglong2 ld_tagged2(const void* p) {
    ulonglong2 v;
    asm volatile("ld.relaxed.gpu.global.v2.b64 {%0,%1}, [%2];" : "=l"(v.x), "=l"(v.y) : "l"(p) : "memory");
    return v;
}
__device__ __forceinline__ float4 atom_add_f4(void* p, float a, float b, float c, float d) {
    float4 r;
    asm volatile("atom.relaxed.gpu.global.add.v4.f32 {%0,%1,%2,%3}, [%4], {%5,%6,%7,%8};"
                 : "=f"(r.x), "=f"(r.y), "=f"(r.z), "=f"(r.w) : "l"(p), "f"(a), "f"(b), "f"(c), "f"(d) : "memory");
    return r;
}
__device__ __forceinline__ void red_release_cta_shared(uint32_t a, unsigned v) {
    asm volatile("red.release.cta.shared::cta.add.u32 [%0], %1;" ::"r"(a), "r"(v) : "memory");
}
__device__ __forceinline__ unsigned ld_acquire_cta_shared(uint32_t a) {
    unsigned v;
    asm volatile("ld.acquire.cta.shared::cta.u32 %0, [%1];" : "=r"(v) : "r"(a) : "memory");
    return v;
}
__device__ __forceinline__ void st_release_cta_shared(uint32_t a, unsigned v) {
    asm volatile("st.release.cta.shared::cta.u32 [%0], %1;" ::"r"(a), "r"(v) : "memory");
}
__device__ __forceinline__ void wait_count(const unsigned* p, unsigned target) {
    unsigned n = 0;
    while (ld_acquire(p) < target) { if (++n > SPIN_LIMIT) __trap(); }
}
__device__ __forceinline__ uint32_t pack_bf16(float lo, float hi) {
    uint32_t r;
    asm("cvt.rn.bf16x2.f32 %0, %1, %2;" : "=r"(r) : "f"(hi), "f"(lo));
    return r;
}
__device__ __forceinline__ float bf_lo(uint32_t v) { return __uint_as_float(v << 16); }
__device__ __forceinline__ float bf_hi(uint32_t v) { return __uint_as_float(v & 0xffff0000u); }
__device__ __forceinline__ float ex2(float x) { float y; asm("ex2.approx.ftz.f32 %0, %1;" : "=f"(y) : "f"(x)); return y; }
__device__ __forceinline__ float expsub(float a, float b) { return ex2((a - b) * LOG2E); }
__device__ __forceinline__ float warp_max(float v) {
#pragma unroll
    for (int m = 16; m; m >>= 1) v = fmaxf(v, __shfl_xor_sync(~0u, v, m));
    return v;
}
__device__ __forceinline__ float warp_sum(float v) {
#pragma unroll
    for (int m = 16; m; m >>= 1) v += __shfl_xor_sync(~0u, v, m);
    return v;
}
template <bool CLU>
__device__ __forceinline__ unsigned unit_block(int u) {
    const unsigned x = ((unsigned)u & (NUK - 1)) / UPP;
    const int lg = u < NUK ? min(KMAX, max(KMIN, 29 - __clz(x | 1))) : (CLU && (int)x >= 4 * VS0 ? 0 : min(VMAX, max(VMIN, 29 - __clz((127 - x) | 1))));
    const unsigned r = x & ((4u << lg) - 1);
    return ((x - r + (r & ((1u << lg) - 1)) * 4 + (r >> lg)) * UPP) | ((unsigned)u & (UPP - 1));
}
__device__ __forceinline__ const char* block_src(const void* base, unsigned blk) {
    const unsigned po = blk / UPP;
    return reinterpret_cast<const char*>(base) + (size_t)(((po & 3) * NH + (po >> 2)) * UPP + blk % UPP) * TILE_BYTES;
}

template <bool CLU>
__device__ __forceinline__ void a_worker(const Params& p, int un, bool once, bool pre, bool hold, int nstatic, uint32_t slot, uint32_t bar,
                                         uint32_t help, unsigned epoch, uint64_t pol) {
    constexpr int NU = 2 * NUK, NR = CLU ? NREPC : NREP;
    const int lane = threadIdx.x & 31, g = lane >> 2, t = lane & 3;
    const int li = lane & 7;
    uint32_t kaddr[4], vaddr[8];
    {
        const int e = (lane >> 3) & 1, kk = lane >> 4;
#pragma unroll
        for (int s = 0; s < 4; s++) kaddr[s] = slot + (16 * li + e) * 256 + ((2 * s + kk + li) & 7) * 16;
        const int vrow = 4 * (li >> 1) + (li & 1) + 2 * kk;
#pragma unroll
        for (int c = 0; c < 8; c++) vaddr[c] = slot + vrow * 256 + e * 128 + ((c + li) & 7) * 16;
#pragma unroll
        for (int c = 0; c < 8; c++) asm volatile("" : "+r"(vaddr[c]));
    }
    const uint32_t vmask = (g >> 1) != t ? 0u : ((g & 1) ? 0xffff0000u : 0xffffu);
    int kseen = -1;
    unsigned long long H0 = 0, H1 = 0;
    auto header = [&](int v, unsigned vb) {
        const void *a0, *a1;
        if (v < NUK) {
            const unsigned po = vb / UPP;
            a0 = scratch(p)->qll + (po & 3) * 2048 + (po >> 2) * 64 + lane;
            a1 = reinterpret_cast<const uint2*>(a0) + 32;
        } else {
            const int half = vb / (NUK / 2);
            if (half > kseen) {
                unsigned n = 0;
                while (ld_acquire_cta_shared(help + 12 + 4 * half) == 0) { if (++n > (SPIN_LIMIT << 4)) __trap(); }
                kseen = half;
            }
            a0 = &scratch(p)->scores[vb * (KEYS / 4) + lane];
            a1 = &scratch(p)->stats[(vb / UPP) * UPP + lane];
        }
        H0 = ld_relaxed64(a0);
        H1 = ld_relaxed64(a1);
    };
    unsigned bu = 0, bn = unit_block<CLU>(un);
    asm volatile("bar.sync 2, %0;" ::"n"(32 * (NW + XW + 1)) : "memory");
    if (!pre && !hold) { const uint32_t t0 = clock(); while ((uint32_t)clock() - t0 < ((threadIdx.x >> 5) - NEARLY + 1) * LATE) {} }
    epoch = __shfl_sync(~0u, epoch, 0);
    if (hold) { unsigned n = 0; while (ld_acquire_cta_shared(help + 24) < 2) { if (++n > (SPIN_LIMIT << 4)) __trap(); } }
    unsigned (*ctl)[32] = scratch(p)->ctl[epoch & 1];
    const unsigned tag = epoch + 1;
    unsigned nxt = once ? NU : 0;
    int u = -1;
    uint32_t phase = 0;
    unsigned kpend = 0;
    const unsigned zero = gridDim.x >> 24;
    uint32_t Q[16];
    float4 oret = make_float4(0.f, 0.f, 0.f, 0.f);
    while (true) {
        const char* nsrc = block_src(un < NUK ? p.kc : p.vc, bn);
        float4* odst = &scratch(p)->oacc[(bu / UPP) * 32 + lane];
        unsigned* vdst = &scratch(p)->vdone[(lane & (NR - 1)) * NH + bu / (4 * UPP)][0];
        float d[8][4];
        uint32_t act = un >= NU ? 0u : (u >= 0 || !pre ? 1u : 0u) | (!once && lane == 0 ? 2u : 0u);
        asm volatile("" : "+l"(odst), "+l"(nsrc), "+r"(act));
        if (u >= NUK) {
#pragma unroll
            for (int j = 0; j < 8; j++) { d[j][0] = d[j][1] = d[j][2] = d[j][3] = 0.f; }
            mbar_wait(bar, phase);
            uint32_t a[2][8][4];
#pragma unroll
            for (int c = 0; c < 8; c++) ldsm4t(a[0][c], vaddr[c]);
#pragma unroll
            for (int j = 0; j < 8; j++) {
                if (j < 7) {
#pragma unroll
                    for (int c = 0; c < 8; c++) ldsm4t(a[(j + 1) & 1][c], vaddr[c] + (j + 1) * 4096);
                }
#pragma unroll
                for (int c = 0; c < 8; c++) mma16816(d[c], a[j & 1][c], Q[2 * j], Q[2 * j + 1]);
            }
            float o[4];
#pragma unroll
            for (int r = 0; r < 2; r++) {
                o[2 * r] = d[0][2 * r] + d[7][2 * r + 1];
                o[2 * r + 1] = d[0][2 * r + 1] + d[1][2 * r];
#pragma unroll
                for (int k = 1; k < 4; k++) {
                    const int src = (lane & 28) | ((t - k) & 3);
                    o[2 * r] += __shfl_sync(~0u, d[2 * k][2 * r] + d[2 * k - 1][2 * r + 1], src);
                    o[2 * r + 1] += __shfl_sync(~0u, d[2 * k][2 * r + 1] + d[2 * k + 1][2 * r], src);
                }
            }
            oret = atom_add_f4(odst, o[0], o[1], o[2], o[3]);
        } else if (u >= 0) {
#pragma unroll
            for (int j = 0; j < 8; j++) { d[j][0] = d[j][1] = d[j][2] = d[j][3] = 0.f; }
            mbar_wait(bar, phase);
            uint32_t a[2][8][4];
#pragma unroll
            for (int j = 0; j < 8; j++) ldsm4(a[0][j], kaddr[0] + (4 * (j & 3) + 2 * (j >> 2)) * 256);
#pragma unroll
            for (int s = 0; s < 8; s++) {
                if (s < 7) {
#pragma unroll
                    for (int j = 0; j < 8; j++)
                        ldsm4(a[(s + 1) & 1][j], kaddr[(s + 1) & 3] + (4 * (j & 3) + 2 * (j >> 2)) * 256 + ((s + 1) >> 2) * 128);
                }
#pragma unroll
                for (int j = 0; j < 8; j++)
                    mma16816(d[j], a[s & 1][j], Q[(s & 4) * 2 + ((2 * s - 2 * j) & 7)], Q[(s & 4) * 2 + ((2 * s + 1 - 2 * j) & 7)]);
            }
        }
        if (u >= 0) phase ^= 1;
        asm volatile("{\n.reg .pred p, q;\n.reg .u32 a;\nelect.sync _|p, 0xffffffff;\nand.b32 a, %5, 1;\nsetp.ne.and.u32 q, a, 0, p;\n"
                     "@q mbarrier.arrive.expect_tx.shared::cta.b64 _, [%2], %4;\n"
                     "@q cp.async.bulk.shared::cluster.global.mbarrier::complete_tx::bytes.L2::cache_hint [%0], [%1], %4, [%2], %3;\n}"
                     ::"r"(slot), "l"(nsrc), "r"(bar), "l"(pol), "n"(TILE_BYTES), "r"(act) : "memory");
        if (act & 2) nxt = atom_inc(&ctl[C_QUEUE][0]);
        const uint32_t tk = clock();
        if ((unsigned)u < (unsigned)NUK) {
            const int j0 = (t - (g >> 1)) & 3;
            float v[4];
#pragma unroll
            for (int q = 0; q < 4; q++) {
                const int jq = (q >> 1) * 4, e = (q & 1) * 2;
                const float x0 = (g & 1) ? d[jq + 0][e + 1] : d[jq + 0][e];
                const float x1 = (g & 1) ? d[jq + 1][e + 1] : d[jq + 1][e];
                const float x2 = (g & 1) ? d[jq + 2][e + 1] : d[jq + 2][e];
                const float x3 = (g & 1) ? d[jq + 3][e + 1] : d[jq + 3][e];
                const float y0 = (j0 & 1) ? x1 : x0, y1 = (j0 & 1) ? x3 : x2;
                v[q] = (j0 & 2) ? y1 : y0;
            }
            const uint32_t r0 = pack_bf16(v[0], v[1]), r1 = pack_bf16(v[2], v[3]);
            const uint32_t s0 = pack_bf16(bf_lo(r0) * SCALE, bf_hi(r0) * SCALE);
            const uint32_t s1 = pack_bf16(bf_lo(r1) * SCALE, bf_hi(r1) * SCALE);
            scratch(p)->scores[bu * (KEYS / 4) + 4 * g + j0] = make_uint2(s0, s1);
            const float f0 = bf_lo(s0), f1 = bf_hi(s0), f2 = bf_lo(s1), f3 = bf_hi(s1);
            const float m = warp_max(fmaxf(fmaxf(f0, f1), fmaxf(f2, f3)));
            const float l = warp_sum((expsub(f0, m) + expsub(f1, m)) + (expsub(f2, m) + expsub(f3, m)));
            if (lane == 0) scratch(p)->stats[bu] = make_float2(m, l);
            kpend++;
            if (un / (NUK / 2) != u / (NUK / 2)) {
                __syncwarp();
                if (lane == 0) {
                    red_release_cta_shared(help + 4 * (u / (NUK / 2)), kpend);
                    if (un >= NUK) red_release_cta_shared(help + 8, 1u);
                }
                kpend = 0;
            }
        }
        int unn = NU;
        if (un < NU) {
            unsigned n = 0;
            while (true) {
                header(un, bn);
                if (un >= NUK || __all_sync(~0u, (uint32_t)(H0 >> 32) == tag && (uint32_t)(H1 >> 32) == tag)) break;
                if (++n > SPIN_LIMIT) __trap();
            }
            if (un >= NUK) {
                const uint32_t s0 = (uint32_t)H0, s1 = (uint32_t)(H0 >> 32);
                const float mu = __uint_as_float((uint32_t)H1);
                const float m = warp_max(mu);
                const float l = warp_sum(__uint_as_float((uint32_t)(H1 >> 32)) * expsub(mu, m));
                const float inv = 1.0f / l;
                const uint32_t w0 = pack_bf16(expsub(bf_lo(s0), m) * inv, expsub(bf_hi(s0), m) * inv);
                const uint32_t w1 = pack_bf16(expsub(bf_lo(s1), m) * inv, expsub(bf_hi(s1), m) * inv);
#pragma unroll
                for (int j = 0; j < 8; j++) {
                    Q[2 * j] = __shfl_sync(~0u, w0, 4 * j + t) & vmask;
                    Q[2 * j + 1] = __shfl_sync(~0u, w1, 4 * j + t) & vmask;
                }
            } else {
#pragma unroll
                for (int j = 0; j < 8; j++) {
                    const int src = (((j + g) & 7) << 2) + t;
                    Q[j] = __shfl_sync(~0u, (uint32_t)H0, src);
                    Q[8 + j] = __shfl_sync(~0u, (uint32_t)H1, src);
                }
            }
            unn = nstatic + (int)__shfl_sync(~0u, nxt, 0);
            if (CLU && ((NU - EARLY - unn) & ~(7 << ELOG)) == 0 && lane < MINCL)
                st_relaxed64(&scratch(p)->dry[lane][(NU - EARLY - unn) >> ELOG],
                             (time_ns() - (((uint32_t)clock() - tk) >> 1) + (NU - unn) * TPU / 16) | (unsigned long long)tag << 32);
        }
        if (u >= NUK && lane < NR)
            red_add_u32(vdst,
                        1u + ((__float_as_uint(oret.x) | __float_as_uint(oret.y) | __float_as_uint(oret.z) | __float_as_uint(oret.w)) & zero));
        if (un >= NU) break;
        bu = bn;
        bn = unit_block<CLU>(unn);
        u = un;
        un = unn;
    }
}

__device__ __forceinline__ void k_helper(const Params& p, uint32_t help, unsigned epoch) {
    if ((threadIdx.x & 31) != 0) return;
    unsigned (*ctl)[32] = scratch(p)->ctl[epoch & 1];
    unsigned sent0 = 0, sent1 = 0, n = 0;
    int seen = 0;
    bool fin = false;
    while (!fin || seen < 2) {
        if (!fin) {
            fin = ld_acquire_cta_shared(help + 8) == NW + XW;
            const unsigned c0 = ld_acquire_cta_shared(help), c1 = ld_acquire_cta_shared(help + 4);
            if (c0 != sent0 || c1 != sent1) {
                fence_gpu();
                if (c0 != sent0) red_add_u32(&ctl[C_KDONE][0], c0 - sent0);
                if (c1 != sent1) red_add_u32(&ctl[C_KDONE + 1][0], c1 - sent1);
                sent0 = c0; sent1 = c1;
            }
        }
        if (seen < 2 && ld_acquire(&ctl[C_KDONE + seen][0]) >= NUK / 2) {
            st_release_cta_shared(help + 12 + 4 * seen, 1u);
            seen++;
        } else {
            __nanosleep(300);
        }
        if (++n > SPIN_LIMIT) __trap();
    }
}

__device__ __forceinline__ void v_poller(const Params& p, uint32_t sbase, int f, int w) {
    constexpr int HL = NH;
    const int lane = threadIdx.x & 31;
    const unsigned (*cp)[32] = &scratch(p)->vdone[((f * NPOLL + w) % NREP) * NH];
    unsigned n = 0;
    while (ld_acquire_cta_shared(sbase + M_HELP + 12) == 0) { __nanosleep(1000); if (++n > SPIN_LIMIT) __trap(); }
    int h = 0;
    bool fast = false;
    while (h < HL) {
        const unsigned r = __ballot_sync(~0u, ld_acquire(&cp[min(h + (lane & 3), HL - 1)][0]) >= 4 * UPP) & 15u;
        if (r & 1) {
            h = min(HL, h + __ffs(~r) - 1);
            __syncwarp();
            if (lane == 0) asm volatile("red.release.cta.shared::cta.max.u32 [%0], %1;" ::"r"(sbase + M_HELP + 20), "r"(h) : "memory");
        }
        if (h < HL - 4) {
            __nanosleep(h ? 300 : 1000);
        } else if (!fast) {
            fast = true;
            const long long t0 = clock64();
            while (clock64() - t0 < w * PGAP) {}
        }
        if (++n > SPIN_LIMIT) __trap();
    }
}
__device__ __forceinline__ void finisher(const Params& p, uint32_t sbase, int f) {
    constexpr int HL = NH;
    const int lane = threadIdx.x & 31;
    {
        const char* wg = reinterpret_cast<const char*>(p.wo);
        const uint32_t dst = sbase + 4 * SLOT + (16 * (lane & 7) + (lane >> 3)) * 16;
#pragma unroll 1
        for (int h = -FPF - 4; h < HL; h++) {
            if (lane == 0 && (unsigned)(h + FPF) < (unsigned)HL) l2_prefetch(wg + (size_t)(h + FPF) * 147456 + f * 2048, 2048);
            if (h >= 0) {
#pragma unroll
                for (int r = 0; r < 4; r++)
                    asm volatile("cp.async.cg.shared.global [%0], [%1], 16;" ::"r"(dst + h * 2048 + ((r & 1) * 4 + (r >> 1) * 8) * 16),
                                 "l"(wg + (size_t)(h * 128 + r * 32 + lane) * (DM * 2) + f * 16) : "memory");
            }
            __nanosleep(FSLEEP);
        }
        asm volatile("cp.async.wait_all;" ::: "memory");
        __syncwarp();
    }
    const float4* vec = scratch(p)->oacc + ((lane >> 2) & 3) * 32 + (lane >> 4) * 16 + (lane & 3);
    float acc[2][2][4];
#pragma unroll
    for (int i = 0; i < 16; i++) acc[i >> 3][(i >> 2) & 1][i & 3] = 0.f;
    uint32_t* outp = reinterpret_cast<uint32_t*>(p.out + (lane >> 2) * (2 * DM) + f * 8 + (lane & 3) * 2);
    uint32_t wa = sbase + 4 * SLOT + lane * 16;
    auto project = [&](const float4 (&x)[4], const uint32_t (&w)[4][4]) {
#pragma unroll
        for (int s = 0; s < 4; s++) {
            const uint32_t a[4] = {pack_bf16(x[s].x, x[s].y), 0u, pack_bf16(x[s].z, x[s].w), 0u};
            mma16816(acc[0][s & 1], a, w[s >> 1][(s & 1) * 2], w[s >> 1][(s & 1) * 2 + 1]);
            mma16816(acc[1][s & 1], a, w[2 + (s >> 1)][(s & 1) * 2], w[2 + (s >> 1)][(s & 1) * 2 + 1]);
        }
    };
    int h = 0;
    unsigned n = 0;
    while (h < HL) {
        uint32_t w[4][4];
#pragma unroll
        for (int q = 0; q < 4; q++) ldsm4t(w[q], wa + q * 512);
        int ready;
        while ((ready = ld_acquire_cta_shared(sbase + M_HELP + 20)) <= h) {
            if (h < HL - 3) __nanosleep(100);
            if (++n > (SPIN_LIMIT << 4)) __trap();
        }
        float4 x[4], y[4];
#pragma unroll
        for (int s = 0; s < 4; s++) x[s] = ld_relaxed16(vec + s * 4);
        const bool two = ready > h + 1;
        if (two) {
#pragma unroll
            for (int s = 0; s < 4; s++) y[s] = ld_relaxed16(vec + 128 + s * 4);
        }
        project(x, w);
        if (two) {
#pragma unroll
            for (int q = 0; q < 4; q++) ldsm4t(w[q], wa + 2048 + q * 512);
            project(y, w);
        }
        const int nr = two ? 2 : 1;
        h += nr;
        vec += nr * 128;
        wa += nr * 2048;
        const float o0 = acc[0][0][0] + acc[0][1][0] + __shfl_down_sync(~0u, acc[1][0][0] + acc[1][1][0], 16);
        const float o1 = acc[0][0][1] + acc[0][1][1] + __shfl_down_sync(~0u, acc[1][0][1] + acc[1][1][1], 16);
        asm volatile("{\n.reg .pred p;\nsetp.ne.u32 p, %2, 0;\n@p st.global.u32 [%0], %1;\n}" ::"l"(outp), "r"(pack_bf16(o0, o1)),
                     "r"((uint32_t)(lane < 16 && h == NH)) : "memory");
    }
}

__device__ __noinline__ void f_collect(const unsigned (*flag)[32], unsigned full, const float4* src, unsigned todo, uint32_t sbase) {
    const int lane = threadIdx.x & 31, g = lane >> 2, t = lane & 3;
    const bool last = todo != 15;
    unsigned n = 0;
    while (todo) {
        const unsigned v = ld_acquire(&flag[t][0]);
        unsigned m = __ballot_sync(~0u, v == full) & todo;
        if (m == 0) {
            if (!last || __shfl_sync(~0u, v, 0) == 0) __nanosleep(200);
            if (++n > SPIN_LIMIT) __trap();
            continue;
        }
        __syncwarp();
        todo ^= m;
        do {
            const int h0 = __ffs(m) - 1, h1 = 31 - __clz(m);
            m &= ~((1u << h0) | (1u << h1));
            float4 x[8];
#pragma unroll
            for (int b = 0; b < 8; b++) x[b] = ld_relaxed16(src + ((b & 4) ? h1 : h0) * 128 + (b & 3) * 32 + lane);
#pragma unroll
            for (int b = 0; b < 8; b++) {
                const uint32_t lo = pack_bf16(x[b].x, x[b].y), hi = pack_bf16(x[b].z, x[b].w);
                const uint32_t o = __shfl_xor_sync(~0u, (g & 1) ? lo : hi, 4);
                const uint32_t e0 = (g & 1) ? o : lo, e1 = (g & 1) ? hi : o;
                asm volatile("st.shared.v2.u32 [%0], {%1,%2};"
                             ::"r"(sbase + F_BF + ((b & 4) ? h1 : h0) * 1024 + t * 256 + ((b ^ t) & 3) * 64 + g * 8),
                               "r"(__byte_perm(e0, e1, 0x5410)), "r"(__byte_perm(e0, e1, 0x7632)) : "memory");
            }
            __syncwarp();
            if (lane < (h0 == h1 ? 1 : 2))
                asm volatile("mbarrier.arrive.shared::cta.b64 _, [%0];" ::"r"(sbase + F_BAR + 32 + (lane ? h1 : h0) * 8) : "memory");
        } while (m);
    }
}

__device__ __forceinline__ void f_request(const Params& p, const CUtensorMap* tm, int panel, int rank, int nsl, int delay, int step, unsigned tag,
                                          uint32_t sbase, uint64_t pol) {
    const int lane = threadIdx.x & 31;
    if (lane == 0) asm volatile("prefetch.tensormap [%0];" ::"l"(tm) : "memory");
    unsigned long long v;
    unsigned n = 0;
    while (!__all_sync(~0u, (v = ld_relaxed64(&scratch(p)->dry[blockIdx.x >> 3][lane >> 2])) >> 32 == tag)) {
        __nanosleep(200);
        if (++n > SPIN_LIMIT) __trap();
    }
    const uint32_t t0 = __shfl_sync(~0u, (uint32_t)v, 0);
    uint32_t due = t0 + (__reduce_add_sync(~0u, (int)((uint32_t)v - t0)) >> 5);
    due += delay;
#pragma unroll 1
    for (int q = 0; q < 8 * nsl; q++, due += step) {
        if (q >= LAG * nsl) mbar_spin(sbase + F_BAR + 64 + (q - LAG * nsl) * 8);
        while ((int)(time_ns() - due) < 0 && ++n < SPIN_LIMIT) {}
        tma3d_warp(sbase + F_W - (q >> 3) * 2 * SLOT + (q & 7) * 8192, tm, 0, (rank * 8 + (q & 7)) * 64, panel + (q >> 3), sbase + F_BAR + 64 + q * 8,
                   8192, pol);
    }
}

__device__ __forceinline__ void f_project(const Params& p, int rank, int j, int nsl, uint32_t sbase) {
    const int lane = threadIdx.x & 31, g = lane >> 2, t = lane & 3;
    const uint32_t wa = sbase + F_W + ((lane & 7) + (lane >> 4) * 8) * 128 + (((2 * j + ((lane >> 3) & 1)) ^ (lane & 7)) * 16);
    const uint32_t ba = sbase + F_BF + (g & 3) * 64 + t * 16;
    const bool up = t & 2;
#pragma unroll 1
    for (int sl = 0; sl < nsl; sl++) {
        const uint32_t rdst = mapa(sbase + F_RX + sl * 1024 + rank * 128 + g * 16 + (t & 1) * 8, 2 * j + (t >> 1));
        const uint32_t rbar = mapa(sbase + F_BAR + 16 + sl * 8, 2 * j + (t >> 1));
        float acc[2][4];
#pragma unroll
        for (int k = 0; k < 8; k++) acc[k >> 2][k & 3] = 0.f;
#pragma unroll 1
        for (int h = 0; h < 4; h++) {
            uint32_t wp = wa + h * 16384 - sl * 2 * SLOT, last = h == 3;
            mbar_spin(sbase + F_BAR + 32 + h * 8);
            uint32_t a[8][4], bf[4][4];
#pragma unroll
            for (int s = 0; s < 4; s++)
                asm volatile("ld.shared.v4.u32 {%0,%1,%2,%3}, [%4];" : "=r"(bf[s][0]), "=r"(bf[s][1]), "=r"(bf[s][2]), "=r"(bf[s][3])
                             : "r"(((ba + h * 1024) ^ (s * 64)) + s * 256) : "memory");
            asm volatile("" : "+r"(wp), "+r"(last));
#pragma unroll
            for (int q = 0; q < 2; q++) {
                mbar_spin(sbase + F_BAR + 64 + sl * 64 + h * 16 + q * 8);
#pragma unroll
                for (int s = 4 * q; s < 4 * q + 4; s++) ldsm4t(a[s], wp + s * 2048);
            }
#pragma unroll
            for (int s = 0; s < 8; s++) mma16816(acc[s & 1], a[s], bf[s & 3][(s >> 2) * 2], bf[s & 3][(s >> 2) * 2 + 1]);
            const float v0 = up ? acc[0][2] + acc[1][2] : acc[0][0] + acc[1][0], v1 = up ? acc[0][3] + acc[1][3] : acc[0][1] + acc[1][1];
            asm volatile("{\n.reg .pred p;\nsetp.ne.u32 p, %4, 0;\n"
                         "@p st.async.weak.shared::cluster.mbarrier::complete_tx::bytes.v2.b32 [%0], {%1,%2}, [%3];\n}"
                         ::"r"(rdst), "r"(__float_as_uint(v0)), "r"(__float_as_uint(v1)), "r"(rbar), "r"(last) : "memory");
        }
    }
}

__device__ __forceinline__ void f_receive(const Params& p, __nv_bfloat16* out, int nsl, uint32_t sbase) {
    const int lane = threadIdx.x & 31;
    out += (lane & 3) * (2 * DM) + (lane >> 2);
#pragma unroll 1
    for (int sl = -1; sl < nsl; sl++) {
        __nv_bfloat16* dst = out + sl * 64;
        uint32_t src = sbase + F_RX + sl * 1024 + lane * 4;
        asm volatile("" : "+l"(dst), "+r"(src));
        if (sl >= 0) mbar_spin_cluster(sbase + F_BAR + 16 + sl * 8);
        float v[8];
#pragma unroll
        for (int r = 0; r < 8; r++) asm volatile("ld.shared.f32 %0, [%1];" : "=f"(v[r]) : "r"(src + r * 128) : "memory");
        const float o = ((v[0] + v[1]) + (v[2] + v[3])) + ((v[4] + v[5]) + (v[6] + v[7]));
        asm volatile("{\n.reg .pred p;\nsetp.ge.s32 p, %2, 0;\n@p st.global.u16 [%0], %1;\n}"
                     ::"l"(dst), "h"((unsigned short)pack_bf16(o, 0.f)), "r"(sl) : "memory");
    }
}

constexpr int BS_WUK = 5, BS_Q = 9, BS_CKV = 11, BS_PART = 27, BS_WUV = 29, BS_END = 33;

__device__ __noinline__ void b_issue(const Params& p, int n, int bi, uint32_t sbase, uint64_t pol) {
    if (n >= BS_END || (n >= BS_Q && n < BS_CKV) || (n >= BS_PART && n < BS_WUV)) return;
    const uint32_t bar = sbase + M_BAR + (NSLOT + n % BRING) * 8;
    const CUtensorMap* tm;
    int row, panel = 2 * bi;
    if (n < BS_WUK) { tm = &p.tm_wq; row = n * 128; }
    else if (n < BS_Q) { tm = &p.tm_wuk; row = (n - BS_WUK) * 128; }
    else if (n < BS_PART) {
        tm = &p.tm_ckv; panel = 0;
        row = (bi >> 3) * SK + ((n - BS_CKV) * 8 + (bi & 7)) * 32;
    }
    else { tm = &p.tm_wuv; row = (n - BS_WUV) * 128; }
    mbar_expect_tx(bar, n == 0 ? 32768 + 4 * 1152 : 32768);
    tma3d(sbase + (n % BRING) * SLOT, tm, 0, row, panel, bar, pol);
}
__device__ __forceinline__ void b_issue_xchg(int n, const void* src, uint32_t sbase, uint64_t pol) {
    asm volatile("fence.proxy.async;" ::: "memory");
#pragma unroll
    for (int i = 0; i < 2; i++) {
        const uint32_t bar = sbase + M_BAR + (NSLOT + (n + i) % BRING) * 8;
        mbar_expect_tx(bar, 32768);
        bulk_load(sbase + ((n + i) % BRING) * SLOT, reinterpret_cast<const char*>(src) + i * 32768, 32768, bar, pol);
    }
}
__device__ __forceinline__ void b_wait(int n, uint32_t sbase) {
    mbar_wait(sbase + M_BAR + (NSLOT + n % BRING) * 8, (n / BRING) & 1);
}

__device__ __noinline__ void b_gemm(const Params& p, uint32_t sbase, int n0, int n1, int ktot, uint32_t xh, uint32_t xl, int pitch,
                                    int bi, uint64_t pol) {
    const int tid = threadIdx.x, warp = tid >> 5, lane = tid & 31, g = lane >> 2, t = lane & 3;
    const uint32_t woff = (warp >> 2) * 16384 + (lane & 15) * 128 + ((((warp & 3) * 2 + (lane >> 4)) ^ (lane & 7)) * 16);
    const uint32_t xoff = (g & 3) * pitch + t * 4;
    float acc[2][4];
#pragma unroll
    for (int i = 0; i < 8; i++) acc[i >> 2][i & 3] = 0.f;
#pragma unroll 1
    for (int n = n0; n < n1; n++) {
        b_wait(n, sbase);
        const uint32_t slot = sbase + (n % BRING) * SLOT + woff;
        const int k0 = (n - n0) * 128;
        const int ns = min(8, (ktot - k0) >> 4);
#pragma unroll 2
        for (int s = 0; s < ns; s++) {
            uint32_t a[4], w[4];
            const uint32_t xo = xoff + (k0 + 16 * s) * 2;
            a[0] = lds32(xh + xo); a[2] = lds32(xh + xo + 16);
            a[1] = xl ? lds32(xl + xo) : 0u; a[3] = xl ? lds32(xl + xo + 16) : 0u;
            ldsm4t(w, slot + s * 2048);
            mma16816(acc[0], a, w[0], w[1]);
            mma16816(acc[1], a, w[2], w[3]);
        }
        __syncthreads();
        if (tid == 0) b_issue(p, n + BD, bi, sbase, pol);
    }
    if (g < 4) {
#pragma unroll
        for (int j = 0; j < 2; j++)
            asm volatile("st.shared.u32 [%0], %1;" ::"r"(sbase + M_QB + g * QP + (warp * 16 + j * 8 + t * 2) * 2),
                         "r"(pack_bf16(acc[j][0] + acc[j][2], acc[j][1] + acc[j][3])) : "memory");
    }
    __syncthreads();
}

__device__ __forceinline__ void b_exchange(unsigned* c, int n, const void* src, uint32_t sbase, uint64_t pol) {
    __syncthreads();
    if (threadIdx.x == 0) {
        fence_gpu();
        red_add_u32(c, 1u);
        wait_count(c, NBCTA);
        b_issue_xchg(n, src, sbase, pol);
    }
}

template <bool CLU>
__device__ __noinline__ void b_chain(const Params& p, char* smem, uint32_t sbase, int bi, unsigned epoch, uint64_t pol) {
    const int tid = threadIdx.x, warp = tid >> 5, lane = tid & 31, g = lane >> 2, t = lane & 3;
    unsigned (*ctl)[32] = scratch(p)->ctl[epoch & 1];
    float* red = reinterpret_cast<float*>(smem + 5 * SLOT);
    __syncthreads();
    b_gemm(p, sbase, 0, BS_WUK, DM, sbase + M_XB, 0, XP, bi, pol);
    {
        uint32_t Q[16];
#pragma unroll
        for (int c = 0; c < 16; c++) Q[c] = lds32(sbase + M_QB + (g & 3) * QP + c * 16 + t * 4);
        float* qa = reinterpret_cast<float*>(smem + M_QA);
#pragma unroll 1
        for (int n = BS_WUK; n < BS_Q; n++) {
            b_wait(n, sbase);
            const uint32_t base = sbase + (n % BRING) * SLOT + (warp * 16 + (lane & 15)) * 128;
            float d[2][4];
#pragma unroll
            for (int i = 0; i < 8; i++) d[i >> 2][i & 3] = 0.f;
#pragma unroll
            for (int s = 0; s < 8; s++) {
                uint32_t a[4];
                ldsm4(a, base + (s >> 2) * 16384 + (((2 * (s & 3) + (lane >> 4)) ^ (lane & 7)) * 16));
                mma16816(d[s & 1], a, Q[2 * s], Q[2 * s + 1]);
            }
            const int c = (n - BS_WUK) * 128 + warp * 16 + g + 8 * (t >> 1);
            qa[(2 * (t & 1)) * 512 + c] = (t & 2) ? d[0][2] + d[1][2] : d[0][0] + d[1][0];
            qa[(2 * (t & 1) + 1) * 512 + c] = (t & 2) ? d[0][3] + d[1][3] : d[0][1] + d[1][1];
            __syncthreads();
            if (tid == 0) b_issue(p, n + BD, bi, sbase, pol);
        }
#pragma unroll 1
        for (int r = 0; r < 2; r++) {
            const int id = tid + r * 256;
            const int b = id >> 7, c0 = ((id >> 2) & 31) * 16 + (id & 3) * 2;
            const float2 u0 = *reinterpret_cast<const float2*>(qa + b * 512 + c0);
            const float2 u1 = *reinterpret_cast<const float2*>(qa + b * 512 + c0 + 8);
            const uint32_t h0 = pack_bf16(u0.x, u0.y), h1 = pack_bf16(u1.x, u1.y);
            const uint32_t l0 = pack_bf16(u0.x - bf_lo(h0), u0.y - bf_hi(h0)), l1 = pack_bf16(u1.x - bf_lo(h1), u1.y - bf_hi(h1));
            scratch(p)->qabs[((id >> 2) * 4 + (bi >> 3)) * 32 + (bi & 7) * 4 + (id & 3)] = make_uint4(h0, l0, h1, l1);
        }
    }
    b_exchange(&ctl[C_BBAR][0], BS_Q, &scratch(p)->qabs[(bi >> 3) * 4096], sbase, pol);
    {
        uint32_t qf[4][4][4];
        b_wait(BS_Q + (warp >> 2), sbase);
        {
            const uint4* qs = reinterpret_cast<const uint4*>(smem + ((BS_Q + (warp >> 2)) % BRING) * SLOT) + (warp & 3) * 512 + lane;
#pragma unroll
            for (int s = 0; s < 4; s++)
#pragma unroll
                for (int i = 0; i < 4; i++) {
                    const uint4 v = qs[(s * 4 + i) * 32];
                    qf[i][s][0] = v.x; qf[i][s][1] = v.y; qf[i][s][2] = v.z; qf[i][s][3] = v.w;
                }
        }
        __syncthreads();
        if (tid == 0) { b_issue(p, BS_Q + BD, bi, sbase, pol); b_issue(p, BS_Q + 1 + BD, bi, sbase, pol); }
        float acc[2][8][4];
#pragma unroll
        for (int i = 0; i < 2; i++)
#pragma unroll
            for (int j = 0; j < 8; j++) { acc[i][j][0] = acc[i][j][1] = acc[i][j][2] = acc[i][j][3] = 0.f; }
        float mrun = -INFINITY, lrun = 0.f;
        const int head = tid >> 3, kq = tid & 7;
        float* alpha = reinterpret_cast<float*>(smem + M_ALPHA);
        for (int n = BS_CKV; n < BS_PART; n++) {
            b_wait(n, sbase);
            const uint32_t slot = sbase + (n % BRING) * SLOT;
            float sc[4][4][4];
#pragma unroll
            for (int i = 0; i < 4; i++)
#pragma unroll
                for (int j = 0; j < 4; j++) { sc[i][j][0] = sc[i][j][1] = sc[i][j][2] = sc[i][j][3] = 0.f; }
#pragma unroll
            for (int j = 0; j < 4; j++)
#pragma unroll
                for (int sp = 0; sp < 2; sp++) {
                    uint32_t bf[4];
                    ldsm4(bf, slot + warp * 4096 + (8 * j + (lane & 7)) * 128 + (((4 * sp + (lane >> 3)) ^ (lane & 7)) * 16));
#pragma unroll
                    for (int i = 0; i < 4; i++) {
                        mma16816(sc[i][j], qf[i][2 * sp], bf[0], bf[1]);
                        mma16816(sc[i][j], qf[i][2 * sp + 1], bf[2], bf[3]);
                    }
                }
#pragma unroll
            for (int i = 0; i < 4; i++)
#pragma unroll
                for (int j = 0; j < 4; j++)
                    *reinterpret_cast<float2*>(red + warp * 1024 + (8 * i + g) * 32 + ((8 * j) ^ (8 * (g & 3))) + 2 * t) =
                        make_float2(sc[i][j][0] + sc[i][j][2], sc[i][j][1] + sc[i][j][3]);
            __syncthreads();
            if (tid == 0 && n > BS_CKV) b_issue(p, n - 1 + BD, bi, sbase, pol);
            {
                float4 s = make_float4(0.f, 0.f, 0.f, 0.f);
#pragma unroll
                for (int w = 0; w < 8; w++) {
                    const float4 v = *reinterpret_cast<const float4*>(red + w * 1024 + head * 32 + ((4 * kq) ^ (8 * (head & 3))));
                    s.x += v.x; s.y += v.y; s.z += v.z; s.w += v.w;
                }
                const uint32_t r0 = pack_bf16(s.x, s.y), r1 = pack_bf16(s.z, s.w);
                const uint32_t s0 = pack_bf16(bf_lo(r0) * SCALE, bf_hi(r0) * SCALE);
                const uint32_t s1 = pack_bf16(bf_lo(r1) * SCALE, bf_hi(r1) * SCALE);
                const float f0 = bf_lo(s0), f1 = bf_hi(s0), f2 = bf_lo(s1), f3 = bf_hi(s1);
                float mx = fmaxf(fmaxf(f0, f1), fmaxf(f2, f3));
                mx = fmaxf(mx, __shfl_xor_sync(~0u, mx, 1));
                mx = fmaxf(mx, __shfl_xor_sync(~0u, mx, 2));
                mx = fmaxf(mx, __shfl_xor_sync(~0u, mx, 4));
                const float mnew = fmaxf(mrun, mx);
                const float al = expsub(mrun, mnew);
                const float p0 = expsub(f0, mnew), p1 = expsub(f1, mnew), p2 = expsub(f2, mnew), p3 = expsub(f3, mnew);
                lrun = lrun * al + ((p0 + p1) + (p2 + p3));
                mrun = mnew;
                *reinterpret_cast<uint2*>(smem + M_P + head * 80 + kq * 8) = make_uint2(pack_bf16(p0, p1), pack_bf16(p2, p3));
                if (kq == 0) alpha[head] = al;
            }
            __syncthreads();
            {
                uint32_t pf[2][2][4];
#pragma unroll
                for (int i = 0; i < 2; i++)
#pragma unroll
                    for (int ks = 0; ks < 2; ks++)
                        ldsm4(pf[i][ks], sbase + M_P + (16 * i + (lane & 15)) * 80 + (16 * ks + 8 * (lane >> 4)) * 2);
#pragma unroll
                for (int i = 0; i < 2; i++) {
                    const float a0 = alpha[16 * i + g], a1 = alpha[16 * i + 8 + g];
#pragma unroll
                    for (int j = 0; j < 8; j++) { acc[i][j][0] *= a0; acc[i][j][1] *= a0; acc[i][j][2] *= a1; acc[i][j][3] *= a1; }
                }
#pragma unroll
                for (int j = 0; j < 8; j++) {
                    uint32_t bf[4];
                    ldsm4t(bf, slot + warp * 4096 + lane * 128 + ((j ^ (lane & 7)) * 16));
#pragma unroll
                    for (int i = 0; i < 2; i++) {
                        mma16816(acc[i][j], pf[i][0], bf[0], bf[1]);
                        mma16816(acc[i][j], pf[i][1], bf[2], bf[3]);
                    }
                }
            }
        }
        __syncthreads();
        if (tid == 0) b_issue(p, BS_PART - 1 + BD, bi, sbase, pol);
        lrun += __shfl_xor_sync(~0u, lrun, 1);
        lrun += __shfl_xor_sync(~0u, lrun, 2);
        lrun += __shfl_xor_sync(~0u, lrun, 4);
        if (kq == 0) scratch(p)->bml[head * NBCTA + bi] = make_float2(mrun, lrun);
#pragma unroll
        for (int i = 0; i < 2; i++)
#pragma unroll
            for (int j = 0; j < 8; j++) {
                scratch(p)->bpart[((16 * i + g) * NBCTA + bi) * 256 + warp * 32 + j * 4 + t] = make_float2(acc[i][j][0], acc[i][j][1]);
                scratch(p)->bpart[((16 * i + 8 + g) * NBCTA + bi) * 256 + warp * 32 + j * 4 + t] = make_float2(acc[i][j][2], acc[i][j][3]);
            }
    }
    b_exchange(&ctl[C_BBAR + 1][0], BS_PART, &scratch(p)->bpart[bi * NBCTA * 256], sbase, pol);
    {
        float* omega = reinterpret_cast<float*>(smem + M_OMEGA);
        if (warp == 0) {
            __syncwarp();
            const uint2 ml = ld_relaxed8(&scratch(p)->bml[bi * NBCTA + lane]);
            const float ms = __uint_as_float(ml.x);
            float m = ms;
            m = fmaxf(m, __shfl_xor_sync(~0u, m, 1));
            m = fmaxf(m, __shfl_xor_sync(~0u, m, 2));
            m = fmaxf(m, __shfl_xor_sync(~0u, m, 4));
            const float w = expsub(ms, m);
            float l = w * __uint_as_float(ml.y);
            l += __shfl_xor_sync(~0u, l, 1);
            l += __shfl_xor_sync(~0u, l, 2);
            l += __shfl_xor_sync(~0u, l, 4);
            omega[lane] = w / l;
        }
        __syncthreads();
        b_wait(BS_PART, sbase);
        b_wait(BS_PART + 1, sbase);
#pragma unroll 1
        for (int b = 0; b < 4; b++) {
            const float2* ps = reinterpret_cast<const float2*>(smem + ((BS_PART + (b >> 1)) % BRING) * SLOT) + (b & 1) * 2048 + tid;
            float c0 = 0.f, c1 = 0.f;
#pragma unroll
            for (int s = 0; s < 8; s++) {
                const float w = omega[b * 8 + s];
                const float2 v = ps[s * 256];
                c0 = fmaf(w, v.x, c0);
                c1 = fmaf(w, v.y, c1);
            }
            const uint32_t hi = pack_bf16(c0, c1);
            *reinterpret_cast<uint32_t*>(smem + M_CH + b * CP + tid * 4) = hi;
            *reinterpret_cast<uint32_t*>(smem + M_CL + b * CP + tid * 4) = pack_bf16(c0 - bf_lo(hi), c1 - bf_hi(hi));
        }
        __syncthreads();
        if (tid == 0) { b_issue(p, BS_PART + BD, bi, sbase, pol); b_issue(p, BS_PART + 1 + BD, bi, sbase, pol); }
    }
    b_gemm(p, sbase, BS_WUV, BS_END, 512, sbase + M_CH, sbase + M_CL, CP, bi, pol);
    if (CLU) {
        if (warp < 4) {
            const unsigned short* c = reinterpret_cast<const unsigned short*>(smem + M_QB + warp * QP) + 16 * t + g;
            scratch(p)->octx[(bi * 4 + warp) * 32 + lane] = make_float4(bf_lo(c[0]), bf_lo(c[8]), bf_lo(c[64]), bf_lo(c[72]));
        }
        __syncthreads();
        if (tid == 0) asm volatile("st.release.gpu.global.u32 [%0], %1;" ::"l"(&scratch(p)->cdone[bi][0]), "r"(epoch + 1) : "memory");
        return;
    }
    if (tid == 0) {
#pragma unroll 1
        for (int i = 0; i < 4; i++) {
            mbar_expect_tx(sbase + M_BAR + i * 8, 36864);
            tma3d(sbase + i * 36864, &p.tm_wo, 0, bi * 128 + i * 32, 0, sbase + M_BAR + i * 8, pol);
        }
    }
    {
        float acc[9][4];
#pragma unroll
        for (int j = 0; j < 9; j++) { acc[j][0] = acc[j][1] = acc[j][2] = acc[j][3] = 0.f; }
#pragma unroll 1
        for (int i = 0; i < 4; i++) {
            const uint32_t xo = sbase + M_QB + (g & 3) * QP + i * 64 + t * 4;
            const uint32_t a0[4] = {lds32(xo), 0u, lds32(xo + 16), 0u}, a1[4] = {lds32(xo + 32), 0u, lds32(xo + 48), 0u};
            mbar_wait(sbase + M_BAR + i * 8, 0);
#pragma unroll
            for (int j = 0; j < 9; j++) {
                const int nt = warp * 9 + j;
                uint32_t w[4];
                ldsm4t(w, sbase + i * 36864 + (nt >> 3) * 4096 + lane * 128 + (((nt & 7) ^ (lane & 7)) * 16));
                mma16816(acc[j], a0, w[0], w[1]);
                mma16816(acc[j], a1, w[2], w[3]);
            }
        }
        if (g < 4) {
#pragma unroll
            for (int j = 0; j < 9; j++) {
                const int c2 = (warp * 9 + j) * 4 + t;
                st_tagged2(&scratch(p)->outb[((c2 / 9) * NH + bi) * 36 + g * 9 + c2 % 9], acc[j][0], acc[j][1], epoch + 1);
            }
        }
    }
    {
        const uint4* src = scratch(p)->outb + (bi * NH + (tid >> 3)) * 36 + (tid & 7);
        float2* part = reinterpret_cast<float2*>(red);
        unsigned n = 0;
        while (true) {
            ulonglong2 v[5];
            bool ok = true;
#pragma unroll
            for (int i = 0; i < 5; i++)
                if (i < 4 || (tid & 7) < 4) v[i] = ld_tagged2(src + i * 8);
#pragma unroll
            for (int i = 0; i < 5; i++)
                if (i < 4 || (tid & 7) < 4) {
                    ok = ok && (unsigned)(v[i].x >> 32) == epoch + 1 && (unsigned)(v[i].y >> 32) == epoch + 1;
                    part[(tid >> 3) * 36 + (tid & 7) + i * 8] = make_float2(__uint_as_float((unsigned)v[i].x), __uint_as_float((unsigned)v[i].y));
                }
            if (ok) break;
            __nanosleep(400);
            if (++n > SPIN_LIMIT) __trap();
        }
        __syncthreads();
        if (tid < 36) {
            float s0 = 0.f, s1 = 0.f;
#pragma unroll 8
            for (int h = 0; h < NH; h++) { const float2 v = part[h * 36 + tid]; s0 += v.x; s1 += v.y; }
            *reinterpret_cast<uint32_t*>(p.out + (tid / 9) * 2 * DM + DM + bi * 18 + (tid % 9) * 2) = pack_bf16(s0, s1);
        }
    }
}

template <bool CLU>
__global__ void __launch_bounds__(256, 1) fused_decode_kernel(const __grid_constant__ Params p) {
    asm volatile("{\n.reg .pred p;\n.reg .u32 a;\n.reg .u64 b;\nsub.u32 a, %1, 128;\nsetp.lt.u32 p, a, %3;\nmad.lo.u32 a, %2, %3, %1;\n"
                 "mad.wide.u32 b, a, 128, %0;\n@p prefetch.global.L2 [b];\n}"
                 ::"l"(p.kc), "r"(threadIdx.x), "r"(blockIdx.x), "n"(PFN) : "memory");
    if (blockIdx.x >= 1024) return;
    extern __shared__ __align__(1024) char smem_raw[];
    const uint32_t sbase = (smem_u32(smem_raw) + 1023u) & ~1023u;
    char* smem = smem_raw + (sbase - smem_u32(smem_raw));
    const int tid = threadIdx.x, warp = __shfl_sync(~0u, tid >> 5, 0), lane = tid & 31;
    const int cl = blockIdx.x >> 3, rank = blockIdx.x & 7;
    const bool isB = CLU ? rank < (cl < MINCL - 2 ? 2 : 3) : (blockIdx.x & 3) == 0 && blockIdx.x < 4 * NBCTA;
    const int bi = CLU ? (rank < 2 ? 2 * cl + rank : cl + MINCL + 2) : blockIdx.x >> 2;
    const int nb = CLU ? 6 * cl + rank - 2 - max(0, cl - (MINCL - 3)) : blockIdx.x - min(NBCTA, (blockIdx.x + 3) >> 2);
    const int blk = CLU ? (isB ? bi : NBCTA + nb) : blockIdx.x;
    const int nblk = CLU ? 8 * MINCL : gridDim.x, nnb = nblk - NBCTA;
    const int nstatic = nnb * (NW + XW);
    uint64_t pol;
    asm volatile("createpolicy.fractional.L2::evict_first.b64 %0, 1.0;" : "=l"(pol));
    const uint32_t wbar = sbase + M_BAR + warp * 8, wslot = sbase + warp * SLOT;
    const int u0 = warp * nnb + nb;
    const bool hold = ((blk >> 2) >> KMIN << KMIN) * 4 * UPP < nstatic;
    const uint32_t jbar = sbase + M_BAR + (NSLOT + BRING) * 8;
    if (warp < 4) {
        const char* src = reinterpret_cast<const char*>(p.kc) + (size_t)(((unsigned)u0 >> 7) * 1024 + (u0 & 127)) * TILE_BYTES;
        asm volatile("" : "+l"(src));
        mbar_init_warp(wbar);
        if (warp < NEARLY && !isB && (CLU || !hold)) tile_load_warp(wslot, src, wbar, pol);
    }
    asm volatile("" ::: "memory");
    if (warp == 7) {
        if (blk < 128) {
            uint64_t poln;
            asm volatile("createpolicy.fractional.L2::evict_normal.b64 %0, 1.0;" : "=l"(poln));
            mbar_init_warp(jbar);
            tma3d_warp(sbase + J0W, &p.tm_j0, blk * 32, 0, 0, jbar, 36864, poln);
            mbar_init_warp(jbar + 8);
            if (lane == 0) {
                mbar_expect_tx(jbar + 8, 4608);
                bulk_load(sbase + M_XA, p.xa, 4608, jbar + 8, poln);
            }
        }
        if (lane < 8) reinterpret_cast<unsigned*>(smem + M_HELP)[lane] = 0;
        __syncwarp();
        if (!isB) asm volatile("bar.arrive 2, %0;" ::"n"(32 * (NW + XW + 1)) : "memory");
    }
    unsigned epoch = 0;
    if (lane == 0) epoch = ld_relaxed4(scratch(p)->epoch);
    if (blk >= 128 ? warp >= 4 : isB && warp < 4) epoch = __shfl_sync(~0u, epoch, 0);
    if (isB && warp == 3) asm volatile("bar.sync 1, 160;" ::: "memory");
    if (isB && tid == 96) {
#pragma unroll 1
        for (int i = 0; i < BRING; i++) mbar_init(sbase + M_BAR + (NSLOT + i) * 8, 1);
        asm volatile("fence.mbarrier_init.release.cluster;" ::: "memory");
        if (hold) { unsigned n = 0; while (ld_acquire_cta_shared(sbase + M_HELP + 24) < 2) { if (++n > (SPIN_LIMIT << 4)) __trap(); } }
#pragma unroll 1
        for (int b = 0; b < 4; b++) bulk_load(sbase + M_XB + b * XP, p.xb + b * DM, 1152, sbase + M_BAR + NSLOT * 8, pol);
#pragma unroll 1
        for (int n = 0; n < BD; n++) b_issue(p, n, bi, sbase, pol);
    }
    if (warp >= 4 && blk < 128) {
        const int g = lane >> 2, t = lane & 3, j = tid - 128;
        asm volatile("bar.sync 1, %0;" ::"r"(isB ? 160 : 128) : "memory");
#pragma unroll 1
        for (int ph = -1;; ph++) {
        const int sl = ph > 0 ? blk + 128 - nblk : blk;
        const uint32_t wa = sbase + J0W + ((warp - 4) * 144 + (lane & 7) + (lane >> 4) * 8) * 64 + ((((lane >> 3) & 1) ^ ((lane >> 1) & 3)) * 16);
        const uint32_t xa = sbase + M_XA + (g & 3) * 1152 + (warp - 4) * 288 + t * 4;
        if (ph >= 0) mbar_wait(jbar + 8, 0);
        uint32_t xb[18];
#pragma unroll
        for (int s = 0; s < 18; s++) xb[s] = lds32(xa + s * 16);
        epoch = __shfl_sync(~0u, epoch, 0);
        if (ph >= 0) mbar_wait(jbar, ph);
        float acc[4][4];
#pragma unroll
        for (int i = 0; i < 16; i++) acc[i >> 2][i & 3] = 0.f;
#pragma unroll
        for (int s = 0; s < 18; s++) {
            uint32_t w[4];
            ldsm4t(w, (wa ^ ((s & 1) * 32)) + (s >> 1) * 1024);
            mma16816(acc[s & 3], w, xb[s & ~1], xb[s | 1]);
        }
        float2* j0 = reinterpret_cast<float2*>(smem + M_J0);
        {
            float* jf = reinterpret_cast<float*>(j0) + (warp - 4) * 128 + (t & 1) * 64 + (t >> 1) * 8 + g;
#pragma unroll
            for (int i = 0; i < 4; i++)
                jf[(i & 1) * 32 + (i >> 1) * 16] = (t & 2) ? acc[i >> 1][2 + (i & 1)] + acc[2 + (i >> 1)][2 + (i & 1)] : acc[i >> 1][i & 1] + acc[2 + (i >> 1)][i & 1];
        }
        asm volatile("bar.sync 1, 128;" ::: "memory");
        const bool again = ph == 0 && blk + 128 - nblk >= nblk;
        if (again && tid == 224) {
            mbar_expect_tx(jbar, 36864);
            tma3d(sbase + J0W, &p.tm_j0, (blk + 128 - nblk) * 32, 0, 0, jbar, pol);
        }
        if (warp < 6) {
            const float2 v0 = j0[j], v1 = j0[64 + j], v2 = j0[128 + j], v3 = j0[192 + j];
            asm volatile("{\n.reg .pred p;\n.reg .b64 v;\nsetp.ge.s32 p, %3, 0;\nmov.b64 v, {%1, %2};\n@p st.relaxed.gpu.global.u64 [%0], v;\n}"
                         ::"l"(&scratch(p)->qll[(j >> 4) * 2048 + sl * 16 + (j & 15)]),
                           "r"(pack_bf16((v0.x + v1.x) + (v2.x + v3.x), (v0.y + v1.y) + (v2.y + v3.y))), "r"(epoch + 1), "r"(ph) : "memory");
            __syncwarp();
            if (lane == 0 && ph >= 0) asm volatile("red.relaxed.cta.shared::cta.add.u32 [%0], 1;" ::"r"(sbase + M_HELP + 24) : "memory");
        } else if (warp == 7) {
            if (blk < C_LINES && ph == 0) scratch(p)->ctl[(epoch & 1) ^ 1][blk][lane] = 0;
        }
        if (ph >= 0 && !again) break;
        asm volatile("bar.sync 1, 128;" ::: "memory");
        }
    }
    if (CLU) {
        if (warp == 6) {
            if (lane < 24 && lane > 1) mbar_init(sbase + F_BAR + lane * 8, 1);
            if ((lane >> 1) == 1) mbar_expect_tx(sbase + F_BAR + lane * 8, 1024);
            asm volatile("fence.mbarrier_init.release.cluster;" ::: "memory");
        }
        asm volatile("barrier.cluster.arrive.relaxed.aligned;" ::: "memory");
    }
    const int c5 = cl % 5;
    const bool partA = CLU && c5 < 3;
    const int nwork = partA && rank == 7 ? 1 : NW + ((CLU ? rank < 2 + X3C && c5 < 4 : (nb & 3) < X3) ? 1 : 0);
    if (isB) {
        b_chain<CLU>(p, smem, sbase, bi, epoch, pol);
        if (!CLU) return;
        if (warp == 2) {
            unsigned n = 0;
            while (ld_acquire(&scratch(p)->ctl[epoch & 1][C_KDONE][0]) < NUK / 2) { __nanosleep(1000); if (++n > SPIN_LIMIT) __trap(); }
        }
    } else if (warp < NW + XW) {
        a_worker<CLU>(p, u0, warp >= nwork, warp < NEARLY && !hold, hold, nstatic, wslot, wbar, sbase + M_HELP,
                      epoch, pol);
        if (!CLU || warp < nwork) return;
        epoch = __shfl_sync(~0u, epoch, 0);
        unsigned n = 0;
        while (ld_acquire_cta_shared(sbase + M_HELP + 12) == 0) { __nanosleep(1000); if (++n > SPIN_LIMIT) __trap(); }
    } else if (warp == 7) {
#pragma unroll 1
        for (int i = nb; i < 4 * NH; i += nnb) scratch(p)->oacc[i * 32 + lane] = make_float4(0.f, 0.f, 0.f, 0.f);
        if (nb < (CLU ? NREPC : NREP) * NH) scratch(p)->vdone[nb][lane] = 0;
        __syncwarp();
        k_helper(p, sbase + M_HELP, epoch);
        if (nb == 0 && lane == 0) scratch(p)->epoch[0] = epoch + 1;
        __syncwarp();
    } else if (!CLU && nb < NFIN) {
        if (warp == 6) {
            finisher(p, sbase, nb);
        } else if (warp >= 6 - NPOLL) {
            v_poller(p, sbase, nb, warp - (6 - NPOLL));
        }
    }
    if (!CLU) return;
    asm volatile("barrier.cluster.wait.acquire.aligned;" ::: "memory");
    const int nsl = c5 == 4 ? 2 : 1, panel = cl / 5 * 3 + (partA ? c5 : c5 - 3);
    if (warp >= 4) {
        f_project(p, rank, warp - 4, nsl, sbase);
        return;
    }
    if (isB ? warp == 2 : warp < 3 || nwork == 3)
        f_collect((partA ? scratch(p)->vdone : scratch(p)->cdone) + 4 * rank, partA ? 4 * UPP : epoch + 1,
                  (partA ? scratch(p)->oacc : scratch(p)->octx) + 4 * rank * 128, nwork == 1 ? 5 * warp : 15, sbase);
    if (warp != 3) return;
    f_request(p, partA ? &p.tm_fa : &p.tm_fb, panel, rank, nsl, nsl == 2 ? B0 + rank * (BJ / 8) : A0 + rank * (AJ / 8), nsl == 2 ? BJ : AJ, epoch + 1, sbase, pol);
    f_receive(p, p.out + (partA ? 0 : DM) + panel * 64 + rank * 8, nsl, sbase);
}

}

typedef CUresult (*EncodeFn)(CUtensorMap*, CUtensorMapDataType, cuuint32_t, void*, const cuuint64_t*, const cuuint64_t*,
                             const cuuint32_t*, const cuuint32_t*, CUtensorMapInterleave, CUtensorMapSwizzle,
                             CUtensorMapL2promotion, CUtensorMapFloatOOBfill);

extern "C" void kernel_launch(void* const* d_in, const int* in_sizes, int n_in, void* d_out, int out_size) {
    (void)in_sizes; (void)n_in; (void)out_size;
    static int nsm = 0, ncl = 0;
    static EncodeFn encode = nullptr;
    static void* scr = nullptr;
    cudaLaunchConfig_t cfg = {};
    cudaLaunchAttribute at[1];
    at[0].id = cudaLaunchAttributeClusterDimension;
    at[0].val.clusterDim.x = 8; at[0].val.clusterDim.y = 1; at[0].val.clusterDim.z = 1;
    cfg.blockDim = dim3(256); cfg.dynamicSmemBytes = SMEM_BYTES; cfg.stream = cudaStreamPerThread; cfg.attrs = at; cfg.numAttrs = 1;
    if (nsm == 0) {
        int dev = 0;
        cudaGetDevice(&dev);
        cudaDeviceGetAttribute(&nsm, cudaDevAttrMultiProcessorCount, dev);
        cudaFuncSetAttribute(fused_decode_kernel<false>, cudaFuncAttributeMaxDynamicSharedMemorySize, SMEM_BYTES);
        cudaFuncSetAttribute(fused_decode_kernel<true>, cudaFuncAttributeMaxDynamicSharedMemorySize, SMEM_BYTES);
        cfg.gridDim = dim3(128);
        if (cudaOccupancyMaxActiveClusters(&ncl, fused_decode_kernel<true>, &cfg) != cudaSuccess) { ncl = 0; (void)cudaGetLastError(); }
        if (ncl > MINCL) ncl = MINCL;
        void* fn = nullptr;
        cudaDriverEntryPointQueryResult qr;
        cudaGetDriverEntryPoint("cuTensorMapEncodeTiled", &fn, cudaEnableDefault, &qr);
        encode = (EncodeFn)fn;
        cudaGetSymbolAddress(&scr, g_scratch);
    }
    Params p;
    auto panels = [&](CUtensorMap* tm, void* ptr, int rows, int cols, int box_rows, int box_panels,
                      CUtensorMapL2promotion promo = CU_TENSOR_MAP_L2_PROMOTION_L2_256B) {
        const cuuint64_t gd[3] = {64, (cuuint64_t)rows, (cuuint64_t)(cols / 64)}, gs[2] = {(cuuint64_t)cols * 2, 128};
        const cuuint32_t box[3] = {64, (cuuint32_t)box_rows, (cuuint32_t)box_panels}, es[3] = {1, 1, 1};
        encode(tm, CU_TENSOR_MAP_DATA_TYPE_BFLOAT16, 3, ptr, gd, gs, box, es, CU_TENSOR_MAP_INTERLEAVE_NONE,
               CU_TENSOR_MAP_SWIZZLE_128B, promo, CU_TENSOR_MAP_FLOAT_OOB_FILL_NONE);
    };
    panels(&p.tm_wq, d_in[7], DM, 4096, 128, 2);
    panels(&p.tm_wuk, d_in[8], 512, 4096, 128, 2);
    panels(&p.tm_wuv, d_in[9], 512, 4096, 128, 2);
    panels(&p.tm_wo, d_in[10], 4096, DM, 32, 9);
    panels(&p.tm_ckv, d_in[6], 4 * SK, 512, 32, 8);
    panels(&p.tm_fa, d_in[4], 4096, DM, 64, 1, CU_TENSOR_MAP_L2_PROMOTION_L2_128B);
    panels(&p.tm_fb, d_in[10], 4096, DM, 64, 1, CU_TENSOR_MAP_L2_PROMOTION_L2_128B);
    {
        const cuuint64_t gd[3] = {4096, 192, 3}, gs[2] = {8192, 192 * 8192};
        const cuuint32_t box[3] = {32, 192, 3}, es[3] = {1, 1, 1};
        encode(&p.tm_j0, CU_TENSOR_MAP_DATA_TYPE_BFLOAT16, 3, d_in[3], gd, gs, box, es, CU_TENSOR_MAP_INTERLEAVE_NONE,
               CU_TENSOR_MAP_SWIZZLE_64B, CU_TENSOR_MAP_L2_PROMOTION_L2_128B, CU_TENSOR_MAP_FLOAT_OOB_FILL_NONE);
    }
    p.xa = (const __nv_bfloat16*)d_in[0];
    p.kc = (const __nv_bfloat16*)d_in[1];
    p.vc = (const __nv_bfloat16*)d_in[2];
    p.wo = (const __nv_bfloat16*)d_in[4];
    p.xb = (const __nv_bfloat16*)d_in[5];
    p.out = (__nv_bfloat16*)d_out;
    p.s = (Scratch*)scr;
    if (ncl >= MINCL) {
        cfg.gridDim = dim3(8 * ncl);
        cudaLaunchKernelEx(&cfg, fused_decode_kernel<true>, p);
    } else {
        fused_decode_kernel<false><<<nsm, 256, SMEM_BYTES, cudaStreamPerThread>>>(p);
    }
}
```

```cpp
#include <cuda_runtime.h>
#include <cuda.h>
#include <cuda_bf16.h>
#include <stdint.h>

namespace {

constexpr int NH = 32, SK = 4096, DM = 576;
constexpr int KEYS = 128;
constexpr int UPP = SK / KEYS;
constexpr int NUK = 4 * NH * UPP;
constexpr int TILE_BYTES = KEYS * 256;
#define NWORK 2
constexpr int NW = NWORK;
constexpr int NBCTA = 32;
constexpr int MINCL = 15;
constexpr int NFIN = 72;
constexpr int SLOT = 32768;
constexpr int NSLOT = 6;
constexpr int BRING = 5;
constexpr int J0W = 5 * SLOT;
constexpr int MISC = NSLOT * SLOT + 4096;
constexpr int XP = 1168, CP = 1040, QP = 272;
constexpr int M_XA = MISC;
constexpr int M_XB = M_XA + 4 * XP;
constexpr int M_CH = M_XB + 4 * XP;
constexpr int M_CL = M_CH + 4 * CP;
constexpr int M_QB = M_CL + 4 * CP;
constexpr int M_QA = M_CH;
constexpr int M_J0 = M_QB + 4 * QP;
constexpr int M_P = M_J0 + 2048;
constexpr int M_ALPHA = M_P + 2560;
constexpr int M_OMEGA = M_ALPHA + 128;
constexpr int M_BAR = M_OMEGA + 128;
constexpr int M_HELP = M_BAR + 128;
constexpr int F_W = 4 * SLOT;
constexpr int F_BF = (M_HELP + 383) / 256 * 256;
constexpr int F_RX = F_BF + 4096;
constexpr int F_BAR = F_RX + 2048;
constexpr int SMEM_BYTES = F_BAR + 192 + 1024;
static_assert(SMEM_BYTES <= 232448 && M_BAR % 8 == 0 && M_QA % 16 == 0 && M_P % 16 == 0, "smem layout");
#define XW 2
#define X3 1
#define X3C 4
#define NEARLY 2
#define LATE 2000
#define BD 5
#define FPF 3
#define FSLEEP 800
#define VS0 24
#define PFN 96
#define EARLY 100
#define ELOG 5
#define TPU 159
#define A0 (1590 + 200 * X3C)
#define AJ 390
#define B0 (A0 - 340)
#define BJ 195
#define LAG 5
#define NPOLL 2
#define PGAP 200
static_assert(X3C <= 4 && NW == 2 && MINCL == 15, "warp 2 of rank 7 is free");
static_assert(NW + XW <= 4 && NEARLY <= NW + XW && BD <= BRING, "slots 4 and 5 hold the finisher weights");
constexpr int KMIN = 2, KMAX = 4, VMIN = 0, VMAX = 4;
constexpr float SCALE = 0.08838834764831845f;
constexpr float LOG2E = 1.4426950408889634f;
constexpr unsigned SPIN_LIMIT = 1u << 24;

#define NREP 2
#define NREPC 1
constexpr int C_QUEUE = 0, C_KDONE = 1, C_BBAR = 3, C_LINES = 5;

struct Scratch {
    unsigned epoch[32];
    unsigned ctl[2][C_LINES][32];
    uint2 qll[4 * 2048];
    uint2 scores[128 * SK / 4];
    float2 stats[128 * UPP];
    float4 oacc[128 * 32];
    unsigned vdone[NREP * NH][32];
    float4 octx[128 * 32];
    unsigned cdone[NH][32];
    unsigned long long dry[16][16];
    uint4 qabs[4 * 8 * 4 * 4 * 32];
    float2 bpart[NBCTA * NH * 256];
    float2 bml[NBCTA * NH];
    uint4 outb[NBCTA * NH * 36];
};
__device__ __align__(256) Scratch g_scratch;

struct Params {
    const __nv_bfloat16 *kc, *xa, *vc, *wo, *xb;
    __nv_bfloat16* out;
    Scratch* s;
    CUtensorMap tm_j0;
    CUtensorMap tm_wq, tm_wuk, tm_ckv, tm_wuv, tm_wo;
    CUtensorMap tm_fa, tm_fb;
};

__device__ __forceinline__ Scratch* scratch(const Params& p) {
    Scratch* s = p.s;
    __builtin_assume(__isGlobal(s));
    return s;
}

__device__ __forceinline__ uint32_t smem_u32(const void* p) { return (uint32_t)__cvta_generic_to_shared(p); }
__device__ __forceinline__ void mbar_init(uint32_t bar, uint32_t cnt) {
    asm volatile("mbarrier.init.shared::cta.b64 [%0], %1;" ::"r"(bar), "r"(cnt) : "memory");
}
__device__ __forceinline__ void mbar_expect_tx(uint32_t bar, uint32_t bytes) {
    asm volatile("mbarrier.arrive.expect_tx.shared::cta.b64 _, [%0], %1;" ::"r"(bar), "r"(bytes) : "memory");
}
__device__ __forceinline__ bool mbar_try(uint32_t bar, uint32_t parity) {
    uint32_t ok;
    asm volatile("{\n.reg .pred p;\nmbarrier.try_wait.parity.shared::cta.b64 p, [%1], %2;\nselp.u32 %0, 1, 0, p;\n}\n"
                 : "=r"(ok) : "r"(bar), "r"(parity) : "memory");
    return ok;
}
__device__ __forceinline__ void mbar_wait(uint32_t bar, uint32_t parity) {
    unsigned n = 0;
    while (!mbar_try(bar, parity)) { if (++n > SPIN_LIMIT) __trap(); }
}
__device__ __forceinline__ void mbar_spin(uint32_t bar) {
    asm volatile("{\n.reg .pred p;\n.reg .u32 n;\nmov.u32 n, 0;\nSPIN:\nmbarrier.try_wait.parity.shared::cta.b64 p, [%0], 0;\n@p bra.uni DONE;\n"
                 "add.u32 n, n, 1;\nsetp.lt.u32 p, n, 0x1000000;\n@p bra.uni SPIN;\ntrap;\nDONE:\n}" ::"r"(bar) : "memory");
}
__device__ __forceinline__ void mbar_spin_cluster(uint32_t bar) {
    asm volatile("{\n.reg .pred p;\n.reg .u32 n;\nmov.u32 n, 0;\nSPIN:\nmbarrier.try_wait.parity.relaxed.cluster.shared::cta.b64 p, [%0], 0;\n"
                 "@p bra.uni DONE;\nadd.u32 n, n, 1;\nsetp.lt.u32 p, n, 0x1000000;\n@p bra.uni SPIN;\ntrap;\nDONE:\n"
                 "fence.acquire.sync_restrict::shared::cluster.cluster;\n}" ::"r"(bar) : "memory");
}
__device__ __forceinline__ void bulk_load(uint32_t dst, const void* src, uint32_t bytes, uint32_t bar, uint64_t pol) {
    asm volatile("cp.async.bulk.shared::cluster.global.mbarrier::complete_tx::bytes.L2::cache_hint [%0], [%1], %2, [%3], %4;"
                 ::"r"(dst), "l"(src), "r"(bytes), "r"(bar), "l"(pol) : "memory");
}
__device__ __forceinline__ void mbar_init_warp(uint32_t bar) {
    asm volatile("{\n.reg .pred p;\nelect.sync _|p, 0xffffffff;\n@p mbarrier.init.shared::cta.b64 [%0], 1;\n@p fence.mbarrier_init.release.cluster;\n}"
                 ::"r"(bar) : "memory");
}
__device__ __forceinline__ void tile_load_warp(uint32_t dst, const void* src, uint32_t bar, uint64_t pol) {
    asm volatile("{\n.reg .pred p;\nelect.sync _|p, 0xffffffff;\n@p mbarrier.arrive.expect_tx.shared::cta.b64 _, [%2], %4;\n"
                 "@p cp.async.bulk.shared::cluster.global.mbarrier::complete_tx::bytes.L2::cache_hint [%0], [%1], %4, [%2], %3;\n}"
                 ::"r"(dst), "l"(src), "r"(bar), "l"(pol), "n"(TILE_BYTES) : "memory");
}
__device__ __forceinline__ void tma3d_warp(uint32_t dst, const CUtensorMap* tm, int c0, int c1, int c2, uint32_t bar, uint32_t bytes, uint64_t pol) {
    asm volatile("{\n.reg .pred p;\nelect.sync _|p, 0xffffffff;\n@p mbarrier.arrive.expect_tx.shared::cta.b64 _, [%2], %7;\n"
                 "@p cp.async.bulk.tensor.3d.shared::cluster.global.mbarrier::complete_tx::bytes.L2::cache_hint [%0], [%1, {%3,%4,%5}], [%2], %6;\n}"
                 ::"r"(dst), "l"(tm), "r"(bar), "r"(c0), "r"(c1), "r"(c2), "l"(pol), "r"(bytes) : "memory");
}
__device__ __forceinline__ void tma3d(uint32_t dst, const CUtensorMap* tm, int c0, int c1, int c2, uint32_t bar, uint64_t pol) {
    asm volatile("cp.async.bulk.tensor.3d.shared::cluster.global.mbarrier::complete_tx::bytes.L2::cache_hint [%0], [%1, {%3,%4,%5}], [%2], %6;"
                 ::"r"(dst), "l"(tm), "r"(bar), "r"(c0), "r"(c1), "r"(c2), "l"(pol) : "memory");
}
__device__ __forceinline__ void l2_prefetch(const void* src, uint32_t bytes) {
    asm volatile("cp.async.bulk.prefetch.L2.global [%0], %1;" ::"l"(src), "r"(bytes) : "memory");
}
__device__ __forceinline__ void ldsm4(uint32_t (&r)[4], uint32_t addr) {
    asm volatile("ldmatrix.sync.aligned.m8n8.x4.shared.b16 {%0,%1,%2,%3}, [%4];"
                 : "=r"(r[0]), "=r"(r[1]), "=r"(r[2]), "=r"(r[3]) : "r"(addr));
}
__device__ __forceinline__ void ldsm4t(uint32_t (&r)[4], uint32_t addr) {
    asm volatile("ldmatrix.sync.aligned.m8n8.x4.trans.shared.b16 {%0,%1,%2,%3}, [%4];"
                 : "=r"(r[0]), "=r"(r[1]), "=r"(r[2]), "=r"(r[3]) : "r"(addr));
}
__device__ __forceinline__ void mma16816(float (&d)[4], const uint32_t (&a)[4], uint32_t b0, uint32_t b1) {
    asm("mma.sync.aligned.m16n8k16.row.col.f32.bf16.bf16.f32 {%0,%1,%2,%3}, {%4,%5,%6,%7}, {%8,%9}, {%0,%1,%2,%3};"
        : "+f"(d[0]), "+f"(d[1]), "+f"(d[2]), "+f"(d[3])
        : "r"(a[0]), "r"(a[1]), "r"(a[2]), "r"(a[3]), "r"(b0), "r"(b1));
}
__device__ __forceinline__ uint32_t lds32(uint32_t a) {
    uint32_t v;
    asm volatile("ld.shared.u32 %0, [%1];" : "=r"(v) : "r"(a));
    return v;
}
__device__ __forceinline__ unsigned ld_acquire(const unsigned* p) {
    unsigned v;
    asm volatile("ld.acquire.gpu.global.u32 %0, [%1];" : "=r"(v) : "l"(p) : "memory");
    return v;
}
__device__ __forceinline__ uint2 ld_relaxed8(const void* p) {
    uint2 v;
    asm volatile("ld.relaxed.gpu.global.v2.u32 {%0,%1}, [%2];" : "=r"(v.x), "=r"(v.y) : "l"(p) : "memory");
    return v;
}
__device__ __forceinline__ unsigned ld_relaxed4(const void* p) {
    unsigned v;
    asm volatile("ld.relaxed.gpu.global.u32 %0, [%1];" : "=r"(v) : "l"(p) : "memory");
    return v;
}
__device__ __forceinline__ unsigned atom_inc(unsigned* p) {
    unsigned v;
    asm volatile("atom.relaxed.gpu.global.inc.u32 %0, [%1], 0x7fffffff;" : "=r"(v) : "l"(p) : "memory");
    return v;
}
__device__ __forceinline__ unsigned long long ld_relaxed64(const void* p) {
    unsigned long long v;
    asm volatile("ld.relaxed.gpu.global.u64 %0, [%1];" : "=l"(v) : "l"(p) : "memory");
    return v;
}
__device__ __forceinline__ void st_relaxed64(void* p, unsigned long long v) {
    asm volatile("st.relaxed.gpu.global.u64 [%0], %1;" ::"l"(p), "l"(v) : "memory");
}
__device__ __forceinline__ float4 ld_relaxed16(const void* p) {
    float4 v;
    asm volatile("ld.relaxed.gpu.global.v4.f32 {%0,%1,%2,%3}, [%4];" : "=f"(v.x), "=f"(v.y), "=f"(v.z), "=f"(v.w) : "l"(p) : "memory");
    return v;
}
__device__ __forceinline__ uint32_t mapa(uint32_t a, uint32_t rank) {
    uint32_t r;
    asm("mapa.shared::cluster.u32 %0, %1, %2;" : "=r"(r) : "r"(a), "r"(rank));
    return r;
}
__device__ __forceinline__ uint32_t time_ns() { uint32_t t; asm volatile("mov.u32 %0, %globaltimer_lo;" : "=r"(t)); return t; }
__device__ __forceinline__ void fence_gpu() { asm volatile("fence.acq_rel.gpu;" ::: "memory"); }
__device__ __forceinline__ void red_add_u32(unsigned* p, unsigned v) {
    asm volatile("red.relaxed.gpu.global.add.u32 [%0], %1;" ::"l"(p), "r"(v) : "memory");
}
__device__ __forceinline__ void st_tagged2(void* p, float a, float b, unsigned tag) {
    const unsigned long long hi = (unsigned long long)tag << 32;
    asm volatile("st.relaxed.gpu.global.v2.b64 [%0], {%1,%2};" ::"l"(p), "l"(hi | __float_as_uint(a)), "l"(hi | __float_as_uint(b)) : "memory");
}
__device__ __forceinline__ ulonglong2 ld_tagged2(const void* p) {
    ulonglong2 v;
    asm volatile("ld.relaxed.gpu.global.v2.b64 {%0,%1}, [%2];" : "=l"(v.x), "=l"(v.y) : "l"(p) : "memory");
    return v;
}
__device__ __forceinline__ float4 atom_add_f4(void* p, float a, float b, float c, float d) {
    float4 r;
    asm volatile("atom.relaxed.gpu.global.add.v4.f32 {%0,%1,%2,%3}, [%4], {%5,%6,%7,%8};"
                 : "=f"(r.x), "=f"(r.y), "=f"(r.z), "=f"(r.w) : "l"(p), "f"(a), "f"(b), "f"(c), "f"(d) : "memory");
    return r;
}
__device__ __forceinline__ void red_release_cta_shared(uint32_t a, unsigned v) {
    asm volatile("red.release.cta.shared::cta.add.u32 [%0], %1;" ::"r"(a), "r"(v) : "memory");
}
__device__ __forceinline__ unsigned ld_acquire_cta_shared(uint32_t a) {
    unsigned v;
    asm volatile("ld.acquire.cta.shared::cta.u32 %0, [%1];" : "=r"(v) : "r"(a) : "memory");
    return v;
}
__device__ __forceinline__ void st_release_cta_shared(uint32_t a, unsigned v) {
    asm volatile("st.release.cta.shared::cta.u32 [%0], %1;" ::"r"(a), "r"(v) : "memory");
}
__device__ __forceinline__ void wait_count(const unsigned* p, unsigned target) {
    unsigned n = 0;
    while (ld_acquire(p) < target) { if (++n > SPIN_LIMIT) __trap(); }
}
__device__ __forceinline__ uint32_t pack_bf16(float lo, float hi) {
    uint32_t r;
    asm("cvt.rn.bf16x2.f32 %0, %1, %2;" : "=r"(r) : "f"(hi), "f"(lo));
    return r;
}
__device__ __forceinline__ float bf_lo(uint32_t v) { return __uint_as_float(v << 16); }
__device__ __forceinline__ float bf_hi(uint32_t v) { return __uint_as_float(v & 0xffff0000u); }
__device__ __forceinline__ float ex2(float x) { float y; asm("ex2.approx.ftz.f32 %0, %1;" : "=f"(y) : "f"(x)); return y; }
__device__ __forceinline__ float expsub(float a, float b) { return ex2((a - b) * LOG2E); }
__device__ __forceinline__ float warp_max(float v) {
#pragma unroll
    for (int m = 16; m; m >>= 1) v = fmaxf(v, __shfl_xor_sync(~0u, v, m));
    return v;
}
__device__ __forceinline__ float warp_sum(float v) {
#pragma unroll
    for (int m = 16; m; m >>= 1) v += __shfl_xor_sync(~0u, v, m);
    return v;
}
template <bool CLU>
__device__ __forceinline__ unsigned unit_block(int u) {
    const unsigned x = ((unsigned)u & (NUK - 1)) / UPP;
    const int lg = u < NUK ? min(KMAX, max(KMIN, 29 - __clz(x | 1))) : (CLU && (int)x >= 4 * VS0 ? 0 : min(VMAX, max(VMIN, 29 - __clz((127 - x) | 1))));
    const unsigned r = x & ((4u << lg) - 1);
    return ((x - r + (r & ((1u << lg) - 1)) * 4 + (r >> lg)) * UPP) | ((unsigned)u & (UPP - 1));
}
__device__ __forceinline__ const char* block_src(const void* base, unsigned blk) {
    const unsigned po = blk / UPP;
    return reinterpret_cast<const char*>(base) + (size_t)(((po & 3) * NH + (po >> 2)) * UPP + blk % UPP) * TILE_BYTES;
}

template <bool CLU>
__device__ __forceinline__ void a_worker(const Params& p, int un, bool once, bool pre, bool hold, int nstatic, uint32_t slot, uint32_t bar,
                                         uint32_t help, unsigned epoch, uint64_t pol) {
    constexpr int NU = 2 * NUK, NR = CLU ? NREPC : NREP;
    const int lane = threadIdx.x & 31, g = lane >> 2, t = lane & 3;
    const int li = lane & 7;
    uint32_t kaddr[4], vaddr[8];
    {
        const int e = (lane >> 3) & 1, kk = lane >> 4;
#pragma unroll
        for (int s = 0; s < 4; s++) kaddr[s] = slot + (16 * li + e) * 256 + ((2 * s + kk + li) & 7) * 16;
        const int vrow = 4 * (li >> 1) + (li & 1) + 2 * kk;
#pragma unroll
        for (int c = 0; c < 8; c++) vaddr[c] = slot + vrow * 256 + e * 128 + ((c + li) & 7) * 16;
#pragma unroll
        for (int c = 0; c < 8; c++) asm volatile("" : "+r"(vaddr[c]));
    }
    const uint32_t vmask = (g >> 1) != t ? 0u : ((g & 1) ? 0xffff0000u : 0xffffu);
    int kseen = -1;
    unsigned long long H0 = 0, H1 = 0;
    auto header = [&](int v, unsigned vb) {
        const void *a0, *a1;
        if (v < NUK) {
            const unsigned po = vb / UPP;
            a0 = scratch(p)->qll + (po & 3) * 2048 + (po >> 2) * 64 + lane;
            a1 = reinterpret_cast<const uint2*>(a0) + 32;
        } else {
            const int half = vb / (NUK / 2);
            if (half > kseen) {
                unsigned n = 0;
                while (ld_acquire_cta_shared(help + 12 + 4 * half) == 0) { if (++n > (SPIN_LIMIT << 4)) __trap(); }
                kseen = half;
            }
            a0 = &scratch(p)->scores[vb * (KEYS / 4) + lane];
            a1 = &scratch(p)->stats[(vb / UPP) * UPP + lane];
        }
        H0 = ld_relaxed64(a0);
        H1 = ld_relaxed64(a1);
    };
    unsigned bu = 0, bn = unit_block<CLU>(un);
    asm volatile("bar.sync 2, %0;" ::"n"(32 * (NW + XW + 1)) : "memory");
    if (!pre && !hold) { const uint32_t t0 = clock(); while ((uint32_t)clock() - t0 < ((threadIdx.x >> 5) - NEARLY + 1) * LATE) {} }
    epoch = __shfl_sync(~0u, epoch, 0);
    if (hold) { unsigned n = 0; while (ld_acquire_cta_shared(help + 24) < 2) { if (++n > (SPIN_LIMIT << 4)) __trap(); } }
    unsigned (*ctl)[32] = scratch(p)->ctl[epoch & 1];
    const unsigned tag = epoch + 1;
    unsigned nxt = once ? NU : 0;
    int u = -1;
    uint32_t phase = 0;
    unsigned kpend = 0;
    const unsigned zero = gridDim.x >> 24;
    uint32_t Q[16];
    float4 oret = make_float4(0.f, 0.f, 0.f, 0.f);
    while (true) {
        const char* nsrc = block_src(un < NUK ? p.kc : p.vc, bn);
        float4* odst = &scratch(p)->oacc[(bu / UPP) * 32 + lane];
        unsigned* vdst = &scratch(p)->vdone[(lane & (NR - 1)) * NH + bu / (4 * UPP)][0];
        float d[8][4];
        uint32_t act = un >= NU ? 0u : (u >= 0 || !pre ? 1u : 0u) | (!once && lane == 0 ? 2u : 0u);
        asm volatile("" : "+l"(odst), "+l"(nsrc), "+r"(act));
        if (u >= NUK) {
#pragma unroll
            for (int j = 0; j < 8; j++) { d[j][0] = d[j][1] = d[j][2] = d[j][3] = 0.f; }
            mbar_wait(bar, phase);
            uint32_t a[2][8][4];
#pragma unroll
            for (int c = 0; c < 8; c++) ldsm4t(a[0][c], vaddr[c]);
#pragma unroll
            for (int j = 0; j < 8; j++) {
                if (j < 7) {
#pragma unroll
                    for (int c = 0; c < 8; c++) ldsm4t(a[(j + 1) & 1][c], vaddr[c] + (j + 1) * 4096);
                }
#pragma unroll
                for (int c = 0; c < 8; c++) mma16816(d[c], a[j & 1][c], Q[2 * j], Q[2 * j + 1]);
            }
            float o[4];
#pragma unroll
            for (int r = 0; r < 2; r++) {
                o[2 * r] = d[0][2 * r] + d[7][2 * r + 1];
                o[2 * r + 1] = d[0][2 * r + 1] + d[1][2 * r];
#pragma unroll
                for (int k = 1; k < 4; k++) {
                    const int src = (lane & 28) | ((t - k) & 3);
                    o[2 * r] += __shfl_sync(~0u, d[2 * k][2 * r] + d[2 * k - 1][2 * r + 1], src);
                    o[2 * r + 1] += __shfl_sync(~0u, d[2 * k][2 * r + 1] + d[2 * k + 1][2 * r], src);
                }
            }
            oret = atom_add_f4(odst, o[0], o[1], o[2], o[3]);
        } else if (u >= 0) {
#pragma unroll
            for (int j = 0; j < 8; j++) { d[j][0] = d[j][1] = d[j][2] = d[j][3] = 0.f; }
            mbar_wait(bar, phase);
            uint32_t a[2][8][4];
#pragma unroll
            for (int j = 0; j < 8; j++) ldsm4(a[0][j], kaddr[0] + (4 * (j & 3) + 2 * (j >> 2)) * 256);
#pragma unroll
            for (int s = 0; s < 8; s++) {
                if (s < 7) {
#pragma unroll
                    for (int j = 0; j < 8; j++)
                        ldsm4(a[(s + 1) & 1][j], kaddr[(s + 1) & 3] + (4 * (j & 3) + 2 * (j >> 2)) * 256 + ((s + 1) >> 2) * 128);
                }
#pragma unroll
                for (int j = 0; j < 8; j++)
                    mma16816(d[j], a[s & 1][j], Q[(s & 4) * 2 + ((2 * s - 2 * j) & 7)], Q[(s & 4) * 2 + ((2 * s + 1 - 2 * j) & 7)]);
            }
        }
        if (u >= 0) phase ^= 1;
        asm volatile("{\n.reg .pred p, q;\n.reg .u32 a;\nelect.sync _|p, 0xffffffff;\nand.b32 a, %5, 1;\nsetp.ne.and.u32 q, a, 0, p;\n"
                     "@q mbarrier.arrive.expect_tx.shared::cta.b64 _, [%2], %4;\n"
                     "@q cp.async.bulk.shared::cluster.global.mbarrier::complete_tx::bytes.L2::cache_hint [%0], [%1], %4, [%2], %3;\n}"
                     ::"r"(slot), "l"(nsrc), "r"(bar), "l"(pol), "n"(TILE_BYTES), "r"(act) : "memory");
        if (act & 2) nxt = atom_inc(&ctl[C_QUEUE][0]);
        const uint32_t tk = clock();
        if ((unsigned)u < (unsigned)NUK) {
            const int j0 = (t - (g >> 1)) & 3;
            float v[4];
#pragma unroll
            for (int q = 0; q < 4; q++) {
                const int jq = (q >> 1) * 4, e = (q & 1) * 2;
                const float x0 = (g & 1) ? d[jq + 0][e + 1] : d[jq + 0][e];
                const float x1 = (g & 1) ? d[jq + 1][e + 1] : d[jq + 1][e];
                const float x2 = (g & 1) ? d[jq + 2][e + 1] : d[jq + 2][e];
                const float x3 = (g & 1) ? d[jq + 3][e + 1] : d[jq + 3][e];
                const float y0 = (j0 & 1) ? x1 : x0, y1 = (j0 & 1) ? x3 : x2;
                v[q] = (j0 & 2) ? y1 : y0;
            }
            const uint32_t r0 = pack_bf16(v[0], v[1]), r1 = pack_bf16(v[2], v[3]);
            const uint32_t s0 = pack_bf16(bf_lo(r0) * SCALE, bf_hi(r0) * SCALE);
            const uint32_t s1 = pack_bf16(bf_lo(r1) * SCALE, bf_hi(r1) * SCALE);
            scratch(p)->scores[bu * (KEYS / 4) + 4 * g + j0] = make_uint2(s0, s1);
            const float f0 = bf_lo(s0), f1 = bf_hi(s0), f2 = bf_lo(s1), f3 = bf_hi(s1);
            const float m = warp_max(fmaxf(fmaxf(f0, f1), fmaxf(f2, f3)));
            const float l = warp_sum((expsub(f0, m) + expsub(f1, m)) + (expsub(f2, m) + expsub(f3, m)));
            if (lane == 0) scratch(p)->stats[bu] = make_float2(m, l);
            kpend++;
            if (un / (NUK / 2) != u / (NUK / 2)) {
                __syncwarp();
                if (lane == 0) {
                    red_release_cta_shared(help + 4 * (u / (NUK / 2)), kpend);
                    if (un >= NUK) red_release_cta_shared(help + 8, 1u);
                }
                kpend = 0;
            }
        }
        int unn = NU;
        if (un < NU) {
            unsigned n = 0;
            while (true) {
                header(un, bn);
                if (un >= NUK || __all_sync(~0u, (uint32_t)(H0 >> 32) == tag && (uint32_t)(H1 >> 32) == tag)) break;
                if (++n > SPIN_LIMIT) __trap();
            }
            if (un >= NUK) {
                const uint32_t s0 = (uint32_t)H0, s1 = (uint32_t)(H0 >> 32);
                const float mu = __uint_as_float((uint32_t)H1);
                const float m = warp_max(mu);
                const float l = warp_sum(__uint_as_float((uint32_t)(H1 >> 32)) * expsub(mu, m));
                const float inv = 1.0f / l;
                const uint32_t w0 = pack_bf16(expsub(bf_lo(s0), m) * inv, expsub(bf_hi(s0), m) * inv);
                const uint32_t w1 = pack_bf16(expsub(bf_lo(s1), m) * inv, expsub(bf_hi(s1), m) * inv);
#pragma unroll
                for (int j = 0; j < 8; j++) {
                    Q[2 * j] = __shfl_sync(~0u, w0, 4 * j + t) & vmask;
                    Q[2 * j + 1] = __shfl_sync(~0u, w1, 4 * j + t) & vmask;
                }
            } else {
#pragma unroll
                for (int j = 0; j < 8; j++) {
                    const int src = (((j + g) & 7) << 2) + t;
                    Q[j] = __shfl_sync(~0u, (uint32_t)H0, src);
                    Q[8 + j] = __shfl_sync(~0u, (uint32_t)H1, src);
                }
            }
            unn = nstatic + (int)__shfl_sync(~0u, nxt, 0);
            if (CLU && ((NU - EARLY - unn) & ~(7 << ELOG)) == 0 && lane < MINCL)
                st_relaxed64(&scratch(p)->dry[lane][(NU - EARLY - unn) >> ELOG],
                             (time_ns() - (((uint32_t)clock() - tk) >> 1) + (NU - unn) * TPU / 16) | (unsigned long long)tag << 32);
        }
        if (u >= NUK && lane < NR)
            red_add_u32(vdst,
                        1u + ((__float_as_uint(oret.x) | __float_as_uint(oret.y) | __float_as_uint(oret.z) | __float_as_uint(oret.w)) & zero));
        if (un >= NU) break;
        bu = bn;
        bn = unit_block<CLU>(unn);
        u = un;
        un = unn;
    }
}

__device__ __forceinline__ void k_helper(const Params& p, uint32_t help, unsigned epoch) {
    if ((threadIdx.x & 31) != 0) return;
    unsigned (*ctl)[32] = scratch(p)->ctl[epoch & 1];
    unsigned sent0 = 0, sent1 = 0, n = 0;
    int seen = 0;
    bool fin = false;
    while (!fin || seen < 2) {
        if (!fin) {
            fin = ld_acquire_cta_shared(help + 8) == NW + XW;
            const unsigned c0 = ld_acquire_cta_shared(help), c1 = ld_acquire_cta_shared(help + 4);
            if (c0 != sent0 || c1 != sent1) {
                fence_gpu();
                if (c0 != sent0) red_add_u32(&ctl[C_KDONE][0], c0 - sent0);
                if (c1 != sent1) red_add_u32(&ctl[C_KDONE + 1][0], c1 - sent1);
                sent0 = c0; sent1 = c1;
            }
        }
        if (seen < 2 && ld_acquire(&ctl[C_KDONE + seen][0]) >= NUK / 2) {
            st_release_cta_shared(help + 12 + 4 * seen, 1u);
            seen++;
        } else {
            __nanosleep(300);
        }
        if (++n > SPIN_LIMIT) __trap();
    }
}

__device__ __forceinline__ void v_poller(const Params& p, uint32_t sbase, int f, int w) {
    constexpr int HL = NH;
    const int lane = threadIdx.x & 31;
    const unsigned (*cp)[32] = &scratch(p)->vdone[((f * NPOLL + w) % NREP) * NH];
    unsigned n = 0;
    while (ld_acquire_cta_shared(sbase + M_HELP + 12) == 0) { __nanosleep(1000); if (++n > SPIN_LIMIT) __trap(); }
    int h = 0;
    bool fast = false;
    while (h < HL) {
        const unsigned r = __ballot_sync(~0u, ld_acquire(&cp[min(h + (lane & 3), HL - 1)][0]) >= 4 * UPP) & 15u;
        if (r & 1) {
            h = min(HL, h + __ffs(~r) - 1);
            __syncwarp();
            if (lane == 0) asm volatile("red.release.cta.shared::cta.max.u32 [%0], %1;" ::"r"(sbase + M_HELP + 20), "r"(h) : "memory");
        }
        if (h < HL - 4) {
            __nanosleep(h ? 300 : 1000);
        } else if (!fast) {
            fast = true;
            const long long t0 = clock64();
            while (clock64() - t0 < w * PGAP) {}
        }
        if (++n > SPIN_LIMIT) __trap();
    }
}
__device__ __forceinline__ void finisher(const Params& p, uint32_t sbase, int f) {
    constexpr int HL = NH;
    const int lane = threadIdx.x & 31;
    {
        const char* wg = reinterpret_cast<const char*>(p.wo);
        const uint32_t dst = sbase + 4 * SLOT + (16 * (lane & 7) + (lane >> 3)) * 16;
#pragma unroll 1
        for (int h = -FPF - 4; h < HL; h++) {
            if (lane == 0 && (unsigned)(h + FPF) < (unsigned)HL) l2_prefetch(wg + (size_t)(h + FPF) * 147456 + f * 2048, 2048);
            if (h >= 0) {
#pragma unroll
                for (int r = 0; r < 4; r++)
                    asm volatile("cp.async.cg.shared.global [%0], [%1], 16;" ::"r"(dst + h * 2048 + ((r & 1) * 4 + (r >> 1) * 8) * 16),
                                 "l"(wg + (size_t)(h * 128 + r * 32 + lane) * (DM * 2) + f * 16) : "memory");
            }
            __nanosleep(FSLEEP);
        }
        asm volatile("cp.async.wait_all;" ::: "memory");
        __syncwarp();
    }
    const float4* vec = scratch(p)->oacc + ((lane >> 2) & 3) * 32 + (lane >> 4) * 16 + (lane & 3);
    float acc[2][2][4];
#pragma unroll
    for (int i = 0; i < 16; i++) acc[i >> 3][(i >> 2) & 1][i & 3] = 0.f;
    uint32_t* outp = reinterpret_cast<uint32_t*>(p.out + (lane >> 2) * (2 * DM) + f * 8 + (lane & 3) * 2);
    uint32_t wa = sbase + 4 * SLOT + lane * 16;
    auto project = [&](const float4 (&x)[4], const uint32_t (&w)[4][4]) {
#pragma unroll
        for (int s = 0; s < 4; s++) {
            const uint32_t a[4] = {pack_bf16(x[s].x, x[s].y), 0u, pack_bf16(x[s].z, x[s].w), 0u};
            mma16816(acc[0][s & 1], a, w[s >> 1][(s & 1) * 2], w[s >> 1][(s & 1) * 2 + 1]);
            mma16816(acc[1][s & 1], a, w[2 + (s >> 1)][(s & 1) * 2], w[2 + (s >> 1)][(s & 1) * 2 + 1]);
        }
    };
    int h = 0;
    unsigned n = 0;
    while (h < HL) {
        uint32_t w[4][4];
#pragma unroll
        for (int q = 0; q < 4; q++) ldsm4t(w[q], wa + q * 512);
        int ready;
        while ((ready = ld_acquire_cta_shared(sbase + M_HELP + 20)) <= h) {
            if (h < HL - 3) __nanosleep(100);
            if (++n > (SPIN_LIMIT << 4)) __trap();
        }
        float4 x[4], y[4];
#pragma unroll
        for (int s = 0; s < 4; s++) x[s] = ld_relaxed16(vec + s * 4);
        const bool two = ready > h + 1;
        if (two) {
#pragma unroll
            for (int s = 0; s < 4; s++) y[s] = ld_relaxed16(vec + 128 + s * 4);
        }
        project(x, w);
        if (two) {
#pragma unroll
            for (int q = 0; q < 4; q++) ldsm4t(w[q], wa + 2048 + q * 512);
            project(y, w);
        }
        const int nr = two ? 2 : 1;
        h += nr;
        vec += nr * 128;
        wa += nr * 2048;
        const float o0 = acc[0][0][0] + acc[0][1][0] + __shfl_down_sync(~0u, acc[1][0][0] + acc[1][1][0], 16);
        const float o1 = acc[0][0][1] + acc[0][1][1] + __shfl_down_sync(~0u, acc[1][0][1] + acc[1][1][1], 16);
        asm volatile("{\n.reg .pred p;\nsetp.ne.u32 p, %2, 0;\n@p st.global.u32 [%0], %1;\n}" ::"l"(outp), "r"(pack_bf16(o0, o1)),
                     "r"((uint32_t)(lane < 16 && h == NH)) : "memory");
    }
}

__device__ __noinline__ void f_collect(const unsigned (*flag)[32], unsigned full, const float4* src, unsigned todo, uint32_t sbase) {
    const int lane = threadIdx.x & 31, g = lane >> 2, t = lane & 3;
    const bool last = todo != 15;
    unsigned n = 0;
    while (todo) {
        const unsigned v = ld_acquire(&flag[t][0]);
        unsigned m = __ballot_sync(~0u, v == full) & todo;
        if (m == 0) {
            if (!last || __shfl_sync(~0u, v, 0) == 0) __nanosleep(200);
            if (++n > SPIN_LIMIT) __trap();
            continue;
        }
        __syncwarp();
        todo ^= m;
        do {
            const int h0 = __ffs(m) - 1, h1 = 31 - __clz(m);
            m &= ~((1u << h0) | (1u << h1));
            float4 x[8];
#pragma unroll
            for (int b = 0; b < 8; b++) x[b] = ld_relaxed16(src + ((b & 4) ? h1 : h0) * 128 + (b & 3) * 32 + lane);
#pragma unroll
            for (int b = 0; b < 8; b++) {
                const uint32_t lo = pack_bf16(x[b].x, x[b].y), hi = pack_bf16(x[b].z, x[b].w);
                const uint32_t o = __shfl_xor_sync(~0u, (g & 1) ? lo : hi, 4);
                const uint32_t e0 = (g & 1) ? o : lo, e1 = (g & 1) ? hi : o;
                asm volatile("st.shared.v2.u32 [%0], {%1,%2};"
                             ::"r"(sbase + F_BF + ((b & 4) ? h1 : h0) * 1024 + t * 256 + ((b ^ t) & 3) * 64 + g * 8),
                               "r"(__byte_perm(e0, e1, 0x5410)), "r"(__byte_perm(e0, e1, 0x7632)) : "memory");
            }
            __syncwarp();
            if (lane < (h0 == h1 ? 1 : 2))
                asm volatile("mbarrier.arrive.shared::cta.b64 _, [%0];" ::"r"(sbase + F_BAR + 32 + (lane ? h1 : h0) * 8) : "memory");
        } while (m);
    }
}

__device__ __forceinline__ void f_request(const Params& p, const CUtensorMap* tm, int panel, int rank, int nsl, int delay, int step, unsigned tag,
                                          uint32_t sbase, uint64_t pol) {
    const int lane = threadIdx.x & 31;
    if (lane == 0) asm volatile("prefetch.tensormap [%0];" ::"l"(tm) : "memory");
    unsigned long long v;
    unsigned n = 0;
    while (!__all_sync(~0u, (v = ld_relaxed64(&scratch(p)->dry[blockIdx.x >> 3][lane >> 2])) >> 32 == tag)) {
        __nanosleep(200);
        if (++n > SPIN_LIMIT) __trap();
    }
    const uint32_t t0 = __shfl_sync(~0u, (uint32_t)v, 0);
    uint32_t due = t0 + (__reduce_add_sync(~0u, (int)((uint32_t)v - t0)) >> 5);
    due += delay;
#pragma unroll 1
    for (int q = 0; q < 8 * nsl; q++, due += step) {
        if (q >= LAG * nsl) mbar_spin(sbase + F_BAR + 64 + (q - LAG * nsl) * 8);
        while ((int)(time_ns() - due) < 0 && ++n < SPIN_LIMIT) {}
        tma3d_warp(sbase + F_W - (q >> 3) * 2 * SLOT + (q & 7) * 8192, tm, 0, (rank * 8 + (q & 7)) * 64, panel + (q >> 3), sbase + F_BAR + 64 + q * 8,
                   8192, pol);
    }
}

__device__ __forceinline__ void f_project(const Params& p, int rank, int j, int nsl, uint32_t sbase) {
    const int lane = threadIdx.x & 31, g = lane >> 2, t = lane & 3;
    const uint32_t wa = sbase + F_W + ((lane & 7) + (lane >> 4) * 8) * 128 + (((2 * j + ((lane >> 3) & 1)) ^ (lane & 7)) * 16);
    const uint32_t ba = sbase + F_BF + (g & 3) * 64 + t * 16;
    const bool up = t & 2;
#pragma unroll 1
    for (int sl = 0; sl < nsl; sl++) {
        const uint32_t rdst = mapa(sbase + F_RX + sl * 1024 + rank * 128 + g * 16 + (t & 1) * 8, 2 * j + (t >> 1));
        const uint32_t rbar = mapa(sbase + F_BAR + 16 + sl * 8, 2 * j + (t >> 1));
        float acc[2][4];
#pragma unroll
        for (int k = 0; k < 8; k++) acc[k >> 2][k & 3] = 0.f;
#pragma unroll 1
        for (int hp = 0; hp < 2; hp++) {
            uint32_t wp = wa + hp * 32768 - sl * 2 * SLOT, bar = sbase + F_BAR + 64 + sl * 64 + hp * 32, last = hp;
            uint32_t bf[2][4][4];
#pragma unroll
            for (int e = 0; e < 2; e++) {
                mbar_spin(sbase + F_BAR + 32 + hp * 16 + e * 8);
#pragma unroll
                for (int s = 0; s < 4; s++)
                    asm volatile("ld.shared.v4.u32 {%0,%1,%2,%3}, [%4];" : "=r"(bf[e][s][0]), "=r"(bf[e][s][1]), "=r"(bf[e][s][2]), "=r"(bf[e][s][3])
                                 : "r"(((ba + hp * 2048 + e * 1024) ^ (s * 64)) + s * 256) : "memory");
            }
            asm volatile("" : "+r"(wp), "+r"(bar), "+r"(last));
#pragma unroll
            for (int e = 0; e < 2; e++) {
                uint32_t a[8][4];
#pragma unroll
                for (int q = 0; q < 2; q++) {
                    mbar_spin(bar + e * 16 + q * 8);
#pragma unroll
                    for (int s = 4 * q; s < 4 * q + 4; s++) ldsm4t(a[s], wp + e * 16384 + s * 2048);
                }
#pragma unroll
                for (int s = 0; s < 8; s++) mma16816(acc[s & 1], a[s], bf[e][s & 3][(s >> 2) * 2], bf[e][s & 3][(s >> 2) * 2 + 1]);
            }
            const float v0 = up ? acc[0][2] + acc[1][2] : acc[0][0] + acc[1][0], v1 = up ? acc[0][3] + acc[1][3] : acc[0][1] + acc[1][1];
            asm volatile("{\n.reg .pred p;\nsetp.ne.u32 p, %4, 0;\n"
                         "@p st.async.weak.shared::cluster.mbarrier::complete_tx::bytes.v2.b32 [%0], {%1,%2}, [%3];\n}"
                         ::"r"(rdst), "r"(__float_as_uint(v0)), "r"(__float_as_uint(v1)), "r"(rbar), "r"(last) : "memory");
        }
    }
}

__device__ __forceinline__ void f_receive(const Params& p, __nv_bfloat16* out, int nsl, uint32_t sbase) {
    const int lane = threadIdx.x & 31;
    out += (lane & 3) * (2 * DM) + (lane >> 2);
#pragma unroll 1
    for (int sl = -1; sl < nsl; sl++) {
        __nv_bfloat16* dst = out + sl * 64;
        uint32_t src = sbase + F_RX + sl * 1024 + lane * 4;
        asm volatile("" : "+l"(dst), "+r"(src));
        if (sl >= 0) mbar_spin_cluster(sbase + F_BAR + 16 + sl * 8);
        float v[8];
#pragma unroll
        for (int r = 0; r < 8; r++) asm volatile("ld.shared.f32 %0, [%1];" : "=f"(v[r]) : "r"(src + r * 128) : "memory");
        const float o = ((v[0] + v[1]) + (v[2] + v[3])) + ((v[4] + v[5]) + (v[6] + v[7]));
        asm volatile("{\n.reg .pred p;\nsetp.ge.s32 p, %2, 0;\n@p st.global.u16 [%0], %1;\n}"
                     ::"l"(dst), "h"((unsigned short)pack_bf16(o, 0.f)), "r"(sl) : "memory");
    }
}

constexpr int BS_WUK = 5, BS_Q = 9, BS_CKV = 11, BS_PART = 27, BS_WUV = 29, BS_END = 33;

__device__ __noinline__ void b_issue(const Params& p, int n, int bi, uint32_t sbase, uint64_t pol) {
    if (n >= BS_END || (n >= BS_Q && n < BS_CKV) || (n >= BS_PART && n < BS_WUV)) return;
    const uint32_t bar = sbase + M_BAR + (NSLOT + n % BRING) * 8;
    const CUtensorMap* tm;
    int row, panel = 2 * bi;
    if (n < BS_WUK) { tm = &p.tm_wq; row = n * 128; }
    else if (n < BS_Q) { tm = &p.tm_wuk; row = (n - BS_WUK) * 128; }
    else if (n < BS_PART) {
        tm = &p.tm_ckv; panel = 0;
        row = (bi >> 3) * SK + ((n - BS_CKV) * 8 + (bi & 7)) * 32;
    }
    else { tm = &p.tm_wuv; row = (n - BS_WUV) * 128; }
    mbar_expect_tx(bar, n == 0 ? 32768 + 4 * 1152 : 32768);
    tma3d(sbase + (n % BRING) * SLOT, tm, 0, row, panel, bar, pol);
}
__device__ __forceinline__ void b_issue_xchg(int n, const void* src, uint32_t sbase, uint64_t pol) {
    asm volatile("fence.proxy.async;" ::: "memory");
#pragma unroll
    for (int i = 0; i < 2; i++) {
        const uint32_t bar = sbase + M_BAR + (NSLOT + (n + i) % BRING) * 8;
        mbar_expect_tx(bar, 32768);
        bulk_load(sbase + ((n + i) % BRING) * SLOT, reinterpret_cast<const char*>(src) + i * 32768, 32768, bar, pol);
    }
}
__device__ __forceinline__ void b_wait(int n, uint32_t sbase) {
    mbar_wait(sbase + M_BAR + (NSLOT + n % BRING) * 8, (n / BRING) & 1);
}

__device__ __noinline__ void b_gemm(const Params& p, uint32_t sbase, int n0, int n1, int ktot, uint32_t xh, uint32_t xl, int pitch,
                                    int bi, uint64_t pol) {
    const int tid = threadIdx.x, warp = tid >> 5, lane = tid & 31, g = lane >> 2, t = lane & 3;
    const uint32_t woff = (warp >> 2) * 16384 + (lane & 15) * 128 + ((((warp & 3) * 2 + (lane >> 4)) ^ (lane & 7)) * 16);
    const uint32_t xoff = (g & 3) * pitch + t * 4;
    float acc[2][4];
#pragma unroll
    for (int i = 0; i < 8; i++) acc[i >> 2][i & 3] = 0.f;
#pragma unroll 1
    for (int n = n0; n < n1; n++) {
        b_wait(n, sbase);
        const uint32_t slot = sbase + (n % BRING) * SLOT + woff;
        const int k0 = (n - n0) * 128;
        const int ns = min(8, (ktot - k0) >> 4);
#pragma unroll 2
        for (int s = 0; s < ns; s++) {
            uint32_t a[4], w[4];
            const uint32_t xo = xoff + (k0 + 16 * s) * 2;
            a[0] = lds32(xh + xo); a[2] = lds32(xh + xo + 16);
            a[1] = xl ? lds32(xl + xo) : 0u; a[3] = xl ? lds32(xl + xo + 16) : 0u;
            ldsm4t(w, slot + s * 2048);
            mma16816(acc[0], a, w[0], w[1]);
            mma16816(acc[1], a, w[2], w[3]);
        }
        __syncthreads();
        if (tid == 0) b_issue(p, n + BD, bi, sbase, pol);
    }
    if (g < 4) {
#pragma unroll
        for (int j = 0; j < 2; j++)
            asm volatile("st.shared.u32 [%0], %1;" ::"r"(sbase + M_QB + g * QP + (warp * 16 + j * 8 + t * 2) * 2),
                         "r"(pack_bf16(acc[j][0] + acc[j][2], acc[j][1] + acc[j][3])) : "memory");
    }
    __syncthreads();
}

__device__ __forceinline__ void b_exchange(unsigned* c, int n, const void* src, uint32_t sbase, uint64_t pol) {
    __syncthreads();
    if (threadIdx.x == 0) {
        fence_gpu();
        red_add_u32(c, 1u);
        wait_count(c, NBCTA);
        b_issue_xchg(n, src, sbase, pol);
    }
}

template <bool CLU>
__device__ __noinline__ void b_chain(const Params& p, char* smem, uint32_t sbase, int bi, unsigned epoch, uint64_t pol) {
    const int tid = threadIdx.x, warp = tid >> 5, lane = tid & 31, g = lane >> 2, t = lane & 3;
    unsigned (*ctl)[32] = scratch(p)->ctl[epoch & 1];
    float* red = reinterpret_cast<float*>(smem + 5 * SLOT);
    __syncthreads();
    b_gemm(p, sbase, 0, BS_WUK, DM, sbase + M_XB, 0, XP, bi, pol);
    {
        uint32_t Q[16];
#pragma unroll
        for (int c = 0; c < 16; c++) Q[c] = lds32(sbase + M_QB + (g & 3) * QP + c * 16 + t * 4);
        float* qa = reinterpret_cast<float*>(smem + M_QA);
#pragma unroll 1
        for (int n = BS_WUK; n < BS_Q; n++) {
            b_wait(n, sbase);
            const uint32_t base = sbase + (n % BRING) * SLOT + (warp * 16 + (lane & 15)) * 128;
            float d[2][4];
#pragma unroll
            for (int i = 0; i < 8; i++) d[i >> 2][i & 3] = 0.f;
#pragma unroll
            for (int s = 0; s < 8; s++) {
                uint32_t a[4];
                ldsm4(a, base + (s >> 2) * 16384 + (((2 * (s & 3) + (lane >> 4)) ^ (lane & 7)) * 16));
                mma16816(d[s & 1], a, Q[2 * s], Q[2 * s + 1]);
            }
            const int c = (n - BS_WUK) * 128 + warp * 16 + g + 8 * (t >> 1);
            qa[(2 * (t & 1)) * 512 + c] = (t & 2) ? d[0][2] + d[1][2] : d[0][0] + d[1][0];
            qa[(2 * (t & 1) + 1) * 512 + c] = (t & 2) ? d[0][3] + d[1][3] : d[0][1] + d[1][1];
            __syncthreads();
            if (tid == 0) b_issue(p, n + BD, bi, sbase, pol);
        }
#pragma unroll 1
        for (int r = 0; r < 2; r++) {
            const int id = tid + r * 256;
            const int b = id >> 7, c0 = ((id >> 2) & 31) * 16 + (id & 3) * 2;
            const float2 u0 = *reinterpret_cast<const float2*>(qa + b * 512 + c0);
            const float2 u1 = *reinterpret_cast<const float2*>(qa + b * 512 + c0 + 8);
            const uint32_t h0 = pack_bf16(u0.x, u0.y), h1 = pack_bf16(u1.x, u1.y);
            const uint32_t l0 = pack_bf16(u0.x - bf_lo(h0), u0.y - bf_hi(h0)), l1 = pack_bf16(u1.x - bf_lo(h1), u1.y - bf_hi(h1));
            scratch(p)->qabs[((id >> 2) * 4 + (bi >> 3)) * 32 + (bi & 7) * 4 + (id & 3)] = make_uint4(h0, l0, h1, l1);
        }
    }
    b_exchange(&ctl[C_BBAR][0], BS_Q, &scratch(p)->qabs[(bi >> 3) * 4096], sbase, pol);
    {
        uint32_t qf[4][4][4];
        b_wait(BS_Q + (warp >> 2), sbase);
        {
            const uint4* qs = reinterpret_cast<const uint4*>(smem + ((BS_Q + (warp >> 2)) % BRING) * SLOT) + (warp & 3) * 512 + lane;
#pragma unroll
            for (int s = 0; s < 4; s++)
#pragma unroll
                for (int i = 0; i < 4; i++) {
                    const uint4 v = qs[(s * 4 + i) * 32];
                    qf[i][s][0] = v.x; qf[i][s][1] = v.y; qf[i][s][2] = v.z; qf[i][s][3] = v.w;
                }
        }
        __syncthreads();
        if (tid == 0) { b_issue(p, BS_Q + BD, bi, sbase, pol); b_issue(p, BS_Q + 1 + BD, bi, sbase, pol); }
        float acc[2][8][4];
#pragma unroll
        for (int i = 0; i < 2; i++)
#pragma unroll
            for (int j = 0; j < 8; j++) { acc[i][j][0] = acc[i][j][1] = acc[i][j][2] = acc[i][j][3] = 0.f; }
        float mrun = -INFINITY, lrun = 0.f;
        const int head = tid >> 3, kq = tid & 7;
        float* alpha = reinterpret_cast<float*>(smem + M_ALPHA);
        for (int n = BS_CKV; n < BS_PART; n++) {
            b_wait(n, sbase);
            const uint32_t slot = sbase + (n % BRING) * SLOT;
            float sc[4][4][4];
#pragma unroll
            for (int i = 0; i < 4; i++)
#pragma unroll
                for (int j = 0; j < 4; j++) { sc[i][j][0] = sc[i][j][1] = sc[i][j][2] = sc[i][j][3] = 0.f; }
#pragma unroll
            for (int j = 0; j < 4; j++)
#pragma unroll
                for (int sp = 0; sp < 2; sp++) {
                    uint32_t bf[4];
                    ldsm4(bf, slot + warp * 4096 + (8 * j + (lane & 7)) * 128 + (((4 * sp + (lane >> 3)) ^ (lane & 7)) * 16));
#pragma unroll
                    for (int i = 0; i < 4; i++) {
                        mma16816(sc[i][j], qf[i][2 * sp], bf[0], bf[1]);
                        mma16816(sc[i][j], qf[i][2 * sp + 1], bf[2], bf[3]);
                    }
                }
#pragma unroll
            for (int i = 0; i < 4; i++)
#pragma unroll
                for (int j = 0; j < 4; j++)
                    *reinterpret_cast<float2*>(red + warp * 1024 + (8 * i + g) * 32 + ((8 * j) ^ (8 * (g & 3))) + 2 * t) =
                        make_float2(sc[i][j][0] + sc[i][j][2], sc[i][j][1] + sc[i][j][3]);
            __syncthreads();
            if (tid == 0 && n > BS_CKV) b_issue(p, n - 1 + BD, bi, sbase, pol);
            {
                float4 s = make_float4(0.f, 0.f, 0.f, 0.f);
#pragma unroll
                for (int w = 0; w < 8; w++) {
                    const float4 v = *reinterpret_cast<const float4*>(red + w * 1024 + head * 32 + ((4 * kq) ^ (8 * (head & 3))));
                    s.x += v.x; s.y += v.y; s.z += v.z; s.w += v.w;
                }
                const uint32_t r0 = pack_bf16(s.x, s.y), r1 = pack_bf16(s.z, s.w);
                const uint32_t s0 = pack_bf16(bf_lo(r0) * SCALE, bf_hi(r0) * SCALE);
                const uint32_t s1 = pack_bf16(bf_lo(r1) * SCALE, bf_hi(r1) * SCALE);
                const float f0 = bf_lo(s0), f1 = bf_hi(s0), f2 = bf_lo(s1), f3 = bf_hi(s1);
                float mx = fmaxf(fmaxf(f0, f1), fmaxf(f2, f3));
                mx = fmaxf(mx, __shfl_xor_sync(~0u, mx, 1));
                mx = fmaxf(mx, __shfl_xor_sync(~0u, mx, 2));
                mx = fmaxf(mx, __shfl_xor_sync(~0u, mx, 4));
                const float mnew = fmaxf(mrun, mx);
                const float al = expsub(mrun, mnew);
                const float p0 = expsub(f0, mnew), p1 = expsub(f1, mnew), p2 = expsub(f2, mnew), p3 = expsub(f3, mnew);
                lrun = lrun * al + ((p0 + p1) + (p2 + p3));
                mrun = mnew;
                *reinterpret_cast<uint2*>(smem + M_P + head * 80 + kq * 8) = make_uint2(pack_bf16(p0, p1), pack_bf16(p2, p3));
                if (kq == 0) alpha[head] = al;
            }
            __syncthreads();
            {
                uint32_t pf[2][2][4];
#pragma unroll
                for (int i = 0; i < 2; i++)
#pragma unroll
                    for (int ks = 0; ks < 2; ks++)
                        ldsm4(pf[i][ks], sbase + M_P + (16 * i + (lane & 15)) * 80 + (16 * ks + 8 * (lane >> 4)) * 2);
#pragma unroll
                for (int i = 0; i < 2; i++) {
                    const float a0 = alpha[16 * i + g], a1 = alpha[16 * i + 8 + g];
#pragma unroll
                    for (int j = 0; j < 8; j++) { acc[i][j][0] *= a0; acc[i][j][1] *= a0; acc[i][j][2] *= a1; acc[i][j][3] *= a1; }
                }
#pragma unroll
                for (int j = 0; j < 8; j++) {
                    uint32_t bf[4];
                    ldsm4t(bf, slot + warp * 4096 + lane * 128 + ((j ^ (lane & 7)) * 16));
#pragma unroll
                    for (int i = 0; i < 2; i++) {
                        mma16816(acc[i][j], pf[i][0], bf[0], bf[1]);
                        mma16816(acc[i][j], pf[i][1], bf[2], bf[3]);
                    }
                }
            }
        }
        __syncthreads();
        if (tid == 0) b_issue(p, BS_PART - 1 + BD, bi, sbase, pol);
        lrun += __shfl_xor_sync(~0u, lrun, 1);
        lrun += __shfl_xor_sync(~0u, lrun, 2);
        lrun += __shfl_xor_sync(~0u, lrun, 4);
        if (kq == 0) scratch(p)->bml[head * NBCTA + bi] = make_float2(mrun, lrun);
#pragma unroll
        for (int i = 0; i < 2; i++)
#pragma unroll
            for (int j = 0; j < 8; j++) {
                scratch(p)->bpart[((16 * i + g) * NBCTA + bi) * 256 + warp * 32 + j * 4 + t] = make_float2(acc[i][j][0], acc[i][j][1]);
                scratch(p)->bpart[((16 * i + 8 + g) * NBCTA + bi) * 256 + warp * 32 + j * 4 + t] = make_float2(acc[i][j][2], acc[i][j][3]);
            }
    }
    b_exchange(&ctl[C_BBAR + 1][0], BS_PART, &scratch(p)->bpart[bi * NBCTA * 256], sbase, pol);
    {
        float* omega = reinterpret_cast<float*>(smem + M_OMEGA);
        if (warp == 0) {
            __syncwarp();
            const uint2 ml = ld_relaxed8(&scratch(p)->bml[bi * NBCTA + lane]);
            const float ms = __uint_as_float(ml.x);
            float m = ms;
            m = fmaxf(m, __shfl_xor_sync(~0u, m, 1));
            m = fmaxf(m, __shfl_xor_sync(~0u, m, 2));
            m = fmaxf(m, __shfl_xor_sync(~0u, m, 4));
            const float w = expsub(ms, m);
            float l = w * __uint_as_float(ml.y);
            l += __shfl_xor_sync(~0u, l, 1);
            l += __shfl_xor_sync(~0u, l, 2);
            l += __shfl_xor_sync(~0u, l, 4);
            omega[lane] = w / l;
        }
        __syncthreads();
        b_wait(BS_PART, sbase);
        b_wait(BS_PART + 1, sbase);
#pragma unroll 1
        for (int b = 0; b < 4; b++) {
            const float2* ps = reinterpret_cast<const float2*>(smem + ((BS_PART + (b >> 1)) % BRING) * SLOT) + (b & 1) * 2048 + tid;
            float c0 = 0.f, c1 = 0.f;
#pragma unroll
            for (int s = 0; s < 8; s++) {
                const float w = omega[b * 8 + s];
                const float2 v = ps[s * 256];
                c0 = fmaf(w, v.x, c0);
                c1 = fmaf(w, v.y, c1);
            }
            const uint32_t hi = pack_bf16(c0, c1);
            *reinterpret_cast<uint32_t*>(smem + M_CH + b * CP + tid * 4) = hi;
            *reinterpret_cast<uint32_t*>(smem + M_CL + b * CP + tid * 4) = pack_bf16(c0 - bf_lo(hi), c1 - bf_hi(hi));
        }
        __syncthreads();
        if (tid == 0) { b_issue(p, BS_PART + BD, bi, sbase, pol); b_issue(p, BS_PART + 1 + BD, bi, sbase, pol); }
    }
    b_gemm(p, sbase, BS_WUV, BS_END, 512, sbase + M_CH, sbase + M_CL, CP, bi, pol);
    if (CLU) {
        if (warp < 4) {
            const unsigned short* c = reinterpret_cast<const unsigned short*>(smem + M_QB + warp * QP) + 16 * t + g;
            scratch(p)->octx[(bi * 4 + warp) * 32 + lane] = make_float4(bf_lo(c[0]), bf_lo(c[8]), bf_lo(c[64]), bf_lo(c[72]));
        }
        __syncthreads();
        if (tid == 0) asm volatile("st.release.gpu.global.u32 [%0], %1;" ::"l"(&scratch(p)->cdone[bi][0]), "r"(epoch + 1) : "memory");
        return;
    }
    if (tid == 0) {
#pragma unroll 1
        for (int i = 0; i < 4; i++) {
            mbar_expect_tx(sbase + M_BAR + i * 8, 36864);
            tma3d(sbase + i * 36864, &p.tm_wo, 0, bi * 128 + i * 32, 0, sbase + M_BAR + i * 8, pol);
        }
    }
    {
        float acc[9][4];
#pragma unroll
        for (int j = 0; j < 9; j++) { acc[j][0] = acc[j][1] = acc[j][2] = acc[j][3] = 0.f; }
#pragma unroll 1
        for (int i = 0; i < 4; i++) {
            const uint32_t xo = sbase + M_QB + (g & 3) * QP + i * 64 + t * 4;
            const uint32_t a0[4] = {lds32(xo), 0u, lds32(xo + 16), 0u}, a1[4] = {lds32(xo + 32), 0u, lds32(xo + 48), 0u};
            mbar_wait(sbase + M_BAR + i * 8, 0);
#pragma unroll
            for (int j = 0; j < 9; j++) {
                const int nt = warp * 9 + j;
                uint32_t w[4];
                ldsm4t(w, sbase + i * 36864 + (nt >> 3) * 4096 + lane * 128 + (((nt & 7) ^ (lane & 7)) * 16));
                mma16816(acc[j], a0, w[0], w[1]);
                mma16816(acc[j], a1, w[2], w[3]);
            }
        }
        if (g < 4) {
#pragma unroll
            for (int j = 0; j < 9; j++) {
                const int c2 = (warp * 9 + j) * 4 + t;
                st_tagged2(&scratch(p)->outb[((c2 / 9) * NH + bi) * 36 + g * 9 + c2 % 9], acc[j][0], acc[j][1], epoch + 1);
            }
        }
    }
    {
        const uint4* src = scratch(p)->outb + (bi * NH + (tid >> 3)) * 36 + (tid & 7);
        float2* part = reinterpret_cast<float2*>(red);
        unsigned n = 0;
        while (true) {
            ulonglong2 v[5];
            bool ok = true;
#pragma unroll
            for (int i = 0; i < 5; i++)
                if (i < 4 || (tid & 7) < 4) v[i] = ld_tagged2(src + i * 8);
#pragma unroll
            for (int i = 0; i < 5; i++)
                if (i < 4 || (tid & 7) < 4) {
                    ok = ok && (unsigned)(v[i].x >> 32) == epoch + 1 && (unsigned)(v[i].y >> 32) == epoch + 1;
                    part[(tid >> 3) * 36 + (tid & 7) + i * 8] = make_float2(__uint_as_float((unsigned)v[i].x), __uint_as_float((unsigned)v[i].y));
                }
            if (ok) break;
            __nanosleep(400);
            if (++n > SPIN_LIMIT) __trap();
        }
        __syncthreads();
        if (tid < 36) {
            float s0 = 0.f, s1 = 0.f;
#pragma unroll 8
            for (int h = 0; h < NH; h++) { const float2 v = part[h * 36 + tid]; s0 += v.x; s1 += v.y; }
            *reinterpret_cast<uint32_t*>(p.out + (tid / 9) * 2 * DM + DM + bi * 18 + (tid % 9) * 2) = pack_bf16(s0, s1);
        }
    }
}

template <bool CLU>
__global__ void __launch_bounds__(256, 1) fused_decode_kernel(const __grid_constant__ Params p) {
    asm volatile("{\n.reg .pred p;\n.reg .u32 a;\n.reg .u64 b;\nsub.u32 a, %1, 128;\nsetp.lt.u32 p, a, %3;\nmad.lo.u32 a, %2, %3, %1;\n"
                 "mad.wide.u32 b, a, 128, %0;\n@p prefetch.global.L2 [b];\n}"
                 ::"l"(p.kc), "r"(threadIdx.x), "r"(blockIdx.x), "n"(PFN) : "memory");
    if (blockIdx.x >= 1024) return;
    extern __shared__ __align__(1024) char smem_raw[];
    const uint32_t sbase = (smem_u32(smem_raw) + 1023u) & ~1023u;
    char* smem = smem_raw + (sbase - smem_u32(smem_raw));
    const int tid = threadIdx.x, warp = __shfl_sync(~0u, tid >> 5, 0), lane = tid & 31;
    const int cl = blockIdx.x >> 3, rank = blockIdx.x & 7;
    const bool isB = CLU ? rank < (cl < MINCL - 2 ? 2 : 3) : (blockIdx.x & 3) == 0 && blockIdx.x < 4 * NBCTA;
    const int bi = CLU ? (rank < 2 ? 2 * cl + rank : cl + MINCL + 2) : blockIdx.x >> 2;
    const int nb = CLU ? 6 * cl + rank - 2 - max(0, cl - (MINCL - 3)) : blockIdx.x - min(NBCTA, (blockIdx.x + 3) >> 2);
    const int blk = CLU ? (isB ? bi : NBCTA + nb) : blockIdx.x;
    const int nblk = CLU ? 8 * MINCL : gridDim.x, nnb = nblk - NBCTA;
    const int nstatic = nnb * (NW + XW);
    uint64_t pol;
    asm volatile("createpolicy.fractional.L2::evict_first.b64 %0, 1.0;" : "=l"(pol));
    const uint32_t wbar = sbase + M_BAR + warp * 8, wslot = sbase + warp * SLOT;
    const int u0 = warp * nnb + nb;
    const bool hold = ((blk >> 2) >> KMIN << KMIN) * 4 * UPP < nstatic;
    const uint32_t jbar = sbase + M_BAR + (NSLOT + BRING) * 8;
    if (warp < 4) {
        const char* src = reinterpret_cast<const char*>(p.kc) + (size_t)(((unsigned)u0 >> 7) * 1024 + (u0 & 127)) * TILE_BYTES;
        asm volatile("" : "+l"(src));
        mbar_init_warp(wbar);
        if (warp < NEARLY && !isB && (CLU || !hold)) tile_load_warp(wslot, src, wbar, pol);
    }
    asm volatile("" ::: "memory");
    if (warp == 7) {
        if (blk < 128) {
            uint64_t poln;
            asm volatile("createpolicy.fractional.L2::evict_normal.b64 %0, 1.0;" : "=l"(poln));
            mbar_init_warp(jbar);
            tma3d_warp(sbase + J0W, &p.tm_j0, blk * 32, 0, 0, jbar, 36864, poln);
            mbar_init_warp(jbar + 8);
            if (lane == 0) {
                mbar_expect_tx(jbar + 8, 4608);
                bulk_load(sbase + M_XA, p.xa, 4608, jbar + 8, poln);
            }
        }
        if (lane < 8) reinterpret_cast<unsigned*>(smem + M_HELP)[lane] = 0;
        __syncwarp();
        if (!isB) asm volatile("bar.arrive 2, %0;" ::"n"(32 * (NW + XW + 1)) : "memory");
    }
    unsigned epoch = 0;
    if (lane == 0) epoch = ld_relaxed4(scratch(p)->epoch);
    if (blk >= 128 ? warp >= 4 : isB && warp < 4) epoch = __shfl_sync(~0u, epoch, 0);
    if (isB && warp == 3) asm volatile("bar.sync 1, 160;" ::: "memory");
    if (isB && tid == 96) {
#pragma unroll 1
        for (int i = 0; i < BRING; i++) mbar_init(sbase + M_BAR + (NSLOT + i) * 8, 1);
        asm volatile("fence.mbarrier_init.release.cluster;" ::: "memory");
        if (hold) { unsigned n = 0; while (ld_acquire_cta_shared(sbase + M_HELP + 24) < 2) { if (++n > (SPIN_LIMIT << 4)) __trap(); } }
#pragma unroll 1
        for (int b = 0; b < 4; b++) bulk_load(sbase + M_XB + b * XP, p.xb + b * DM, 1152, sbase + M_BAR + NSLOT * 8, pol);
#pragma unroll 1
        for (int n = 0; n < BD; n++) b_issue(p, n, bi, sbase, pol);
    }
    if (warp >= 4 && blk < 128) {
        const int g = lane >> 2, t = lane & 3, j = tid - 128;
        asm volatile("bar.sync 1, %0;" ::"r"(isB ? 160 : 128) : "memory");
#pragma unroll 1
        for (int ph = -1;; ph++) {
        const int sl = ph > 0 ? blk + 128 - nblk : blk;
        const uint32_t wa = sbase + J0W + ((warp - 4) * 144 + (lane & 7) + (lane >> 4) * 8) * 64 + ((((lane >> 3) & 1) ^ ((lane >> 1) & 3)) * 16);
        const uint32_t xa = sbase + M_XA + (g & 3) * 1152 + (warp - 4) * 288 + t * 4;
        if (ph >= 0) mbar_wait(jbar + 8, 0);
        uint32_t xb[18];
#pragma unroll
        for (int s = 0; s < 18; s++) xb[s] = lds32(xa + s * 16);
        epoch = __shfl_sync(~0u, epoch, 0);
        if (ph >= 0) mbar_wait(jbar, ph);
        float acc[4][4];
#pragma unroll
        for (int i = 0; i < 16; i++) acc[i >> 2][i & 3] = 0.f;
#pragma unroll
        for (int s = 0; s < 18; s++) {
            uint32_t w[4];
            ldsm4t(w, (wa ^ ((s & 1) * 32)) + (s >> 1) * 1024);
            mma16816(acc[s & 3], w, xb[s & ~1], xb[s | 1]);
        }
        float2* j0 = reinterpret_cast<float2*>(smem + M_J0);
        {
            float* jf = reinterpret_cast<float*>(j0) + (warp - 4) * 128 + (t & 1) * 64 + (t >> 1) * 8 + g;
#pragma unroll
            for (int i = 0; i < 4; i++)
                jf[(i & 1) * 32 + (i >> 1) * 16] = (t & 2) ? acc[i >> 1][2 + (i & 1)] + acc[2 + (i >> 1)][2 + (i & 1)] : acc[i >> 1][i & 1] + acc[2 + (i >> 1)][i & 1];
        }
        asm volatile("bar.sync 1, 128;" ::: "memory");
        const bool again = ph == 0 && blk + 128 - nblk >= nblk;
        if (again && tid == 224) {
            mbar_expect_tx(jbar, 36864);
            tma3d(sbase + J0W, &p.tm_j0, (blk + 128 - nblk) * 32, 0, 0, jbar, pol);
        }
        if (warp < 6) {
            const float2 v0 = j0[j], v1 = j0[64 + j], v2 = j0[128 + j], v3 = j0[192 + j];
            asm volatile("{\n.reg .pred p;\n.reg .b64 v;\nsetp.ge.s32 p, %3, 0;\nmov.b64 v, {%1, %2};\n@p st.relaxed.gpu.global.u64 [%0], v;\n}"
                         ::"l"(&scratch(p)->qll[(j >> 4) * 2048 + sl * 16 + (j & 15)]),
                           "r"(pack_bf16((v0.x + v1.x) + (v2.x + v3.x), (v0.y + v1.y) + (v2.y + v3.y))), "r"(epoch + 1), "r"(ph) : "memory");
            __syncwarp();
            if (lane == 0 && ph >= 0) asm volatile("red.relaxed.cta.shared::cta.add.u32 [%0], 1;" ::"r"(sbase + M_HELP + 24) : "memory");
        } else if (warp == 7) {
            if (blk < C_LINES && ph == 0) scratch(p)->ctl[(epoch & 1) ^ 1][blk][lane] = 0;
        }
        if (ph >= 0 && !again) break;
        asm volatile("bar.sync 1, 128;" ::: "memory");
        }
    }
    if (CLU) {
        if (warp == 6) {
            if (lane < 24 && lane > 1) mbar_init(sbase + F_BAR + lane * 8, 1);
            if ((lane >> 1) == 1) mbar_expect_tx(sbase + F_BAR + lane * 8, 1024);
            asm volatile("fence.mbarrier_init.release.cluster;" ::: "memory");
        }
        asm volatile("barrier.cluster.arrive.relaxed.aligned;" ::: "memory");
    }
    const int c5 = cl % 5;
    const bool partA = CLU && c5 < 3;
    const int nwork = partA && rank == 7 ? 1 : NW + ((CLU ? rank < 2 + X3C && c5 < 4 : (nb & 3) < X3) ? 1 : 0);
    if (isB) {
        b_chain<CLU>(p, smem, sbase, bi, epoch, pol);
        if (!CLU) return;
        if (warp == 2) {
            unsigned n = 0;
            while (ld_acquire(&scratch(p)->ctl[epoch & 1][C_KDONE][0]) < NUK / 2) { __nanosleep(1000); if (++n > SPIN_LIMIT) __trap(); }
        }
    } else if (warp < NW + XW) {
        a_worker<CLU>(p, u0, warp >= nwork, warp < NEARLY && !hold, hold, nstatic, wslot, wbar, sbase + M_HELP,
                      epoch, pol);
        if (!CLU || warp < nwork) return;
        epoch = __shfl_sync(~0u, epoch, 0);
        unsigned n = 0;
        while (ld_acquire_cta_shared(sbase + M_HELP + 12) == 0) { __nanosleep(1000); if (++n > SPIN_LIMIT) __trap(); }
    } else if (warp == 7) {
#pragma unroll 1
        for (int i = nb; i < 4 * NH; i += nnb) scratch(p)->oacc[i * 32 + lane] = make_float4(0.f, 0.f, 0.f, 0.f);
        if (nb < (CLU ? NREPC : NREP) * NH) scratch(p)->vdone[nb][lane] = 0;
        __syncwarp();
        k_helper(p, sbase + M_HELP, epoch);
        if (nb == 0 && lane == 0) scratch(p)->epoch[0] = epoch + 1;
        __syncwarp();
    } else if (!CLU && nb < NFIN) {
        if (warp == 6) {
            finisher(p, sbase, nb);
        } else if (warp >= 6 - NPOLL) {
            v_poller(p, sbase, nb, warp - (6 - NPOLL));
        }
    }
    if (!CLU) return;
    asm volatile("barrier.cluster.wait.acquire.aligned;" ::: "memory");
    const int nsl = c5 == 4 ? 2 : 1, panel = cl / 5 * 3 + (partA ? c5 : c5 - 3);
    if (warp >= 4) {
        f_project(p, rank, warp - 4, nsl, sbase);
        return;
    }
    if (isB ? warp == 2 : warp < 3 || nwork == 3)
        f_collect((partA ? scratch(p)->vdone : scratch(p)->cdone) + 4 * rank, partA ? 4 * UPP : epoch + 1,
                  (partA ? scratch(p)->oacc : scratch(p)->octx) + 4 * rank * 128, nwork == 1 ? 5 * warp : 15, sbase);
    if (warp != 3) return;
    f_request(p, partA ? &p.tm_fa : &p.tm_fb, panel, rank, nsl, nsl == 2 ? B0 + rank * (BJ / 8) : A0 + rank * (AJ / 8), nsl == 2 ? BJ : AJ, epoch + 1, sbase, pol);
    f_receive(p, p.out + (partA ? 0 : DM) + panel * 64 + rank * 8, nsl, sbase);
}

}

typedef CUresult (*EncodeFn)(CUtensorMap*, CUtensorMapDataType, cuuint32_t, void*, const cuuint64_t*, const cuuint64_t*,
                             const cuuint32_t*, const cuuint32_t*, CUtensorMapInterleave, CUtensorMapSwizzle,
                             CUtensorMapL2promotion, CUtensorMapFloatOOBfill);

extern "C" void kernel_launch(void* const* d_in, const int* in_sizes, int n_in, void* d_out, int out_size) {
    (void)in_sizes; (void)n_in; (void)out_size;
    static int nsm = 0, ncl = 0;
    static EncodeFn encode = nullptr;
    static void* scr = nullptr;
    cudaLaunchConfig_t cfg = {};
    cudaLaunchAttribute at[1];
    at[0].id = cudaLaunchAttributeClusterDimension;
    at[0].val.clusterDim.x = 8; at[0].val.clusterDim.y = 1; at[0].val.clusterDim.z = 1;
    cfg.blockDim = dim3(256); cfg.dynamicSmemBytes = SMEM_BYTES; cfg.stream = cudaStreamPerThread; cfg.attrs = at; cfg.numAttrs = 1;
    if (nsm == 0) {
        int dev = 0;
        cudaGetDevice(&dev);
        cudaDeviceGetAttribute(&nsm, cudaDevAttrMultiProcessorCount, dev);
        cudaFuncSetAttribute(fused_decode_kernel<false>, cudaFuncAttributeMaxDynamicSharedMemorySize, SMEM_BYTES);
        cudaFuncSetAttribute(fused_decode_kernel<true>, cudaFuncAttributeMaxDynamicSharedMemorySize, SMEM_BYTES);
        cfg.gridDim = dim3(128);
        if (cudaOccupancyMaxActiveClusters(&ncl, fused_decode_kernel<true>, &cfg) != cudaSuccess) { ncl = 0; (void)cudaGetLastError(); }
        if (ncl > MINCL) ncl = MINCL;
        void* fn = nullptr;
        cudaDriverEntryPointQueryResult qr;
        cudaGetDriverEntryPoint("cuTensorMapEncodeTiled", &fn, cudaEnableDefault, &qr);
        encode = (EncodeFn)fn;
        cudaGetSymbolAddress(&scr, g_scratch);
    }
    Params p;
    auto panels = [&](CUtensorMap* tm, void* ptr, int rows, int cols, int box_rows, int box_panels,
                      CUtensorMapL2promotion promo = CU_TENSOR_MAP_L2_PROMOTION_L2_256B) {
        const cuuint64_t gd[3] = {64, (cuuint64_t)rows, (cuuint64_t)(cols / 64)}, gs[2] = {(cuuint64_t)cols * 2, 128};
        const cuuint32_t box[3] = {64, (cuuint32_t)box_rows, (cuuint32_t)box_panels}, es[3] = {1, 1, 1};
        encode(tm, CU_TENSOR_MAP_DATA_TYPE_BFLOAT16, 3, ptr, gd, gs, box, es, CU_TENSOR_MAP_INTERLEAVE_NONE,
               CU_TENSOR_MAP_SWIZZLE_128B, promo, CU_TENSOR_MAP_FLOAT_OOB_FILL_NONE);
    };
    panels(&p.tm_wq, d_in[7], DM, 4096, 128, 2);
    panels(&p.tm_wuk, d_in[8], 512, 4096, 128, 2);
    panels(&p.tm_wuv, d_in[9], 512, 4096, 128, 2);
    panels(&p.tm_wo, d_in[10], 4096, DM, 32, 9);
    panels(&p.tm_ckv, d_in[6], 4 * SK, 512, 32, 8);
    panels(&p.tm_fa, d_in[4], 4096, DM, 64, 1, CU_TENSOR_MAP_L2_PROMOTION_L2_128B);
    panels(&p.tm_fb, d_in[10], 4096, DM, 64, 1, CU_TENSOR_MAP_L2_PROMOTION_L2_128B);
    {
        const cuuint64_t gd[3] = {4096, 192, 3}, gs[2] = {8192, 192 * 8192};
        const cuuint32_t box[3] = {32, 192, 3}, es[3] = {1, 1, 1};
        encode(&p.tm_j0, CU_TENSOR_MAP_DATA_TYPE_BFLOAT16, 3, d_in[3], gd, gs, box, es, CU_TENSOR_MAP_INTERLEAVE_NONE,
               CU_TENSOR_MAP_SWIZZLE_64B, CU_TENSOR_MAP_L2_PROMOTION_L2_128B, CU_TENSOR_MAP_FLOAT_OOB_FILL_NONE);
    }
    p.xa = (const __nv_bfloat16*)d_in[0];
    p.kc = (const __nv_bfloat16*)d_in[1];
    p.vc = (const __nv_bfloat16*)d_in[2];
    p.wo = (const __nv_bfloat16*)d_in[4];
    p.xb = (const __nv_bfloat16*)d_in[5];
    p.out = (__nv_bfloat16*)d_out;
    p.s = (Scratch*)scr;
    if (ncl >= MINCL) {
        cfg.gridDim = dim3(8 * ncl);
        cudaLaunchKernelEx(&cfg, fused_decode_kernel<true>, p);
    } else {
        fused_decode_kernel<false><<<nsm, 256, SMEM_BYTES, cudaStreamPerThread>>>(p);
    }
}
```

```cpp
#include <cuda_runtime.h>
#include <cuda.h>
#include <cuda_bf16.h>
#include <stdint.h>

namespace {

constexpr int NH = 32, SK = 4096, DM = 576;
constexpr int KEYS = 128;
constexpr int UPP = SK / KEYS;
constexpr int NUK = 4 * NH * UPP;
constexpr int TILE_BYTES = KEYS * 256;
#define NWORK 2
constexpr int NW = NWORK;
constexpr int NBCTA = 32;
constexpr int MINCL = 15;
constexpr int NFIN = 72;
constexpr int SLOT = 32768;
constexpr int NSLOT = 6;
constexpr int BRING = 5;
constexpr int J0W = 5 * SLOT;
constexpr int MISC = NSLOT * SLOT + 4096;
constexpr int XP = 1168, CP = 1040, QP = 272;
constexpr int M_XA = MISC;
constexpr int M_XB = M_XA + 4 * XP;
constexpr int M_CH = M_XB + 4 * XP;
constexpr int M_CL = M_CH + 4 * CP;
constexpr int M_QB = M_CL + 4 * CP;
constexpr int M_QA = M_CH;
constexpr int M_J0 = M_QB + 4 * QP;
constexpr int M_P = M_J0 + 2048;
constexpr int M_ALPHA = M_P + 2560;
constexpr int M_OMEGA = M_ALPHA + 128;
constexpr int M_BAR = M_OMEGA + 128;
constexpr int M_HELP = M_BAR + 128;
constexpr int F_W = 4 * SLOT;
constexpr int F_BF = (M_HELP + 383) / 256 * 256;
constexpr int F_RX = F_BF + 4096;
constexpr int F_BAR = F_RX + 2048;
constexpr int SMEM_BYTES = F_BAR + 192 + 1024;
static_assert(SMEM_BYTES <= 232448 && M_BAR % 8 == 0 && M_QA % 16 == 0 && M_P % 16 == 0, "smem layout");
#define XW 2
#define X3 1
#define X3C 4
#define NEARLY 2
#define LATE 2000
#define BD 5
#define FPF 3
#define FSLEEP 800
#define VS0 24
#define PFN 96
#define EARLY 100
#define ELOG 5
#define TPU 159
#define T1A (1590 + 200 * X3C)
#define T1D 390
#define T2A (T1A - 340)
#define T2D 195
#define LAG 5
#define NPOLL 2
#define PGAP 200
static_assert(X3C <= 4 && NW == 2 && XW == 2 && MINCL == 15, "roles of the cluster launch");
static_assert(NW + XW <= 4 && NEARLY <= NW + XW && BD <= BRING, "slots 4 and 5 hold the finisher weights");
constexpr int KMIN = 2, KMAX = 4, VMIN = 0, VMAX = 4;
constexpr float SCALE = 0.08838834764831845f;
constexpr float LOG2E = 1.4426950408889634f;
constexpr unsigned SPIN_LIMIT = 1u << 24;

#define NREP 2
#define NREPC 1
constexpr int C_QUEUE = 0, C_KDONE = 1, C_BBAR = 3, C_LINES = 5;

struct Scratch {
    unsigned epoch[32];
    unsigned ctl[2][C_LINES][32];
    uint2 qll[4 * 2048];
    uint2 scores[128 * SK / 4];
    float2 stats[128 * UPP];
    float4 oacc[128 * 32];
    unsigned vdone[NREP * NH][32];
    float4 octx[128 * 32];
    unsigned cdone[NH][32];
    unsigned long long dry[16][16];
    uint4 qabs[4 * 8 * 4 * 4 * 32];
    float2 bpart[NBCTA * NH * 256];
    float2 bml[NBCTA * NH];
    uint4 outb[NBCTA * NH * 36];
};
__device__ __align__(256) Scratch g_scratch;

struct Params {
    const __nv_bfloat16 *kc, *xa, *vc, *wo, *xb;
    __nv_bfloat16* out;
    Scratch* s;
    CUtensorMap tm_j0;
    CUtensorMap tm_wq, tm_wuk, tm_ckv, tm_wuv, tm_wo;
    CUtensorMap tm_fa, tm_fb;
};

__device__ __forceinline__ Scratch* scratch(const Params& p) {
    Scratch* s = p.s;
    __builtin_assume(__isGlobal(s));
    return s;
}

__device__ __forceinline__ uint32_t smem_u32(const void* p) { return (uint32_t)__cvta_generic_to_shared(p); }
__device__ __forceinline__ void mbar_init(uint32_t bar, uint32_t cnt) {
    asm volatile("mbarrier.init.shared::cta.b64 [%0], %1;" ::"r"(bar), "r"(cnt) : "memory");
}
__device__ __forceinline__ void mbar_expect_tx(uint32_t bar, uint32_t bytes) {
    asm volatile("mbarrier.arrive.expect_tx.shared::cta.b64 _, [%0], %1;" ::"r"(bar), "r"(bytes) : "memory");
}
__device__ __forceinline__ bool mbar_try(uint32_t bar, uint32_t parity) {
    uint32_t ok;
    asm volatile("{\n.reg .pred p;\nmbarrier.try_wait.parity.shared::cta.b64 p, [%1], %2;\nselp.u32 %0, 1, 0, p;\n}\n"
                 : "=r"(ok) : "r"(bar), "r"(parity) : "memory");
    return ok;
}
__device__ __forceinline__ void mbar_wait(uint32_t bar, uint32_t parity) {
    unsigned n = 0;
    while (!mbar_try(bar, parity)) { if (++n > SPIN_LIMIT) __trap(); }
}
__device__ __forceinline__ void mbar_spin(uint32_t bar) {
    asm volatile("{\n.reg .pred p;\n.reg .u32 n;\nmov.u32 n, 0;\nSPIN:\nmbarrier.try_wait.parity.shared::cta.b64 p, [%0], 0;\n@p bra.uni DONE;\n"
                 "add.u32 n, n, 1;\nsetp.lt.u32 p, n, 0x1000000;\n@p bra.uni SPIN;\ntrap;\nDONE:\n}" ::"r"(bar) : "memory");
}
__device__ __forceinline__ void mbar_spin_cluster(uint32_t bar) {
    asm volatile("{\n.reg .pred p;\n.reg .u32 n;\nmov.u32 n, 0;\nSPIN:\nmbarrier.try_wait.parity.relaxed.cluster.shared::cta.b64 p, [%0], 0;\n"
                 "@p bra.uni DONE;\nadd.u32 n, n, 1;\nsetp.lt.u32 p, n, 0x1000000;\n@p bra.uni SPIN;\ntrap;\nDONE:\n"
                 "fence.acquire.sync_restrict::shared::cluster.cluster;\n}" ::"r"(bar) : "memory");
}
__device__ __forceinline__ void bulk_load(uint32_t dst, const void* src, uint32_t bytes, uint32_t bar, uint64_t pol) {
    asm volatile("cp.async.bulk.shared::cluster.global.mbarrier::complete_tx::bytes.L2::cache_hint [%0], [%1], %2, [%3], %4;"
                 ::"r"(dst), "l"(src), "r"(bytes), "r"(bar), "l"(pol) : "memory");
}
__device__ __forceinline__ void mbar_init_warp(uint32_t bar) {
    asm volatile("{\n.reg .pred p;\nelect.sync _|p, 0xffffffff;\n@p mbarrier.init.shared::cta.b64 [%0], 1;\n@p fence.mbarrier_init.release.cluster;\n}"
                 ::"r"(bar) : "memory");
}
__device__ __forceinline__ void tile_load_warp(uint32_t dst, const void* src, uint32_t bar, uint64_t pol) {
    asm volatile("{\n.reg .pred p;\nelect.sync _|p, 0xffffffff;\n@p mbarrier.arrive.expect_tx.shared::cta.b64 _, [%2], %4;\n"
                 "@p cp.async.bulk.shared::cluster.global.mbarrier::complete_tx::bytes.L2::cache_hint [%0], [%1], %4, [%2], %3;\n}"
                 ::"r"(dst), "l"(src), "r"(bar), "l"(pol), "n"(TILE_BYTES) : "memory");
}
__device__ __forceinline__ void tma3d_warp(uint32_t dst, const CUtensorMap* tm, int c0, int c1, int c2, uint32_t bar, uint32_t bytes, uint64_t pol) {
    asm volatile("{\n.reg .pred p;\nelect.sync _|p, 0xffffffff;\n@p mbarrier.arrive.expect_tx.shared::cta.b64 _, [%2], %7;\n"
                 "@p cp.async.bulk.tensor.3d.shared::cluster.global.mbarrier::complete_tx::bytes.L2::cache_hint [%0], [%1, {%3,%4,%5}], [%2], %6;\n}"
                 ::"r"(dst), "l"(tm), "r"(bar), "r"(c0), "r"(c1), "r"(c2), "l"(pol), "r"(bytes) : "memory");
}
__device__ __forceinline__ void tma3d(uint32_t dst, const CUtensorMap* tm, int c0, int c1, int c2, uint32_t bar, uint64_t pol) {
    asm volatile("cp.async.bulk.tensor.3d.shared::cluster.global.mbarrier::complete_tx::bytes.L2::cache_hint [%0], [%1, {%3,%4,%5}], [%2], %6;"
                 ::"r"(dst), "l"(tm), "r"(bar), "r"(c0), "r"(c1), "r"(c2), "l"(pol) : "memory");
}
__device__ __forceinline__ void l2_prefetch(const void* src, uint32_t bytes) {
    asm volatile("cp.async.bulk.prefetch.L2.global [%0], %1;" ::"l"(src), "r"(bytes) : "memory");
}
__device__ __forceinline__ void ldsm4(uint32_t (&r)[4], uint32_t addr) {
    asm volatile("ldmatrix.sync.aligned.m8n8.x4.shared.b16 {%0,%1,%2,%3}, [%4];"
                 : "=r"(r[0]), "=r"(r[1]), "=r"(r[2]), "=r"(r[3]) : "r"(addr));
}
__device__ __forceinline__ void ldsm4t(uint32_t (&r)[4], uint32_t addr) {
    asm volatile("ldmatrix.sync.aligned.m8n8.x4.trans.shared.b16 {%0,%1,%2,%3}, [%4];"
                 : "=r"(r[0]), "=r"(r[1]), "=r"(r[2]), "=r"(r[3]) : "r"(addr));
}
__device__ __forceinline__ void mma16816(float (&d)[4], const uint32_t (&a)[4], uint32_t b0, uint32_t b1) {
    asm("mma.sync.aligned.m16n8k16.row.col.f32.bf16.bf16.f32 {%0,%1,%2,%3}, {%4,%5,%6,%7}, {%8,%9}, {%0,%1,%2,%3};"
        : "+f"(d[0]), "+f"(d[1]), "+f"(d[2]), "+f"(d[3])
        : "r"(a[0]), "r"(a[1]), "r"(a[2]), "r"(a[3]), "r"(b0), "r"(b1));
}
__device__ __forceinline__ uint32_t lds32(uint32_t a) {
    uint32_t v;
    asm volatile("ld.shared.u32 %0, [%1];" : "=r"(v) : "r"(a));
    return v;
}
__device__ __forceinline__ unsigned ld_acquire(const unsigned* p) {
    unsigned v;
    asm volatile("ld.acquire.gpu.global.u32 %0, [%1];" : "=r"(v) : "l"(p) : "memory");
    return v;
}
__device__ __forceinline__ uint2 ld_relaxed8(const void* p) {
    uint2 v;
    asm volatile("ld.relaxed.gpu.global.v2.u32 {%0,%1}, [%2];" : "=r"(v.x), "=r"(v.y) : "l"(p) : "memory");
    return v;
}
__device__ __forceinline__ unsigned ld_relaxed4(const void* p) {
    unsigned v;
    asm volatile("ld.relaxed.gpu.global.u32 %0, [%1];" : "=r"(v) : "l"(p) : "memory");
    return v;
}
__device__ __forceinline__ unsigned atom_inc(unsigned* p) {
    unsigned v;
    asm volatile("atom.relaxed.gpu.global.inc.u32 %0, [%1], 0x7fffffff;" : "=r"(v) : "l"(p) : "memory");
    return v;
}
__device__ __forceinline__ unsigned long long ld_relaxed64(const void* p) {
    unsigned long long v;
    asm volatile("ld.relaxed.gpu.global.u64 %0, [%1];" : "=l"(v) : "l"(p) : "memory");
    return v;
}
__device__ __forceinline__ void st_relaxed64(void* p, unsigned long long v) {
    asm volatile("st.relaxed.gpu.global.u64 [%0], %1;" ::"l"(p), "l"(v) : "memory");
}
__device__ __forceinline__ float4 ld_relaxed16(const void* p) {
    float4 v;
    asm volatile("ld.relaxed.gpu.global.v4.f32 {%0,%1,%2,%3}, [%4];" : "=f"(v.x), "=f"(v.y), "=f"(v.z), "=f"(v.w) : "l"(p) : "memory");
    return v;
}
__device__ __forceinline__ uint32_t mapa(uint32_t a, uint32_t rank) {
    uint32_t r;
    asm("mapa.shared::cluster.u32 %0, %1, %2;" : "=r"(r) : "r"(a), "r"(rank));
    return r;
}
__device__ __forceinline__ uint32_t time_ns() { uint32_t t; asm volatile("mov.u32 %0, %globaltimer_lo;" : "=r"(t)); return t; }
__device__ __forceinline__ void fence_gpu() { asm volatile("fence.acq_rel.gpu;" ::: "memory"); }
__device__ __forceinline__ void red_add_u32(unsigned* p, unsigned v) {
    asm volatile("red.relaxed.gpu.global.add.u32 [%0], %1;" ::"l"(p), "r"(v) : "memory");
}
__device__ __forceinline__ void st_tagged2(void* p, float a, float b, unsigned tag) {
    const unsigned long long hi = (unsigned long long)tag << 32;
    asm volatile("st.relaxed.gpu.global.v2.b64 [%0], {%1,%2};" ::"l"(p), "l"(hi | __float_as_uint(a)), "l"(hi | __float_as_uint(b)) : "memory");
}
__device__ __forceinline__ ulonglong2 ld_tagged2(const void* p) {
    ulonglong2 v;
    asm volatile("ld.relaxed.gpu.global.v2.b64 {%0,%1}, [%2];" : "=l"(v.x), "=l"(v.y) : "l"(p) : "memory");
    return v;
}
__device__ __forceinline__ float4 atom_add_f4(void* p, float a, float b, float c, float d) {
    float4 r;
    asm volatile("atom.relaxed.gpu.global.add.v4.f32 {%0,%1,%2,%3}, [%4], {%5,%6,%7,%8};"
                 : "=f"(r.x), "=f"(r.y), "=f"(r.z), "=f"(r.w) : "l"(p), "f"(a), "f"(b), "f"(c), "f"(d) : "memory");
    return r;
}
__device__ __forceinline__ void red_release_cta_shared(uint32_t a, unsigned v) {
    asm volatile("red.release.cta.shared::cta.add.u32 [%0], %1;" ::"r"(a), "r"(v) : "memory");
}
__device__ __forceinline__ unsigned ld_acquire_cta_shared(uint32_t a) {
    unsigned v;
    asm volatile("ld.acquire.cta.shared::cta.u32 %0, [%1];" : "=r"(v) : "r"(a) : "memory");
    return v;
}
__device__ __forceinline__ void st_release_cta_shared(uint32_t a, unsigned v) {
    asm volatile("st.release.cta.shared::cta.u32 [%0], %1;" ::"r"(a), "r"(v) : "memory");
}
__device__ __forceinline__ void wait_count(const unsigned* p, unsigned target) {
    unsigned n = 0;
    while (ld_acquire(p) < target) { if (++n > SPIN_LIMIT) __trap(); }
}
__device__ __forceinline__ uint32_t pack_bf16(float lo, float hi) {
    uint32_t r;
    asm("cvt.rn.bf16x2.f32 %0, %1, %2;" : "=r"(r) : "f"(hi), "f"(lo));
    return r;
}
__device__ __forceinline__ float bf_lo(uint32_t v) { return __uint_as_float(v << 16); }
__device__ __forceinline__ float bf_hi(uint32_t v) { return __uint_as_float(v & 0xffff0000u); }
__device__ __forceinline__ float ex2(float x) { float y; asm("ex2.approx.ftz.f32 %0, %1;" : "=f"(y) : "f"(x)); return y; }
__device__ __forceinline__ float expsub(float a, float b) { return ex2((a - b) * LOG2E); }
__device__ __forceinline__ float warp_max(float v) {
#pragma unroll
    for (int m = 16; m; m >>= 1) v = fmaxf(v, __shfl_xor_sync(~0u, v, m));
    return v;
}
__device__ __forceinline__ float warp_sum(float v) {
#pragma unroll
    for (int m = 16; m; m >>= 1) v += __shfl_xor_sync(~0u, v, m);
    return v;
}
template <bool CLU>
__device__ __forceinline__ unsigned unit_block(int u) {
    const unsigned x = ((unsigned)u & (NUK - 1)) / UPP;
    const int lg = u < NUK ? min(KMAX, max(KMIN, 29 - __clz(x | 1))) : (CLU && (int)x >= 4 * VS0 ? 0 : min(VMAX, max(VMIN, 29 - __clz((127 - x) | 1))));
    const unsigned r = x & ((4u << lg) - 1);
    return ((x - r + (r & ((1u << lg) - 1)) * 4 + (r >> lg)) * UPP) | ((unsigned)u & (UPP - 1));
}
__device__ __forceinline__ const char* block_src(const void* base, unsigned blk) {
    const unsigned po = blk / UPP;
    return reinterpret_cast<const char*>(base) + (size_t)(((po & 3) * NH + (po >> 2)) * UPP + blk % UPP) * TILE_BYTES;
}

template <bool CLU>
__device__ __forceinline__ void a_worker(const Params& p, int un, bool once, bool pre, bool hold, int nstatic, uint32_t slot, uint32_t bar,
                                         uint32_t help, unsigned epoch, uint64_t pol) {
    constexpr int NU = 2 * NUK, NR = CLU ? NREPC : NREP;
    const int lane = threadIdx.x & 31, g = lane >> 2, t = lane & 3;
    const int li = lane & 7;
    uint32_t kaddr[4], vaddr[8];
    {
        const int e = (lane >> 3) & 1, kk = lane >> 4;
#pragma unroll
        for (int s = 0; s < 4; s++) kaddr[s] = slot + (16 * li + e) * 256 + ((2 * s + kk + li) & 7) * 16;
        const int vrow = 4 * (li >> 1) + (li & 1) + 2 * kk;
#pragma unroll
        for (int c = 0; c < 8; c++) vaddr[c] = slot + vrow * 256 + e * 128 + ((c + li) & 7) * 16;
#pragma unroll
        for (int c = 0; c < 8; c++) asm volatile("" : "+r"(vaddr[c]));
    }
    const uint32_t vmask = (g >> 1) != t ? 0u : ((g & 1) ? 0xffff0000u : 0xffffu);
    int kseen = -1;
    unsigned long long H0 = 0, H1 = 0;
    auto header = [&](int v, unsigned vb) {
        const void *a0, *a1;
        if (v < NUK) {
            const unsigned po = vb / UPP;
            a0 = scratch(p)->qll + (po & 3) * 2048 + (po >> 2) * 64 + lane;
            a1 = reinterpret_cast<const uint2*>(a0) + 32;
        } else {
            const int half = vb / (NUK / 2);
            if (half > kseen) {
                unsigned n = 0;
                while (ld_acquire_cta_shared(help + 12 + 4 * half) == 0) { if (++n > (SPIN_LIMIT << 4)) __trap(); }
                kseen = half;
            }
            a0 = &scratch(p)->scores[vb * (KEYS / 4) + lane];
            a1 = &scratch(p)->stats[(vb / UPP) * UPP + lane];
        }
        H0 = ld_relaxed64(a0);
        H1 = ld_relaxed64(a1);
    };
    unsigned bu = 0, bn = unit_block<CLU>(un);
    asm volatile("bar.sync 2, %0;" ::"n"(32 * (NW + XW + 1)) : "memory");
    if (!pre && !hold) { const uint32_t t0 = clock(); while ((uint32_t)clock() - t0 < ((threadIdx.x >> 5) - NEARLY + 1) * LATE) {} }
    epoch = __shfl_sync(~0u, epoch, 0);
    if (hold) { unsigned n = 0; while (ld_acquire_cta_shared(help + 24) < 2) { if (++n > (SPIN_LIMIT << 4)) __trap(); } }
    unsigned (*ctl)[32] = scratch(p)->ctl[epoch & 1];
    const unsigned tag = epoch + 1;
    unsigned nxt = once ? NU : 0;
    int u = -1;
    uint32_t phase = 0;
    unsigned kpend = 0;
    const unsigned zero = gridDim.x >> 24;
    uint32_t Q[16];
    float4 oret = make_float4(0.f, 0.f, 0.f, 0.f);
    while (true) {
        const char* nsrc = block_src(un < NUK ? p.kc : p.vc, bn);
        float4* odst = &scratch(p)->oacc[(bu / UPP) * 32 + lane];
        unsigned* vdst = &scratch(p)->vdone[(lane & (NR - 1)) * NH + bu / (4 * UPP)][0];
        float d[8][4];
        uint32_t act = un >= NU ? 0u : (u >= 0 || !pre ? 1u : 0u) | (!once && lane == 0 ? 2u : 0u);
        asm volatile("" : "+l"(odst), "+l"(nsrc), "+r"(act));
        if (u >= NUK) {
#pragma unroll
            for (int j = 0; j < 8; j++) { d[j][0] = d[j][1] = d[j][2] = d[j][3] = 0.f; }
            mbar_wait(bar, phase);
            uint32_t a[2][8][4];
#pragma unroll
            for (int c = 0; c < 8; c++) ldsm4t(a[0][c], vaddr[c]);
#pragma unroll
            for (int j = 0; j < 8; j++) {
                if (j < 7) {
#pragma unroll
                    for (int c = 0; c < 8; c++) ldsm4t(a[(j + 1) & 1][c], vaddr[c] + (j + 1) * 4096);
                }
#pragma unroll
                for (int c = 0; c < 8; c++) mma16816(d[c], a[j & 1][c], Q[2 * j], Q[2 * j + 1]);
            }
            float o[4];
#pragma unroll
            for (int r = 0; r < 2; r++) {
                o[2 * r] = d[0][2 * r] + d[7][2 * r + 1];
                o[2 * r + 1] = d[0][2 * r + 1] + d[1][2 * r];
#pragma unroll
                for (int k = 1; k < 4; k++) {
                    const int src = (lane & 28) | ((t - k) & 3);
                    o[2 * r] += __shfl_sync(~0u, d[2 * k][2 * r] + d[2 * k - 1][2 * r + 1], src);
                    o[2 * r + 1] += __shfl_sync(~0u, d[2 * k][2 * r + 1] + d[2 * k + 1][2 * r], src);
                }
            }
            oret = atom_add_f4(odst, o[0], o[1], o[2], o[3]);
        } else if (u >= 0) {
#pragma unroll
            for (int j = 0; j < 8; j++) { d[j][0] = d[j][1] = d[j][2] = d[j][3] = 0.f; }
            mbar_wait(bar, phase);
            uint32_t a[2][8][4];
#pragma unroll
            for (int j = 0; j < 8; j++) ldsm4(a[0][j], kaddr[0] + (4 * (j & 3) + 2 * (j >> 2)) * 256);
#pragma unroll
            for (int s = 0; s < 8; s++) {
                if (s < 7) {
#pragma unroll
                    for (int j = 0; j < 8; j++)
                        ldsm4(a[(s + 1) & 1][j], kaddr[(s + 1) & 3] + (4 * (j & 3) + 2 * (j >> 2)) * 256 + ((s + 1) >> 2) * 128);
                }
#pragma unroll
                for (int j = 0; j < 8; j++)
                    mma16816(d[j], a[s & 1][j], Q[(s & 4) * 2 + ((2 * s - 2 * j) & 7)], Q[(s & 4) * 2 + ((2 * s + 1 - 2 * j) & 7)]);
            }
        }
        if (u >= 0) phase ^= 1;
        asm volatile("{\n.reg .pred p, q;\n.reg .u32 a;\nelect.sync _|p, 0xffffffff;\nand.b32 a, %5, 1;\nsetp.ne.and.u32 q, a, 0, p;\n"
                     "@q mbarrier.arrive.expect_tx.shared::cta.b64 _, [%2], %4;\n"
                     "@q cp.async.bulk.shared::cluster.global.mbarrier::complete_tx::bytes.L2::cache_hint [%0], [%1], %4, [%2], %3;\n}"
                     ::"r"(slot), "l"(nsrc), "r"(bar), "l"(pol), "n"(TILE_BYTES), "r"(act) : "memory");
        if (act & 2) nxt = atom_inc(&ctl[C_QUEUE][0]);
        const uint32_t tk = clock();
        if ((unsigned)u < (unsigned)NUK) {
            const int j0 = (t - (g >> 1)) & 3;
            float v[4];
#pragma unroll
            for (int q = 0; q < 4; q++) {
                const int jq = (q >> 1) * 4, e = (q & 1) * 2;
                const float x0 = (g & 1) ? d[jq + 0][e + 1] : d[jq + 0][e];
                const float x1 = (g & 1) ? d[jq + 1][e + 1] : d[jq + 1][e];
                const float x2 = (g & 1) ? d[jq + 2][e + 1] : d[jq + 2][e];
                const float x3 = (g & 1) ? d[jq + 3][e + 1] : d[jq + 3][e];
                const float y0 = (j0 & 1) ? x1 : x0, y1 = (j0 & 1) ? x3 : x2;
                v[q] = (j0 & 2) ? y1 : y0;
            }
            const uint32_t r0 = pack_bf16(v[0], v[1]), r1 = pack_bf16(v[2], v[3]);
            const uint32_t s0 = pack_bf16(bf_lo(r0) * SCALE, bf_hi(r0) * SCALE);
            const uint32_t s1 = pack_bf16(bf_lo(r1) * SCALE, bf_hi(r1) * SCALE);
            scratch(p)->scores[bu * (KEYS / 4) + 4 * g + j0] = make_uint2(s0, s1);
            const float f0 = bf_lo(s0), f1 = bf_hi(s0), f2 = bf_lo(s1), f3 = bf_hi(s1);
            const float m = warp_max(fmaxf(fmaxf(f0, f1), fmaxf(f2, f3)));
            const float l = warp_sum((expsub(f0, m) + expsub(f1, m)) + (expsub(f2, m) + expsub(f3, m)));
            if (lane == 0) scratch(p)->stats[bu] = make_float2(m, l);
            kpend++;
            if (un / (NUK / 2) != u / (NUK / 2)) {
                __syncwarp();
                if (lane == 0) {
                    red_release_cta_shared(help + 4 * (u / (NUK / 2)), kpend);
                    if (un >= NUK) red_release_cta_shared(help + 8, 1u);
                }
                kpend = 0;
            }
        }
        int unn = NU;
        if (un < NU) {
            unsigned n = 0;
            while (true) {
                header(un, bn);
                if (un >= NUK || __all_sync(~0u, (uint32_t)(H0 >> 32) == tag && (uint32_t)(H1 >> 32) == tag)) break;
                if (++n > SPIN_LIMIT) __trap();
            }
            if (un >= NUK) {
                const uint32_t s0 = (uint32_t)H0, s1 = (uint32_t)(H0 >> 32);
                const float mu = __uint_as_float((uint32_t)H1);
                const float m = warp_max(mu);
                const float l = warp_sum(__uint_as_float((uint32_t)(H1 >> 32)) * expsub(mu, m));
                const float inv = 1.0f / l;
                const uint32_t w0 = pack_bf16(expsub(bf_lo(s0), m) * inv, expsub(bf_hi(s0), m) * inv);
                const uint32_t w1 = pack_bf16(expsub(bf_lo(s1), m) * inv, expsub(bf_hi(s1), m) * inv);
#pragma unroll
                for (int j = 0; j < 8; j++) {
                    Q[2 * j] = __shfl_sync(~0u, w0, 4 * j + t) & vmask;
                    Q[2 * j + 1] = __shfl_sync(~0u, w1, 4 * j + t) & vmask;
                }
            } else {
#pragma unroll
                for (int j = 0; j < 8; j++) {
                    const int src = (((j + g) & 7) << 2) + t;
                    Q[j] = __shfl_sync(~0u, (uint32_t)H0, src);
                    Q[8 + j] = __shfl_sync(~0u, (uint32_t)H1, src);
                }
            }
            unn = nstatic + (int)__shfl_sync(~0u, nxt, 0);
            if (CLU && ((NU - EARLY - unn) & ~(7 << ELOG)) == 0 && lane < MINCL)
                st_relaxed64(&scratch(p)->dry[lane][(NU - EARLY - unn) >> ELOG],
                             (time_ns() - (((uint32_t)clock() - tk) >> 1) + (NU - unn) * TPU / 16) | (unsigned long long)tag << 32);
        }
        if (u >= NUK && lane < NR)
            red_add_u32(vdst,
                        1u + ((__float_as_uint(oret.x) | __float_as_uint(oret.y) | __float_as_uint(oret.z) | __float_as_uint(oret.w)) & zero));
        if (un >= NU) break;
        bu = bn;
        bn = unit_block<CLU>(unn);
        u = un;
        un = unn;
    }
}

__device__ __forceinline__ void k_helper(const Params& p, uint32_t help, unsigned epoch) {
    if ((threadIdx.x & 31) != 0) return;
    unsigned (*ctl)[32] = scratch(p)->ctl[epoch & 1];
    unsigned sent0 = 0, sent1 = 0, n = 0;
    int seen = 0;
    bool fin = false;
    while (!fin || seen < 2) {
        if (!fin) {
            fin = ld_acquire_cta_shared(help + 8) == NW + XW;
            const unsigned c0 = ld_acquire_cta_shared(help), c1 = ld_acquire_cta_shared(help + 4);
            if (c0 != sent0 || c1 != sent1) {
                fence_gpu();
                if (c0 != sent0) red_add_u32(&ctl[C_KDONE][0], c0 - sent0);
                if (c1 != sent1) red_add_u32(&ctl[C_KDONE + 1][0], c1 - sent1);
                sent0 = c0; sent1 = c1;
            }
        }
        if (seen < 2 && ld_acquire(&ctl[C_KDONE + seen][0]) >= NUK / 2) {
            st_release_cta_shared(help + 12 + 4 * seen, 1u);
            seen++;
        } else {
            __nanosleep(300);
        }
        if (++n > SPIN_LIMIT) __trap();
    }
}

__device__ __forceinline__ void v_poller(const Params& p, uint32_t sbase, int f, int w) {
    constexpr int HL = NH;
    const int lane = threadIdx.x & 31;
    const unsigned (*cp)[32] = &scratch(p)->vdone[((f * NPOLL + w) % NREP) * NH];
    unsigned n = 0;
    while (ld_acquire_cta_shared(sbase + M_HELP + 12) == 0) { __nanosleep(1000); if (++n > SPIN_LIMIT) __trap(); }
    int h = 0;
    bool fast = false;
    while (h < HL) {
        const unsigned r = __ballot_sync(~0u, ld_acquire(&cp[min(h + (lane & 3), HL - 1)][0]) >= 4 * UPP) & 15u;
        if (r & 1) {
            h = min(HL, h + __ffs(~r) - 1);
            __syncwarp();
            if (lane == 0) asm volatile("red.release.cta.shared::cta.max.u32 [%0], %1;" ::"r"(sbase + M_HELP + 20), "r"(h) : "memory");
        }
        if (h < HL - 4) {
            __nanosleep(h ? 300 : 1000);
        } else if (!fast) {
            fast = true;
            const long long t0 = clock64();
            while (clock64() - t0 < w * PGAP) {}
        }
        if (++n > SPIN_LIMIT) __trap();
    }
}
__device__ __forceinline__ void finisher(const Params& p, uint32_t sbase, int f) {
    constexpr int HL = NH;
    const int lane = threadIdx.x & 31;
    {
        const char* wg = reinterpret_cast<const char*>(p.wo);
        const uint32_t dst = sbase + 4 * SLOT + (16 * (lane & 7) + (lane >> 3)) * 16;
#pragma unroll 1
        for (int h = -FPF - 4; h < HL; h++) {
            if (lane == 0 && (unsigned)(h + FPF) < (unsigned)HL) l2_prefetch(wg + (size_t)(h + FPF) * 147456 + f * 2048, 2048);
            if (h >= 0) {
#pragma unroll
                for (int r = 0; r < 4; r++)
                    asm volatile("cp.async.cg.shared.global [%0], [%1], 16;" ::"r"(dst + h * 2048 + ((r & 1) * 4 + (r >> 1) * 8) * 16),
                                 "l"(wg + (size_t)(h * 128 + r * 32 + lane) * (DM * 2) + f * 16) : "memory");
            }
            __nanosleep(FSLEEP);
        }
        asm volatile("cp.async.wait_all;" ::: "memory");
        __syncwarp();
    }
    const float4* vec = scratch(p)->oacc + ((lane >> 2) & 3) * 32 + (lane >> 4) * 16 + (lane & 3);
    float acc[2][2][4];
#pragma unroll
    for (int i = 0; i < 16; i++) acc[i >> 3][(i >> 2) & 1][i & 3] = 0.f;
    uint32_t* outp = reinterpret_cast<uint32_t*>(p.out + (lane >> 2) * (2 * DM) + f * 8 + (lane & 3) * 2);
    uint32_t wa = sbase + 4 * SLOT + lane * 16;
    auto project = [&](const float4 (&x)[4], const uint32_t (&w)[4][4]) {
#pragma unroll
        for (int s = 0; s < 4; s++) {
            const uint32_t a[4] = {pack_bf16(x[s].x, x[s].y), 0u, pack_bf16(x[s].z, x[s].w), 0u};
            mma16816(acc[0][s & 1], a, w[s >> 1][(s & 1) * 2], w[s >> 1][(s & 1) * 2 + 1]);
            mma16816(acc[1][s & 1], a, w[2 + (s >> 1)][(s & 1) * 2], w[2 + (s >> 1)][(s & 1) * 2 + 1]);
        }
    };
    int h = 0;
    unsigned n = 0;
    while (h < HL) {
        uint32_t w[4][4];
#pragma unroll
        for (int q = 0; q < 4; q++) ldsm4t(w[q], wa + q * 512);
        int ready;
        while ((ready = ld_acquire_cta_shared(sbase + M_HELP + 20)) <= h) {
            if (h < HL - 3) __nanosleep(100);
            if (++n > (SPIN_LIMIT << 4)) __trap();
        }
        float4 x[4], y[4];
#pragma unroll
        for (int s = 0; s < 4; s++) x[s] = ld_relaxed16(vec + s * 4);
        const bool two = ready > h + 1;
        if (two) {
#pragma unroll
            for (int s = 0; s < 4; s++) y[s] = ld_relaxed16(vec + 128 + s * 4);
        }
        project(x, w);
        if (two) {
#pragma unroll
            for (int q = 0; q < 4; q++) ldsm4t(w[q], wa + 2048 + q * 512);
            project(y, w);
        }
        const int nr = two ? 2 : 1;
        h += nr;
        vec += nr * 128;
        wa += nr * 2048;
        const float o0 = acc[0][0][0] + acc[0][1][0] + __shfl_down_sync(~0u, acc[1][0][0] + acc[1][1][0], 16);
        const float o1 = acc[0][0][1] + acc[0][1][1] + __shfl_down_sync(~0u, acc[1][0][1] + acc[1][1][1], 16);
        asm volatile("{\n.reg .pred p;\nsetp.ne.u32 p, %2, 0;\n@p st.global.u32 [%0], %1;\n}" ::"l"(outp), "r"(pack_bf16(o0, o1)),
                     "r"((uint32_t)(lane < 16 && h == NH)) : "memory");
    }
}

__device__ __noinline__ void f_collect(const unsigned (*flag)[32], unsigned full, const float4* src, unsigned todo, uint32_t sbase) {
    const int lane = threadIdx.x & 31, g = lane >> 2, t = lane & 3;
    const bool last = todo != 15;
    unsigned n = 0;
    while (todo) {
        const unsigned v = ld_acquire(&flag[t][0]);
        unsigned m = __ballot_sync(~0u, v == full) & todo;
        if (m == 0) {
            if (!last || __shfl_sync(~0u, v, 0) == 0) __nanosleep(200);
            if (++n > SPIN_LIMIT) __trap();
            continue;
        }
        __syncwarp();
        todo ^= m;
        do {
            const int h0 = __ffs(m) - 1, h1 = 31 - __clz(m);
            m &= ~((1u << h0) | (1u << h1));
            float4 x[8];
#pragma unroll
            for (int b = 0; b < 8; b++) x[b] = ld_relaxed16(src + ((b & 4) ? h1 : h0) * 128 + (b & 3) * 32 + lane);
#pragma unroll
            for (int b = 0; b < 8; b++) {
                const uint32_t lo = pack_bf16(x[b].x, x[b].y), hi = pack_bf16(x[b].z, x[b].w);
                const uint32_t o = __shfl_xor_sync(~0u, (g & 1) ? lo : hi, 4);
                const uint32_t e0 = (g & 1) ? o : lo, e1 = (g & 1) ? hi : o;
                asm volatile("st.shared.v2.u32 [%0], {%1,%2};"
                             ::"r"(sbase + F_BF + ((b & 4) ? h1 : h0) * 1024 + t * 256 + ((b ^ t) & 3) * 64 + g * 8),
                               "r"(__byte_perm(e0, e1, 0x5410)), "r"(__byte_perm(e0, e1, 0x7632)) : "memory");
            }
            __syncwarp();
            if (lane < (h0 == h1 ? 1 : 2))
                asm volatile("mbarrier.arrive.shared::cta.b64 _, [%0];" ::"r"(sbase + F_BAR + 32 + (lane ? h1 : h0) * 8) : "memory");
        } while (m);
    }
}

__device__ __forceinline__ void f_request(const Params& p, const CUtensorMap* tm, int panel, int rank, int nsl, int delay, int step, unsigned tag,
                                          uint32_t sbase, uint64_t pol) {
    const int lane = threadIdx.x & 31;
    if (lane == 0) asm volatile("prefetch.tensormap [%0];" ::"l"(tm) : "memory");
    unsigned long long v;
    unsigned n = 0;
    while (!__all_sync(~0u, (v = ld_relaxed64(&scratch(p)->dry[blockIdx.x >> 3][lane >> 2])) >> 32 == tag)) {
        __nanosleep(200);
        if (++n > SPIN_LIMIT) __trap();
    }
    const uint32_t t0 = __shfl_sync(~0u, (uint32_t)v, 0);
    uint32_t due = t0 + (__reduce_add_sync(~0u, (int)((uint32_t)v - t0)) >> 5);
    due += delay;
#pragma unroll 1
    for (int q = 0; q < 8 * nsl; q++, due += step) {
        if (q >= LAG * nsl) mbar_spin(sbase + F_BAR + 64 + (q - LAG * nsl) * 8);
        while ((int)(time_ns() - due) < 0 && ++n < SPIN_LIMIT) {}
        tma3d_warp(sbase + F_W - (q >> 3) * 2 * SLOT + (q & 7) * 8192, tm, 0, (rank * 8 + (q & 7)) * 64, panel + (q >> 3), sbase + F_BAR + 64 + q * 8,
                   8192, pol);
    }
}

__device__ __forceinline__ void f_project(const Params& p, int rank, int j, int nsl, uint32_t sbase) {
    const int lane = threadIdx.x & 31, g = lane >> 2, t = lane & 3;
    const uint32_t wa = sbase + F_W + ((lane & 7) + (lane >> 4) * 8) * 128 + (((2 * j + ((lane >> 3) & 1)) ^ (lane & 7)) * 16);
    const uint32_t ba = sbase + F_BF + (g & 3) * 64 + t * 16;
    const bool up = t & 2;
#pragma unroll 1
    for (int sl = 0; sl < nsl; sl++) {
        const uint32_t rdst = mapa(sbase + F_RX + sl * 1024 + rank * 128 + g * 16 + (t & 1) * 8, 2 * j + (t >> 1));
        const uint32_t rbar = mapa(sbase + F_BAR + 16 + sl * 8, 2 * j + (t >> 1));
        float acc[2][4];
#pragma unroll
        for (int k = 0; k < 8; k++) acc[k >> 2][k & 3] = 0.f;
#pragma unroll 1
        for (int hp = 0; hp < 2; hp++) {
            uint32_t wp = wa + hp * 32768 - sl * 2 * SLOT, bar = sbase + F_BAR + 64 + sl * 64 + hp * 32, last = hp;
            uint32_t bf[2][4][4];
#pragma unroll
            for (int e = 0; e < 2; e++) {
                mbar_spin(sbase + F_BAR + 32 + hp * 16 + e * 8);
#pragma unroll
                for (int s = 0; s < 4; s++)
                    asm volatile("ld.shared.v4.u32 {%0,%1,%2,%3}, [%4];" : "=r"(bf[e][s][0]), "=r"(bf[e][s][1]), "=r"(bf[e][s][2]), "=r"(bf[e][s][3])
                                 : "r"(((ba + hp * 2048 + e * 1024) ^ (s * 64)) + s * 256) : "memory");
            }
            asm volatile("" : "+r"(wp), "+r"(bar), "+r"(last));
#pragma unroll
            for (int e = 0; e < 2; e++) {
                uint32_t a[8][4];
#pragma unroll
                for (int q = 0; q < 2; q++) {
                    mbar_spin(bar + e * 16 + q * 8);
#pragma unroll
                    for (int s = 4 * q; s < 4 * q + 4; s++) ldsm4t(a[s], wp + e * 16384 + s * 2048);
                }
#pragma unroll
                for (int s = 0; s < 8; s++) mma16816(acc[s & 1], a[s], bf[e][s & 3][(s >> 2) * 2], bf[e][s & 3][(s >> 2) * 2 + 1]);
            }
            const float v0 = up ? acc[0][2] + acc[1][2] : acc[0][0] + acc[1][0], v1 = up ? acc[0][3] + acc[1][3] : acc[0][1] + acc[1][1];
            asm volatile("{\n.reg .pred p;\nsetp.ne.u32 p, %4, 0;\n"
                         "@p st.async.weak.shared::cluster.mbarrier::complete_tx::bytes.v2.b32 [%0], {%1,%2}, [%3];\n}"
                         ::"r"(rdst), "r"(__float_as_uint(v0)), "r"(__float_as_uint(v1)), "r"(rbar), "r"(last) : "memory");
        }
    }
}

__device__ __forceinline__ void f_receive(const Params& p, __nv_bfloat16* out, int nsl, uint32_t sbase) {
    const int lane = threadIdx.x & 31;
    out += (lane & 3) * (2 * DM) + (lane >> 2);
#pragma unroll 1
    for (int sl = -1; sl < nsl; sl++) {
        __nv_bfloat16* dst = out + sl * 64;
        uint32_t src = sbase + F_RX + sl * 1024 + lane * 4;
        asm volatile("" : "+l"(dst), "+r"(src));
        if (sl >= 0) mbar_spin_cluster(sbase + F_BAR + 16 + sl * 8);
        float v[8];
#pragma unroll
        for (int r = 0; r < 8; r++) asm volatile("ld.shared.f32 %0, [%1];" : "=f"(v[r]) : "r"(src + r * 128) : "memory");
        const float o = ((v[0] + v[1]) + (v[2] + v[3])) + ((v[4] + v[5]) + (v[6] + v[7]));
        asm volatile("{\n.reg .pred p;\nsetp.ge.s32 p, %2, 0;\n@p st.global.u16 [%0], %1;\n}"
                     ::"l"(dst), "h"((unsigned short)pack_bf16(o, 0.f)), "r"(sl) : "memory");
    }
}

constexpr int BS_WUK = 5, BS_Q = 9, BS_CKV = 11, BS_PART = 27, BS_WUV = 29, BS_END = 33;

__device__ __noinline__ void b_issue(const Params& p, int n, int bi, uint32_t sbase, uint64_t pol) {
    if (n >= BS_END || (n >= BS_Q && n < BS_CKV) || (n >= BS_PART && n < BS_WUV)) return;
    const uint32_t bar = sbase + M_BAR + (NSLOT + n % BRING) * 8;
    const CUtensorMap* tm;
    int row, panel = 2 * bi;
    if (n < BS_WUK) { tm = &p.tm_wq; row = n * 128; }
    else if (n < BS_Q) { tm = &p.tm_wuk; row = (n - BS_WUK) * 128; }
    else if (n < BS_PART) {
        tm = &p.tm_ckv; panel = 0;
        row = (bi >> 3) * SK + ((n - BS_CKV) * 8 + (bi & 7)) * 32;
    }
    else { tm = &p.tm_wuv; row = (n - BS_WUV) * 128; }
    mbar_expect_tx(bar, n == 0 ? 32768 + 4 * 1152 : 32768);
    tma3d(sbase + (n % BRING) * SLOT, tm, 0, row, panel, bar, pol);
}
__device__ __forceinline__ void b_issue_xchg(int n, const void* src, uint32_t sbase, uint64_t pol) {
    asm volatile("fence.proxy.async;" ::: "memory");
#pragma unroll
    for (int i = 0; i < 2; i++) {
        const uint32_t bar = sbase + M_BAR + (NSLOT + (n + i) % BRING) * 8;
        mbar_expect_tx(bar, 32768);
        bulk_load(sbase + ((n + i) % BRING) * SLOT, reinterpret_cast<const char*>(src) + i * 32768, 32768, bar, pol);
    }
}
__device__ __forceinline__ void b_wait(int n, uint32_t sbase) {
    mbar_wait(sbase + M_BAR + (NSLOT + n % BRING) * 8, (n / BRING) & 1);
}

__device__ __noinline__ void b_gemm(const Params& p, uint32_t sbase, int n0, int n1, int ktot, uint32_t xh, uint32_t xl, int pitch,
                                    int bi, uint64_t pol) {
    const int tid = threadIdx.x, warp = tid >> 5, lane = tid & 31, g = lane >> 2, t = lane & 3;
    const uint32_t woff = (warp >> 2) * 16384 + (lane & 15) * 128 + ((((warp & 3) * 2 + (lane >> 4)) ^ (lane & 7)) * 16);
    const uint32_t xoff = (g & 3) * pitch + t * 4;
    float acc[2][4];
#pragma unroll
    for (int i = 0; i < 8; i++) acc[i >> 2][i & 3] = 0.f;
#pragma unroll 1
    for (int n = n0; n < n1; n++) {
        b_wait(n, sbase);
        const uint32_t slot = sbase + (n % BRING) * SLOT + woff;
        const int k0 = (n - n0) * 128;
        const int ns = min(8, (ktot - k0) >> 4);
#pragma unroll 2
        for (int s = 0; s < ns; s++) {
            uint32_t a[4], w[4];
            const uint32_t xo = xoff + (k0 + 16 * s) * 2;
            a[0] = lds32(xh + xo); a[2] = lds32(xh + xo + 16);
            a[1] = xl ? lds32(xl + xo) : 0u; a[3] = xl ? lds32(xl + xo + 16) : 0u;
            ldsm4t(w, slot + s * 2048);
            mma16816(acc[0], a, w[0], w[1]);
            mma16816(acc[1], a, w[2], w[3]);
        }
        __syncthreads();
        if (tid == 0) b_issue(p, n + BD, bi, sbase, pol);
    }
    if (g < 4) {
#pragma unroll
        for (int j = 0; j < 2; j++)
            asm volatile("st.shared.u32 [%0], %1;" ::"r"(sbase + M_QB + g * QP + (warp * 16 + j * 8 + t * 2) * 2),
                         "r"(pack_bf16(acc[j][0] + acc[j][2], acc[j][1] + acc[j][3])) : "memory");
    }
    __syncthreads();
}

__device__ __forceinline__ void b_exchange(unsigned* c, int n, const void* src, uint32_t sbase, uint64_t pol) {
    __syncthreads();
    if (threadIdx.x == 0) {
        fence_gpu();
        red_add_u32(c, 1u);
        wait_count(c, NBCTA);
        b_issue_xchg(n, src, sbase, pol);
    }
}

template <bool CLU>
__device__ __noinline__ void b_chain(const Params& p, char* smem, uint32_t sbase, int bi, unsigned epoch, uint64_t pol) {
    const int tid = threadIdx.x, warp = tid >> 5, lane = tid & 31, g = lane >> 2, t = lane & 3;
    unsigned (*ctl)[32] = scratch(p)->ctl[epoch & 1];
    float* red = reinterpret_cast<float*>(smem + 5 * SLOT);
    __syncthreads();
    b_gemm(p, sbase, 0, BS_WUK, DM, sbase + M_XB, 0, XP, bi, pol);
    {
        uint32_t Q[16];
#pragma unroll
        for (int c = 0; c < 16; c++) Q[c] = lds32(sbase + M_QB + (g & 3) * QP + c * 16 + t * 4);
        float* qa = reinterpret_cast<float*>(smem + M_QA);
#pragma unroll 1
        for (int n = BS_WUK; n < BS_Q; n++) {
            b_wait(n, sbase);
            const uint32_t base = sbase + (n % BRING) * SLOT + (warp * 16 + (lane & 15)) * 128;
            float d[2][4];
#pragma unroll
            for (int i = 0; i < 8; i++) d[i >> 2][i & 3] = 0.f;
#pragma unroll
            for (int s = 0; s < 8; s++) {
                uint32_t a[4];
                ldsm4(a, base + (s >> 2) * 16384 + (((2 * (s & 3) + (lane >> 4)) ^ (lane & 7)) * 16));
                mma16816(d[s & 1], a, Q[2 * s], Q[2 * s + 1]);
            }
            const int c = (n - BS_WUK) * 128 + warp * 16 + g + 8 * (t >> 1);
            qa[(2 * (t & 1)) * 512 + c] = (t & 2) ? d[0][2] + d[1][2] : d[0][0] + d[1][0];
            qa[(2 * (t & 1) + 1) * 512 + c] = (t & 2) ? d[0][3] + d[1][3] : d[0][1] + d[1][1];
            __syncthreads();
            if (tid == 0) b_issue(p, n + BD, bi, sbase, pol);
        }
#pragma unroll 1
        for (int r = 0; r < 2; r++) {
            const int id = tid + r * 256;
            const int b = id >> 7, c0 = ((id >> 2) & 31) * 16 + (id & 3) * 2;
            const float2 u0 = *reinterpret_cast<const float2*>(qa + b * 512 + c0);
            const float2 u1 = *reinterpret_cast<const float2*>(qa + b * 512 + c0 + 8);
            const uint32_t h0 = pack_bf16(u0.x, u0.y), h1 = pack_bf16(u1.x, u1.y);
            const uint32_t l0 = pack_bf16(u0.x - bf_lo(h0), u0.y - bf_hi(h0)), l1 = pack_bf16(u1.x - bf_lo(h1), u1.y - bf_hi(h1));
            scratch(p)->qabs[((id >> 2) * 4 + (bi >> 3)) * 32 + (bi & 7) * 4 + (id & 3)] = make_uint4(h0, l0, h1, l1);
        }
    }
    b_exchange(&ctl[C_BBAR][0], BS_Q, &scratch(p)->qabs[(bi >> 3) * 4096], sbase, pol);
    {
        uint32_t qf[4][4][4];
        b_wait(BS_Q + (warp >> 2), sbase);
        {
            const uint4* qs = reinterpret_cast<const uint4*>(smem + ((BS_Q + (warp >> 2)) % BRING) * SLOT) + (warp & 3) * 512 + lane;
#pragma unroll
            for (int s = 0; s < 4; s++)
#pragma unroll
                for (int i = 0; i < 4; i++) {
                    const uint4 v = qs[(s * 4 + i) * 32];
                    qf[i][s][0] = v.x; qf[i][s][1] = v.y; qf[i][s][2] = v.z; qf[i][s][3] = v.w;
                }
        }
        __syncthreads();
        if (tid == 0) { b_issue(p, BS_Q + BD, bi, sbase, pol); b_issue(p, BS_Q + 1 + BD, bi, sbase, pol); }
        float acc[2][8][4];
#pragma unroll
        for (int i = 0; i < 2; i++)
#pragma unroll
            for (int j = 0; j < 8; j++) { acc[i][j][0] = acc[i][j][1] = acc[i][j][2] = acc[i][j][3] = 0.f; }
        float mrun = -INFINITY, lrun = 0.f;
        const int head = tid >> 3, kq = tid & 7;
        float* alpha = reinterpret_cast<float*>(smem + M_ALPHA);
        for (int n = BS_CKV; n < BS_PART; n++) {
            b_wait(n, sbase);
            const uint32_t slot = sbase + (n % BRING) * SLOT;
            float sc[4][4][4];
#pragma unroll
            for (int i = 0; i < 4; i++)
#pragma unroll
                for (int j = 0; j < 4; j++) { sc[i][j][0] = sc[i][j][1] = sc[i][j][2] = sc[i][j][3] = 0.f; }
#pragma unroll
            for (int j = 0; j < 4; j++)
#pragma unroll
                for (int sp = 0; sp < 2; sp++) {
                    uint32_t bf[4];
                    ldsm4(bf, slot + warp * 4096 + (8 * j + (lane & 7)) * 128 + (((4 * sp + (lane >> 3)) ^ (lane & 7)) * 16));
#pragma unroll
                    for (int i = 0; i < 4; i++) {
                        mma16816(sc[i][j], qf[i][2 * sp], bf[0], bf[1]);
                        mma16816(sc[i][j], qf[i][2 * sp + 1], bf[2], bf[3]);
                    }
                }
#pragma unroll
            for (int i = 0; i < 4; i++)
#pragma unroll
                for (int j = 0; j < 4; j++)
                    *reinterpret_cast<float2*>(red + warp * 1024 + (8 * i + g) * 32 + ((8 * j) ^ (8 * (g & 3))) + 2 * t) =
                        make_float2(sc[i][j][0] + sc[i][j][2], sc[i][j][1] + sc[i][j][3]);
            __syncthreads();
            if (tid == 0 && n > BS_CKV) b_issue(p, n - 1 + BD, bi, sbase, pol);
            {
                float4 s = make_float4(0.f, 0.f, 0.f, 0.f);
#pragma unroll
                for (int w = 0; w < 8; w++) {
                    const float4 v = *reinterpret_cast<const float4*>(red + w * 1024 + head * 32 + ((4 * kq) ^ (8 * (head & 3))));
                    s.x += v.x; s.y += v.y; s.z += v.z; s.w += v.w;
                }
                const uint32_t r0 = pack_bf16(s.x, s.y), r1 = pack_bf16(s.z, s.w);
                const uint32_t s0 = pack_bf16(bf_lo(r0) * SCALE, bf_hi(r0) * SCALE);
                const uint32_t s1 = pack_bf16(bf_lo(r1) * SCALE, bf_hi(r1) * SCALE);
                const float f0 = bf_lo(s0), f1 = bf_hi(s0), f2 = bf_lo(s1), f3 = bf_hi(s1);
                float mx = fmaxf(fmaxf(f0, f1), fmaxf(f2, f3));
                mx = fmaxf(mx, __shfl_xor_sync(~0u, mx, 1));
                mx = fmaxf(mx, __shfl_xor_sync(~0u, mx, 2));
                mx = fmaxf(mx, __shfl_xor_sync(~0u, mx, 4));
                const float mnew = fmaxf(mrun, mx);
                const float al = expsub(mrun, mnew);
                const float p0 = expsub(f0, mnew), p1 = expsub(f1, mnew), p2 = expsub(f2, mnew), p3 = expsub(f3, mnew);
                lrun = lrun * al + ((p0 + p1) + (p2 + p3));
                mrun = mnew;
                *reinterpret_cast<uint2*>(smem + M_P + head * 80 + kq * 8) = make_uint2(pack_bf16(p0, p1), pack_bf16(p2, p3));
                if (kq == 0) alpha[head] = al;
            }
            __syncthreads();
            {
                uint32_t pf[2][2][4];
#pragma unroll
                for (int i = 0; i < 2; i++)
#pragma unroll
                    for (int ks = 0; ks < 2; ks++)
                        ldsm4(pf[i][ks], sbase + M_P + (16 * i + (lane & 15)) * 80 + (16 * ks + 8 * (lane >> 4)) * 2);
#pragma unroll
                for (int i = 0; i < 2; i++) {
                    const float a0 = alpha[16 * i + g], a1 = alpha[16 * i + 8 + g];
#pragma unroll
                    for (int j = 0; j < 8; j++) { acc[i][j][0] *= a0; acc[i][j][1] *= a0; acc[i][j][2] *= a1; acc[i][j][3] *= a1; }
                }
#pragma unroll
                for (int j = 0; j < 8; j++) {
                    uint32_t bf[4];
                    ldsm4t(bf, slot + warp * 4096 + lane * 128 + ((j ^ (lane & 7)) * 16));
#pragma unroll
                    for (int i = 0; i < 2; i++) {
                        mma16816(acc[i][j], pf[i][0], bf[0], bf[1]);
                        mma16816(acc[i][j], pf[i][1], bf[2], bf[3]);
                    }
                }
            }
        }
        __syncthreads();
        if (tid == 0) b_issue(p, BS_PART - 1 + BD, bi, sbase, pol);
        lrun += __shfl_xor_sync(~0u, lrun, 1);
        lrun += __shfl_xor_sync(~0u, lrun, 2);
        lrun += __shfl_xor_sync(~0u, lrun, 4);
        if (kq == 0) scratch(p)->bml[head * NBCTA + bi] = make_float2(mrun, lrun);
#pragma unroll
        for (int i = 0; i < 2; i++)
#pragma unroll
            for (int j = 0; j < 8; j++) {
                scratch(p)->bpart[((16 * i + g) * NBCTA + bi) * 256 + warp * 32 + j * 4 + t] = make_float2(acc[i][j][0], acc[i][j][1]);
                scratch(p)->bpart[((16 * i + 8 + g) * NBCTA + bi) * 256 + warp * 32 + j * 4 + t] = make_float2(acc[i][j][2], acc[i][j][3]);
            }
    }
    b_exchange(&ctl[C_BBAR + 1][0], BS_PART, &scratch(p)->bpart[bi * NBCTA * 256], sbase, pol);
    {
        float* omega = reinterpret_cast<float*>(smem + M_OMEGA);
        if (warp == 0) {
            __syncwarp();
            const uint2 ml = ld_relaxed8(&scratch(p)->bml[bi * NBCTA + lane]);
            const float ms = __uint_as_float(ml.x);
            float m = ms;
            m = fmaxf(m, __shfl_xor_sync(~0u, m, 1));
            m = fmaxf(m, __shfl_xor_sync(~0u, m, 2));
            m = fmaxf(m, __shfl_xor_sync(~0u, m, 4));
            const float w = expsub(ms, m);
            float l = w * __uint_as_float(ml.y);
            l += __shfl_xor_sync(~0u, l, 1);
            l += __shfl_xor_sync(~0u, l, 2);
            l += __shfl_xor_sync(~0u, l, 4);
            omega[lane] = w / l;
        }
        __syncthreads();
        b_wait(BS_PART, sbase);
        b_wait(BS_PART + 1, sbase);
#pragma unroll 1
        for (int b = 0; b < 4; b++) {
            const float2* ps = reinterpret_cast<const float2*>(smem + ((BS_PART + (b >> 1)) % BRING) * SLOT) + (b & 1) * 2048 + tid;
            float c0 = 0.f, c1 = 0.f;
#pragma unroll
            for (int s = 0; s < 8; s++) {
                const float w = omega[b * 8 + s];
                const float2 v = ps[s * 256];
                c0 = fmaf(w, v.x, c0);
                c1 = fmaf(w, v.y, c1);
            }
            const uint32_t hi = pack_bf16(c0, c1);
            *reinterpret_cast<uint32_t*>(smem + M_CH + b * CP + tid * 4) = hi;
            *reinterpret_cast<uint32_t*>(smem + M_CL + b * CP + tid * 4) = pack_bf16(c0 - bf_lo(hi), c1 - bf_hi(hi));
        }
        __syncthreads();
        if (tid == 0) { b_issue(p, BS_PART + BD, bi, sbase, pol); b_issue(p, BS_PART + 1 + BD, bi, sbase, pol); }
    }
    b_gemm(p, sbase, BS_WUV, BS_END, 512, sbase + M_CH, sbase + M_CL, CP, bi, pol);
    if (CLU) {
        if (warp < 4) {
            const unsigned short* c = reinterpret_cast<const unsigned short*>(smem + M_QB + warp * QP) + 16 * t + g;
            scratch(p)->octx[(bi * 4 + warp) * 32 + lane] = make_float4(bf_lo(c[0]), bf_lo(c[8]), bf_lo(c[64]), bf_lo(c[72]));
        }
        __syncthreads();
        if (tid == 0) asm volatile("st.release.gpu.global.u32 [%0], %1;" ::"l"(&scratch(p)->cdone[bi][0]), "r"(epoch + 1) : "memory");
        return;
    }
    if (tid == 0) {
#pragma unroll 1
        for (int i = 0; i < 4; i++) {
            mbar_expect_tx(sbase + M_BAR + i * 8, 36864);
            tma3d(sbase + i * 36864, &p.tm_wo, 0, bi * 128 + i * 32, 0, sbase + M_BAR + i * 8, pol);
        }
    }
    {
        float acc[9][4];
#pragma unroll
        for (int j = 0; j < 9; j++) { acc[j][0] = acc[j][1] = acc[j][2] = acc[j][3] = 0.f; }
#pragma unroll 1
        for (int i = 0; i < 4; i++) {
            const uint32_t xo = sbase + M_QB + (g & 3) * QP + i * 64 + t * 4;
            const uint32_t a0[4] = {lds32(xo), 0u, lds32(xo + 16), 0u}, a1[4] = {lds32(xo + 32), 0u, lds32(xo + 48), 0u};
            mbar_wait(sbase + M_BAR + i * 8, 0);
#pragma unroll
            for (int j = 0; j < 9; j++) {
                const int nt = warp * 9 + j;
                uint32_t w[4];
                ldsm4t(w, sbase + i * 36864 + (nt >> 3) * 4096 + lane * 128 + (((nt & 7) ^ (lane & 7)) * 16));
                mma16816(acc[j], a0, w[0], w[1]);
                mma16816(acc[j], a1, w[2], w[3]);
            }
        }
        if (g < 4) {
#pragma unroll
            for (int j = 0; j < 9; j++) {
                const int c2 = (warp * 9 + j) * 4 + t;
                st_tagged2(&scratch(p)->outb[((c2 / 9) * NH + bi) * 36 + g * 9 + c2 % 9], acc[j][0], acc[j][1], epoch + 1);
            }
        }
    }
    {
        const uint4* src = scratch(p)->outb + (bi * NH + (tid >> 3)) * 36 + (tid & 7);
        float2* part = reinterpret_cast<float2*>(red);
        unsigned n = 0;
        while (true) {
            ulonglong2 v[5];
            bool ok = true;
#pragma unroll
            for (int i = 0; i < 5; i++)
                if (i < 4 || (tid & 7) < 4) v[i] = ld_tagged2(src + i * 8);
#pragma unroll
            for (int i = 0; i < 5; i++)
                if (i < 4 || (tid & 7) < 4) {
                    ok = ok && (unsigned)(v[i].x >> 32) == epoch + 1 && (unsigned)(v[i].y >> 32) == epoch + 1;
                    part[(tid >> 3) * 36 + (tid & 7) + i * 8] = make_float2(__uint_as_float((unsigned)v[i].x), __uint_as_float((unsigned)v[i].y));
                }
            if (ok) break;
            __nanosleep(400);
            if (++n > SPIN_LIMIT) __trap();
        }
        __syncthreads();
        if (tid < 36) {
            float s0 = 0.f, s1 = 0.f;
#pragma unroll 8
            for (int h = 0; h < NH; h++) { const float2 v = part[h * 36 + tid]; s0 += v.x; s1 += v.y; }
            *reinterpret_cast<uint32_t*>(p.out + (tid / 9) * 2 * DM + DM + bi * 18 + (tid % 9) * 2) = pack_bf16(s0, s1);
        }
    }
}

template <bool CLU>
__global__ void __launch_bounds__(256, 1) fused_decode_kernel(const __grid_constant__ Params p) {
    asm volatile("{\n.reg .pred p;\n.reg .u32 a;\n.reg .u64 b;\nsub.u32 a, %1, 128;\nsetp.lt.u32 p, a, %3;\nmad.lo.u32 a, %2, %3, %1;\n"
                 "mad.wide.u32 b, a, 128, %0;\n@p prefetch.global.L2 [b];\n}"
                 ::"l"(p.kc), "r"(threadIdx.x), "r"(blockIdx.x), "n"(PFN) : "memory");
    if (blockIdx.x >= 1024) return;
    extern __shared__ __align__(1024) char smem_raw[];
    const uint32_t sbase = (smem_u32(smem_raw) + 1023u) & ~1023u;
    char* smem = smem_raw + (sbase - smem_u32(smem_raw));
    const int tid = threadIdx.x, warp = __shfl_sync(~0u, tid >> 5, 0), lane = tid & 31;
    const int cl = blockIdx.x >> 3, rank = blockIdx.x & 7;
    const bool isB = CLU ? rank < (cl < MINCL - 2 ? 2 : 3) : (blockIdx.x & 3) == 0 && blockIdx.x < 4 * NBCTA;
    const int bi = CLU ? (rank < 2 ? 2 * cl + rank : cl + MINCL + 2) : blockIdx.x >> 2;
    const int nb = CLU ? 6 * cl + rank - 2 - max(0, cl - (MINCL - 3)) : blockIdx.x - min(NBCTA, (blockIdx.x + 3) >> 2);
    const int blk = CLU ? (isB ? bi : NBCTA + nb) : blockIdx.x;
    const int nblk = CLU ? 8 * MINCL : gridDim.x, nnb = nblk - NBCTA;
    const int nstatic = nnb * (NW + XW);
    uint64_t pol;
    asm volatile("createpolicy.fractional.L2::evict_first.b64 %0, 1.0;" : "=l"(pol));
    const uint32_t wbar = sbase + M_BAR + warp * 8, wslot = sbase + warp * SLOT;
    const int u0 = warp * nnb + nb;
    const bool hold = ((blk >> 2) >> KMIN << KMIN) * 4 * UPP < nstatic;
    const uint32_t jbar = sbase + M_BAR + (NSLOT + BRING) * 8;
    if (warp < 4) {
        const char* src = reinterpret_cast<const char*>(p.kc) + (size_t)(((unsigned)u0 >> 7) * 1024 + (u0 & 127)) * TILE_BYTES;
        asm volatile("" : "+l"(src));
        mbar_init_warp(wbar);
        if (warp < NEARLY && !isB && (CLU || !hold)) tile_load_warp(wslot, src, wbar, pol);
    }
    asm volatile("" ::: "memory");
    if (warp == 7) {
        if (blk < 128) {
            uint64_t poln;
            asm volatile("createpolicy.fractional.L2::evict_normal.b64 %0, 1.0;" : "=l"(poln));
            mbar_init_warp(jbar);
            tma3d_warp(sbase + J0W, &p.tm_j0, blk * 32, 0, 0, jbar, 36864, poln);
            mbar_init_warp(jbar + 8);
            if (lane == 0) {
                mbar_expect_tx(jbar + 8, 4608);
                bulk_load(sbase + M_XA, p.xa, 4608, jbar + 8, poln);
            }
        }
        if (lane < 8) reinterpret_cast<unsigned*>(smem + M_HELP)[lane] = 0;
        __syncwarp();
        if (!isB) asm volatile("bar.arrive 2, %0;" ::"n"(32 * (NW + XW + 1)) : "memory");
    }
    unsigned epoch = 0;
    if (lane == 0) epoch = ld_relaxed4(scratch(p)->epoch);
    if (blk >= 128 ? warp >= 4 : isB && warp < 4) epoch = __shfl_sync(~0u, epoch, 0);
    if (isB && warp == 3) asm volatile("bar.sync 1, 160;" ::: "memory");
    if (isB && tid == 96) {
#pragma unroll 1
        for (int i = 0; i < BRING; i++) mbar_init(sbase + M_BAR + (NSLOT + i) * 8, 1);
        asm volatile("fence.mbarrier_init.release.cluster;" ::: "memory");
        if (hold) { unsigned n = 0; while (ld_acquire_cta_shared(sbase + M_HELP + 24) < 2) { if (++n > (SPIN_LIMIT << 4)) __trap(); } }
#pragma unroll 1
        for (int b = 0; b < 4; b++) bulk_load(sbase + M_XB + b * XP, p.xb + b * DM, 1152, sbase + M_BAR + NSLOT * 8, pol);
#pragma unroll 1
        for (int n = 0; n < BD; n++) b_issue(p, n, bi, sbase, pol);
    }
    if (warp >= 4 && blk < 128) {
        const int g = lane >> 2, t = lane & 3, j = tid - 128;
        asm volatile("bar.sync 1, %0;" ::"r"(isB ? 160 : 128) : "memory");
#pragma unroll 1
        for (int ph = -1;; ph++) {
        const int sl = ph > 0 ? blk + 128 - nblk : blk;
        const uint32_t wa = sbase + J0W + ((warp - 4) * 144 + (lane & 7) + (lane >> 4) * 8) * 64 + ((((lane >> 3) & 1) ^ ((lane >> 1) & 3)) * 16);
        const uint32_t xa = sbase + M_XA + (g & 3) * 1152 + (warp - 4) * 288 + t * 4;
        if (ph >= 0) mbar_wait(jbar + 8, 0);
        uint32_t xb[18];
#pragma unroll
        for (int s = 0; s < 18; s++) xb[s] = lds32(xa + s * 16);
        epoch = __shfl_sync(~0u, epoch, 0);
        if (ph >= 0) mbar_wait(jbar, ph);
        float acc[4][4];
#pragma unroll
        for (int i = 0; i < 16; i++) acc[i >> 2][i & 3] = 0.f;
#pragma unroll
        for (int s = 0; s < 18; s++) {
            uint32_t w[4];
            ldsm4t(w, (wa ^ ((s & 1) * 32)) + (s >> 1) * 1024);
            mma16816(acc[s & 3], w, xb[s & ~1], xb[s | 1]);
        }
        float2* j0 = reinterpret_cast<float2*>(smem + M_J0);
        {
            float* jf = reinterpret_cast<float*>(j0) + (warp - 4) * 128 + (t & 1) * 64 + (t >> 1) * 8 + g;
#pragma unroll
            for (int i = 0; i < 4; i++)
                jf[(i & 1) * 32 + (i >> 1) * 16] = (t & 2) ? acc[i >> 1][2 + (i & 1)] + acc[2 + (i >> 1)][2 + (i & 1)] : acc[i >> 1][i & 1] + acc[2 + (i >> 1)][i & 1];
        }
        asm volatile("bar.sync 1, 128;" ::: "memory");
        const bool again = ph == 0 && blk + 128 - nblk >= nblk;
        if (again && tid == 224) {
            mbar_expect_tx(jbar, 36864);
            tma3d(sbase + J0W, &p.tm_j0, (blk + 128 - nblk) * 32, 0, 0, jbar, pol);
        }
        if (warp < 6) {
            const float2 v0 = j0[j], v1 = j0[64 + j], v2 = j0[128 + j], v3 = j0[192 + j];
            asm volatile("{\n.reg .pred p;\n.reg .b64 v;\nsetp.ge.s32 p, %3, 0;\nmov.b64 v, {%1, %2};\n@p st.relaxed.gpu.global.u64 [%0], v;\n}"
                         ::"l"(&scratch(p)->qll[(j >> 4) * 2048 + sl * 16 + (j & 15)]),
                           "r"(pack_bf16((v0.x + v1.x) + (v2.x + v3.x), (v0.y + v1.y) + (v2.y + v3.y))), "r"(epoch + 1), "r"(ph) : "memory");
            __syncwarp();
            if (lane == 0 && ph >= 0) asm volatile("red.relaxed.cta.shared::cta.add.u32 [%0], 1;" ::"r"(sbase + M_HELP + 24) : "memory");
        } else if (warp == 7) {
            if (blk < C_LINES && ph == 0) scratch(p)->ctl[(epoch & 1) ^ 1][blk][lane] = 0;
        }
        if (ph >= 0 && !again) break;
        asm volatile("bar.sync 1, 128;" ::: "memory");
        }
    }
    if (CLU) {
        if (warp == 6) {
            if (lane < 24 && lane > 1) mbar_init(sbase + F_BAR + lane * 8, 1);
            if ((lane >> 1) == 1) mbar_expect_tx(sbase + F_BAR + lane * 8, 1024);
            asm volatile("fence.mbarrier_init.release.cluster;" ::: "memory");
        }
        asm volatile("barrier.cluster.arrive.relaxed.aligned;" ::: "memory");
    }
    const int c5 = cl % 5;
    const bool partA = CLU && c5 < 3;
    const int nwork = partA && rank == 7 ? 1 : NW + ((CLU ? rank < 2 + X3C && c5 < 4 : (nb & 3) < X3) ? 1 : 0);
    if (isB) {
        b_chain<CLU>(p, smem, sbase, bi, epoch, pol);
        if (!CLU) return;
        if (warp == 2) {
            unsigned n = 0;
            while (ld_acquire(&scratch(p)->ctl[epoch & 1][C_KDONE][0]) < NUK / 2) { __nanosleep(1000); if (++n > SPIN_LIMIT) __trap(); }
        }
    } else if (warp < NW + XW) {
        a_worker<CLU>(p, u0, warp >= nwork, warp < NEARLY && !hold, hold, nstatic, wslot, wbar, sbase + M_HELP,
                      epoch, pol);
        if (!CLU || warp < nwork) return;
        epoch = __shfl_sync(~0u, epoch, 0);
        unsigned n = 0;
        while (ld_acquire_cta_shared(sbase + M_HELP + 12) == 0) { __nanosleep(1000); if (++n > SPIN_LIMIT) __trap(); }
    } else if (warp == 7) {
#pragma unroll 1
        for (int i = nb; i < 4 * NH; i += nnb) scratch(p)->oacc[i * 32 + lane] = make_float4(0.f, 0.f, 0.f, 0.f);
        if (nb < (CLU ? NREPC : NREP) * NH) scratch(p)->vdone[nb][lane] = 0;
        __syncwarp();
        k_helper(p, sbase + M_HELP, epoch);
        if (nb == 0 && lane == 0) scratch(p)->epoch[0] = epoch + 1;
        __syncwarp();
    } else if (!CLU && nb < NFIN) {
        if (warp == 6) {
            finisher(p, sbase, nb);
        } else if (warp >= 6 - NPOLL) {
            v_poller(p, sbase, nb, warp - (6 - NPOLL));
        }
    }
    if (!CLU) return;
    asm volatile("barrier.cluster.wait.acquire.aligned;" ::: "memory");
    const int nsl = c5 == 4 ? 2 : 1, panel = cl / 5 * 3 + (partA ? c5 : c5 - 3);
    if (warp >= 4) {
        f_project(p, rank, warp - 4, nsl, sbase);
        return;
    }
    if (isB ? warp == 2 : warp < 3 || nwork == 3)
        f_collect((partA ? scratch(p)->vdone : scratch(p)->cdone) + 4 * rank, partA ? 4 * UPP : epoch + 1,
                  (partA ? scratch(p)->oacc : scratch(p)->octx) + 4 * rank * 128, nwork == 1 ? 5 * warp : 15, sbase);
    if (warp != 3) return;
    f_request(p, partA ? &p.tm_fa : &p.tm_fb, panel, rank, nsl, nsl == 2 ? T2A + rank * (T2D / 8) : T1A + rank * (T1D / 8), nsl == 2 ? T2D : T1D, epoch + 1, sbase, pol);
    f_receive(p, p.out + (partA ? 0 : DM) + panel * 64 + rank * 8, nsl, sbase);
}

}

typedef CUresult (*EncodeFn)(CUtensorMap*, CUtensorMapDataType, cuuint32_t, void*, const cuuint64_t*, const cuuint64_t*,
                             const cuuint32_t*, const cuuint32_t*, CUtensorMapInterleave, CUtensorMapSwizzle,
                             CUtensorMapL2promotion, CUtensorMapFloatOOBfill);

extern "C" void kernel_launch(void* const* d_in, const int* in_sizes, int n_in, void* d_out, int out_size) {
    (void)in_sizes; (void)n_in; (void)out_size;
    static int nsm = 0, ncl = 0;
    static EncodeFn encode = nullptr;
    static void* scr = nullptr;
    cudaLaunchConfig_t cfg = {};
    cudaLaunchAttribute at[1];
    at[0].id = cudaLaunchAttributeClusterDimension;
    at[0].val.clusterDim.x = 8; at[0].val.clusterDim.y = 1; at[0].val.clusterDim.z = 1;
    cfg.blockDim = dim3(256); cfg.dynamicSmemBytes = SMEM_BYTES; cfg.stream = cudaStreamPerThread; cfg.attrs = at; cfg.numAttrs = 1;
    if (nsm == 0) {
        int dev = 0;
        cudaGetDevice(&dev);
        cudaDeviceGetAttribute(&nsm, cudaDevAttrMultiProcessorCount, dev);
        cudaFuncSetAttribute(fused_decode_kernel<false>, cudaFuncAttributeMaxDynamicSharedMemorySize, SMEM_BYTES);
        cudaFuncSetAttribute(fused_decode_kernel<true>, cudaFuncAttributeMaxDynamicSharedMemorySize, SMEM_BYTES);
        cfg.gridDim = dim3(128);
        if (cudaOccupancyMaxActiveClusters(&ncl, fused_decode_kernel<true>, &cfg) != cudaSuccess) { ncl = 0; (void)cudaGetLastError(); }
        if (ncl > MINCL) ncl = MINCL;
        void* fn = nullptr;
        cudaDriverEntryPointQueryResult qr;
        cudaGetDriverEntryPoint("cuTensorMapEncodeTiled", &fn, cudaEnableDefault, &qr);
        encode = (EncodeFn)fn;
        cudaGetSymbolAddress(&scr, g_scratch);
    }
    Params p;
    auto panels = [&](CUtensorMap* tm, void* ptr, int rows, int cols, int box_rows, int box_panels,
                      CUtensorMapL2promotion promo = CU_TENSOR_MAP_L2_PROMOTION_L2_256B) {
        const cuuint64_t gd[3] = {64, (cuuint64_t)rows, (cuuint64_t)(cols / 64)}, gs[2] = {(cuuint64_t)cols * 2, 128};
        const cuuint32_t box[3] = {64, (cuuint32_t)box_rows, (cuuint32_t)box_panels}, es[3] = {1, 1, 1};
        encode(tm, CU_TENSOR_MAP_DATA_TYPE_BFLOAT16, 3, ptr, gd, gs, box, es, CU_TENSOR_MAP_INTERLEAVE_NONE,
               CU_TENSOR_MAP_SWIZZLE_128B, promo, CU_TENSOR_MAP_FLOAT_OOB_FILL_NONE);
    };
    panels(&p.tm_wq, d_in[7], DM, 4096, 128, 2);
    panels(&p.tm_wuk, d_in[8], 512, 4096, 128, 2);
    panels(&p.tm_wuv, d_in[9], 512, 4096, 128, 2);
    panels(&p.tm_wo, d_in[10], 4096, DM, 32, 9);
    panels(&p.tm_ckv, d_in[6], 4 * SK, 512, 32, 8);
    panels(&p.tm_fa, d_in[4], 4096, DM, 64, 1, CU_TENSOR_MAP_L2_PROMOTION_L2_128B);
    panels(&p.tm_fb, d_in[10], 4096, DM, 64, 1, CU_TENSOR_MAP_L2_PROMOTION_L2_128B);
    {
        const cuuint64_t gd[3] = {4096, 192, 3}, gs[2] = {8192, 192 * 8192};
        const cuuint32_t box[3] = {32, 192, 3}, es[3] = {1, 1, 1};
        encode(&p.tm_j0, CU_TENSOR_MAP_DATA_TYPE_BFLOAT16, 3, d_in[3], gd, gs, box, es, CU_TENSOR_MAP_INTERLEAVE_NONE,
               CU_TENSOR_MAP_SWIZZLE_64B, CU_TENSOR_MAP_L2_PROMOTION_L2_128B, CU_TENSOR_MAP_FLOAT_OOB_FILL_NONE);
    }
    p.xa = (const __nv_bfloat16*)d_in[0];
    p.kc = (const __nv_bfloat16*)d_in[1];
    p.vc = (const __nv_bfloat16*)d_in[2];
    p.wo = (const __nv_bfloat16*)d_in[4];
    p.xb = (const __nv_bfloat16*)d_in[5];
    p.out = (__nv_bfloat16*)d_out;
    p.s = (Scratch*)scr;
    if (ncl >= MINCL) {
        cfg.gridDim = dim3(8 * ncl);
        cudaLaunchKernelEx(&cfg, fused_decode_kernel<true>, p);
    } else {
        fused_decode_kernel<false><<<nsm, 256, SMEM_BYTES, cudaStreamPerThread>>>(p);
    }
}
```

```cpp
#include <cuda_runtime.h>
#include <cuda.h>
#include <cuda_bf16.h>
#include <stdint.h>

namespace {

constexpr int NH = 32, SK = 4096, DM = 576;
constexpr int KEYS = 128;
constexpr int UPP = SK / KEYS;
constexpr int NUK = 4 * NH * UPP;
constexpr int TILE_BYTES = KEYS * 256;
#define NWORK 2
constexpr int NW = NWORK;
constexpr int NBCTA = 32;
constexpr int MINCL = 15;
constexpr int NFIN = 72;
constexpr int SLOT = 32768;
constexpr int NSLOT = 6;
constexpr int BRING = 5;
constexpr int J0W = 5 * SLOT;
constexpr int MISC = NSLOT * SLOT + 4096;
constexpr int XP = 1168, CP = 1040, QP = 272;
constexpr int M_XA = MISC;
constexpr int M_XB = M_XA + 4 * XP;
constexpr int M_CH = M_XB + 4 * XP;
constexpr int M_CL = M_CH + 4 * CP;
constexpr int M_QB = M_CL + 4 * CP;
constexpr int M_QA = M_CH;
constexpr int M_J0 = M_QB + 4 * QP;
constexpr int M_P = M_J0 + 2048;
constexpr int M_ALPHA = M_P + 2560;
constexpr int M_OMEGA = M_ALPHA + 128;
constexpr int M_BAR = M_OMEGA + 128;
constexpr int M_HELP = M_BAR + 128;
constexpr int F_W = 4 * SLOT;
constexpr int F_BF = (M_HELP + 383) / 256 * 256;
constexpr int F_RX = NSLOT * SLOT;
constexpr int F_BAR = F_BF + 4096;
constexpr int SMEM_BYTES = F_BAR + 200 + 1024;
static_assert(SMEM_BYTES <= 232448 && F_RX + 7168 <= M_XB && M_BAR % 8 == 0 && M_QA % 16 == 0 && M_P % 16 == 0, "smem layout");
#define XW 2
#define X3 1
#define X3C 4
#define NEARLY 2
#define LATE 2000
#define BD 5
#define FPF 3
#define FSLEEP 800
#define VS0 24
#define PFN 96
#define EARLY 100
#define ELOG 5
#define TPU 159
#define T1A (1590 + 200 * X3C)
#define T1D 390
#define T2A (T1A - 340)
#define T2D 195
#define TOWN 90
#define LAG 5
#define NPOLL 2
#define PGAP 200
static_assert(X3C <= 4 && NW == 2 && XW == 2 && MINCL == 15, "roles of the cluster launch");
static_assert(NW + XW <= 4 && NEARLY <= NW + XW && BD <= BRING, "slots 4 and 5 hold the finisher weights");
constexpr int KMIN = 2, KMAX = 4, VMIN = 0, VMAX = 4;
constexpr float SCALE = 0.08838834764831845f;
constexpr float LOG2E = 1.4426950408889634f;
constexpr unsigned SPIN_LIMIT = 1u << 24;

#define NREP 2
#define NREPC 1
constexpr int C_QUEUE = 0, C_KDONE = 1, C_BBAR = 3, C_LINES = 5;

struct Scratch {
    unsigned epoch[32];
    unsigned ctl[2][C_LINES][32];
    uint2 qll[4 * 2048];
    uint2 scores[128 * SK / 4];
    float2 stats[128 * UPP];
    float4 oacc[128 * 32];
    unsigned vdone[NREP * NH][32];
    float4 octx[128 * 32];
    unsigned cdone[NH][32];
    unsigned long long dry[16][16];
    uint4 qabs[4 * 8 * 4 * 4 * 32];
    float2 bpart[NBCTA * NH * 256];
    float2 bml[NBCTA * NH];
    uint4 outb[NBCTA * NH * 36];
};
__device__ __align__(256) Scratch g_scratch;

struct Params {
    const __nv_bfloat16 *kc, *xa, *vc, *wo, *xb;
    __nv_bfloat16* out;
    Scratch* s;
    CUtensorMap tm_j0;
    CUtensorMap tm_wq, tm_wuk, tm_ckv, tm_wuv, tm_wo;
    CUtensorMap tm_fa, tm_fb;
};

__device__ __forceinline__ Scratch* scratch(const Params& p) {
    Scratch* s = p.s;
    __builtin_assume(__isGlobal(s));
    return s;
}

__device__ __forceinline__ uint32_t smem_u32(const void* p) { return (uint32_t)__cvta_generic_to_shared(p); }
__device__ __forceinline__ void mbar_init(uint32_t bar, uint32_t cnt) {
    asm volatile("mbarrier.init.shared::cta.b64 [%0], %1;" ::"r"(bar), "r"(cnt) : "memory");
}
__device__ __forceinline__ void mbar_expect_tx(uint32_t bar, uint32_t bytes) {
    asm volatile("mbarrier.arrive.expect_tx.shared::cta.b64 _, [%0], %1;" ::"r"(bar), "r"(bytes) : "memory");
}
__device__ __forceinline__ bool mbar_try(uint32_t bar, uint32_t parity) {
    uint32_t ok;
    asm volatile("{\n.reg .pred p;\nmbarrier.try_wait.parity.shared::cta.b64 p, [%1], %2;\nselp.u32 %0, 1, 0, p;\n}\n"
                 : "=r"(ok) : "r"(bar), "r"(parity) : "memory");
    return ok;
}
__device__ __forceinline__ void mbar_wait(uint32_t bar, uint32_t parity) {
    unsigned n = 0;
    while (!mbar_try(bar, parity)) { if (++n > SPIN_LIMIT) __trap(); }
}
__device__ __forceinline__ void mbar_spin(uint32_t bar) {
    asm volatile("{\n.reg .pred p;\n.reg .u32 n;\nmov.u32 n, 0;\nSPIN:\nmbarrier.try_wait.parity.shared::cta.b64 p, [%0], 0;\n@p bra.uni DONE;\n"
                 "add.u32 n, n, 1;\nsetp.lt.u32 p, n, 0x1000000;\n@p bra.uni SPIN;\ntrap;\nDONE:\n}" ::"r"(bar) : "memory");
}
__device__ __forceinline__ void mbar_spin_cluster(uint32_t bar) {
    asm volatile("{\n.reg .pred p;\n.reg .u32 n;\nmov.u32 n, 0;\nSPIN:\nmbarrier.try_wait.parity.relaxed.cluster.shared::cta.b64 p, [%0], 0;\n"
                 "@p bra.uni DONE;\nadd.u32 n, n, 1;\nsetp.lt.u32 p, n, 0x1000000;\n@p bra.uni SPIN;\ntrap;\nDONE:\n"
                 "fence.acquire.sync_restrict::shared::cluster.cluster;\n}" ::"r"(bar) : "memory");
}
__device__ __forceinline__ void bulk_load(uint32_t dst, const void* src, uint32_t bytes, uint32_t bar, uint64_t pol) {
    asm volatile("cp.async.bulk.shared::cluster.global.mbarrier::complete_tx::bytes.L2::cache_hint [%0], [%1], %2, [%3], %4;"
                 ::"r"(dst), "l"(src), "r"(bytes), "r"(bar), "l"(pol) : "memory");
}
__device__ __forceinline__ void mbar_init_warp(uint32_t bar) {
    asm volatile("{\n.reg .pred p;\nelect.sync _|p, 0xffffffff;\n@p mbarrier.init.shared::cta.b64 [%0], 1;\n@p fence.mbarrier_init.release.cluster;\n}"
                 ::"r"(bar) : "memory");
}
__device__ __forceinline__ void tile_load_warp(uint32_t dst, const void* src, uint32_t bar, uint64_t pol) {
    asm volatile("{\n.reg .pred p;\nelect.sync _|p, 0xffffffff;\n@p mbarrier.arrive.expect_tx.shared::cta.b64 _, [%2], %4;\n"
                 "@p cp.async.bulk.shared::cluster.global.mbarrier::complete_tx::bytes.L2::cache_hint [%0], [%1], %4, [%2], %3;\n}"
                 ::"r"(dst), "l"(src), "r"(bar), "l"(pol), "n"(TILE_BYTES) : "memory");
}
__device__ __forceinline__ void tma3d_warp(uint32_t dst, const CUtensorMap* tm, int c0, int c1, int c2, uint32_t bar, uint32_t bytes, uint64_t pol) {
    asm volatile("{\n.reg .pred p;\nelect.sync _|p, 0xffffffff;\n@p mbarrier.arrive.expect_tx.shared::cta.b64 _, [%2], %7;\n"
                 "@p cp.async.bulk.tensor.3d.shared::cluster.global.mbarrier::complete_tx::bytes.L2::cache_hint [%0], [%1, {%3,%4,%5}], [%2], %6;\n}"
                 ::"r"(dst), "l"(tm), "r"(bar), "r"(c0), "r"(c1), "r"(c2), "l"(pol), "r"(bytes) : "memory");
}
__device__ __forceinline__ void tma3d(uint32_t dst, const CUtensorMap* tm, int c0, int c1, int c2, uint32_t bar, uint64_t pol) {
    asm volatile("cp.async.bulk.tensor.3d.shared::cluster.global.mbarrier::complete_tx::bytes.L2::cache_hint [%0], [%1, {%3,%4,%5}], [%2], %6;"
                 ::"r"(dst), "l"(tm), "r"(bar), "r"(c0), "r"(c1), "r"(c2), "l"(pol) : "memory");
}
__device__ __forceinline__ void l2_prefetch(const void* src, uint32_t bytes) {
    asm volatile("cp.async.bulk.prefetch.L2.global [%0], %1;" ::"l"(src), "r"(bytes) : "memory");
}
__device__ __forceinline__ void ldsm4(uint32_t (&r)[4], uint32_t addr) {
    asm volatile("ldmatrix.sync.aligned.m8n8.x4.shared.b16 {%0,%1,%2,%3}, [%4];"
                 : "=r"(r[0]), "=r"(r[1]), "=r"(r[2]), "=r"(r[3]) : "r"(addr));
}
__device__ __forceinline__ void ldsm4t(uint32_t (&r)[4], uint32_t addr) {
    asm volatile("ldmatrix.sync.aligned.m8n8.x4.trans.shared.b16 {%0,%1,%2,%3}, [%4];"
                 : "=r"(r[0]), "=r"(r[1]), "=r"(r[2]), "=r"(r[3]) : "r"(addr));
}
__device__ __forceinline__ void mma16816(float (&d)[4], const uint32_t (&a)[4], uint32_t b0, uint32_t b1) {
    asm("mma.sync.aligned.m16n8k16.row.col.f32.bf16.bf16.f32 {%0,%1,%2,%3}, {%4,%5,%6,%7}, {%8,%9}, {%0,%1,%2,%3};"
        : "+f"(d[0]), "+f"(d[1]), "+f"(d[2]), "+f"(d[3])
        : "r"(a[0]), "r"(a[1]), "r"(a[2]), "r"(a[3]), "r"(b0), "r"(b1));
}
__device__ __forceinline__ uint32_t lds32(uint32_t a) {
    uint32_t v;
    asm volatile("ld.shared.u32 %0, [%1];" : "=r"(v) : "r"(a));
    return v;
}
__device__ __forceinline__ unsigned ld_acquire(const unsigned* p) {
    unsigned v;
    asm volatile("ld.acquire.gpu.global.u32 %0, [%1];" : "=r"(v) : "l"(p) : "memory");
    return v;
}
__device__ __forceinline__ uint2 ld_relaxed8(const void* p) {
    uint2 v;
    asm volatile("ld.relaxed.gpu.global.v2.u32 {%0,%1}, [%2];" : "=r"(v.x), "=r"(v.y) : "l"(p) : "memory");
    return v;
}
__device__ __forceinline__ unsigned ld_relaxed4(const void* p) {
    unsigned v;
    asm volatile("ld.relaxed.gpu.global.u32 %0, [%1];" : "=r"(v) : "l"(p) : "memory");
    return v;
}
__device__ __forceinline__ unsigned atom_inc(unsigned* p) {
    unsigned v;
    asm volatile("atom.relaxed.gpu.global.inc.u32 %0, [%1], 0x7fffffff;" : "=r"(v) : "l"(p) : "memory");
    return v;
}
__device__ __forceinline__ unsigned long long ld_relaxed64(const void* p) {
    unsigned long long v;
    asm volatile("ld.relaxed.gpu.global.u64 %0, [%1];" : "=l"(v) : "l"(p) : "memory");
    return v;
}
__device__ __forceinline__ void st_relaxed64(void* p, unsigned long long v) {
    asm volatile("st.relaxed.gpu.global.u64 [%0], %1;" ::"l"(p), "l"(v) : "memory");
}
__device__ __forceinline__ float4 ld_relaxed16(const void* p) {
    float4 v;
    asm volatile("ld.relaxed.gpu.global.v4.f32 {%0,%1,%2,%3}, [%4];" : "=f"(v.x), "=f"(v.y), "=f"(v.z), "=f"(v.w) : "l"(p) : "memory");
    return v;
}
__device__ __forceinline__ uint32_t mapa(uint32_t a, uint32_t rank) {
    uint32_t r;
    asm("mapa.shared::cluster.u32 %0, %1, %2;" : "=r"(r) : "r"(a), "r"(rank));
    return r;
}
__device__ __forceinline__ uint32_t time_ns() { uint32_t t; asm volatile("mov.u32 %0, %globaltimer_lo;" : "=r"(t)); return t; }
__device__ __forceinline__ void fence_gpu() { asm volatile("fence.acq_rel.gpu;" ::: "memory"); }
__device__ __forceinline__ void red_add_u32(unsigned* p, unsigned v) {
    asm volatile("red.relaxed.gpu.global.add.u32 [%0], %1;" ::"l"(p), "r"(v) : "memory");
}
__device__ __forceinline__ void st_tagged2(void* p, float a, float b, unsigned tag) {
    const unsigned long long hi = (unsigned long long)tag << 32;
    asm volatile("st.relaxed.gpu.global.v2.b64 [%0], {%1,%2};" ::"l"(p), "l"(hi | __float_as_uint(a)), "l"(hi | __float_as_uint(b)) : "memory");
}
__device__ __forceinline__ ulonglong2 ld_tagged2(const void* p) {
    ulonglong2 v;
    asm volatile("ld.relaxed.gpu.global.v2.b64 {%0,%1}, [%2];" : "=l"(v.x), "=l"(v.y) : "l"(p) : "memory");
    return v;
}
__device__ __forceinline__ float4 atom_add_f4(void* p, float a, float b, float c, float d) {
    float4 r;
    asm volatile("atom.relaxed.gpu.global.add.v4.f32 {%0,%1,%2,%3}, [%4], {%5,%6,%7,%8};"
                 : "=f"(r.x), "=f"(r.y), "=f"(r.z), "=f"(r.w) : "l"(p), "f"(a), "f"(b), "f"(c), "f"(d) : "memory");
    return r;
}
__device__ __forceinline__ void red_release_cta_shared(uint32_t a, unsigned v) {
    asm volatile("red.release.cta.shared::cta.add.u32 [%0], %1;" ::"r"(a), "r"(v) : "memory");
}
__device__ __forceinline__ unsigned ld_acquire_cta_shared(uint32_t a) {
    unsigned v;
    asm volatile("ld.acquire.cta.shared::cta.u32 %0, [%1];" : "=r"(v) : "r"(a) : "memory");
    return v;
}
__device__ __forceinline__ void st_release_cta_shared(uint32_t a, unsigned v) {
    asm volatile("st.release.cta.shared::cta.u32 [%0], %1;" ::"r"(a), "r"(v) : "memory");
}
__device__ __forceinline__ void wait_count(const unsigned* p, unsigned target) {
    unsigned n = 0;
    while (ld_acquire(p) < target) { if (++n > SPIN_LIMIT) __trap(); }
}
__device__ __forceinline__ uint32_t pack_bf16(float lo, float hi) {
    uint32_t r;
    asm("cvt.rn.bf16x2.f32 %0, %1, %2;" : "=r"(r) : "f"(hi), "f"(lo));
    return r;
}
__device__ __forceinline__ float bf_lo(uint32_t v) { return __uint_as_float(v << 16); }
__device__ __forceinline__ float bf_hi(uint32_t v) { return __uint_as_float(v & 0xffff0000u); }
__device__ __forceinline__ float ex2(float x) { float y; asm("ex2.approx.ftz.f32 %0, %1;" : "=f"(y) : "f"(x)); return y; }
__device__ __forceinline__ float expsub(float a, float b) { return ex2((a - b) * LOG2E); }
__device__ __forceinline__ float warp_max(float v) {
#pragma unroll
    for (int m = 16; m; m >>= 1) v = fmaxf(v, __shfl_xor_sync(~0u, v, m));
    return v;
}
__device__ __forceinline__ float warp_sum(float v) {
#pragma unroll
    for (int m = 16; m; m >>= 1) v += __shfl_xor_sync(~0u, v, m);
    return v;
}
template <bool CLU>
__device__ __forceinline__ unsigned unit_block(int u) {
    const unsigned x = ((unsigned)u & (NUK - 1)) / UPP;
    const int lg = u < NUK ? min(KMAX, max(KMIN, 29 - __clz(x | 1))) : (CLU && (int)x >= 4 * VS0 ? 0 : min(VMAX, max(VMIN, 29 - __clz((127 - x) | 1))));
    const unsigned r = x & ((4u << lg) - 1);
    return ((x - r + (r & ((1u << lg) - 1)) * 4 + (r >> lg)) * UPP) | ((unsigned)u & (UPP - 1));
}
__device__ __forceinline__ const char* block_src(const void* base, unsigned blk) {
    const unsigned po = blk / UPP;
    return reinterpret_cast<const char*>(base) + (size_t)(((po & 3) * NH + (po >> 2)) * UPP + blk % UPP) * TILE_BYTES;
}

template <bool CLU>
__device__ __forceinline__ void a_worker(const Params& p, int un, bool once, bool pre, bool hold, int nstatic, uint32_t slot, uint32_t bar,
                                         uint32_t help, unsigned epoch, uint64_t pol) {
    constexpr int NU = 2 * NUK, NR = CLU ? NREPC : NREP;
    const int lane = threadIdx.x & 31, g = lane >> 2, t = lane & 3;
    const int li = lane & 7;
    uint32_t kaddr[4], vaddr[8];
    {
        const int e = (lane >> 3) & 1, kk = lane >> 4;
#pragma unroll
        for (int s = 0; s < 4; s++) kaddr[s] = slot + (16 * li + e) * 256 + ((2 * s + kk + li) & 7) * 16;
        const int vrow = 4 * (li >> 1) + (li & 1) + 2 * kk;
#pragma unroll
        for (int c = 0; c < 8; c++) vaddr[c] = slot + vrow * 256 + e * 128 + ((c + li) & 7) * 16;
#pragma unroll
        for (int c = 0; c < 8; c++) asm volatile("" : "+r"(vaddr[c]));
    }
    const uint32_t vmask = (g >> 1) != t ? 0u : ((g & 1) ? 0xffff0000u : 0xffffu);
    int kseen = -1;
    unsigned long long H0 = 0, H1 = 0;
    auto header = [&](int v, unsigned vb) {
        const void *a0, *a1;
        if (v < NUK) {
            const unsigned po = vb / UPP;
            a0 = scratch(p)->qll + (po & 3) * 2048 + (po >> 2) * 64 + lane;
            a1 = reinterpret_cast<const uint2*>(a0) + 32;
        } else {
            const int half = vb / (NUK / 2);
            if (half > kseen) {
                unsigned n = 0;
                while (ld_acquire_cta_shared(help + 12 + 4 * half) == 0) { if (++n > (SPIN_LIMIT << 4)) __trap(); }
                kseen = half;
            }
            a0 = &scratch(p)->scores[vb * (KEYS / 4) + lane];
            a1 = &scratch(p)->stats[(vb / UPP) * UPP + lane];
        }
        H0 = ld_relaxed64(a0);
        H1 = ld_relaxed64(a1);
    };
    unsigned bu = 0, bn = unit_block<CLU>(un);
    asm volatile("bar.sync 2, %0;" ::"n"(32 * (NW + XW + 1)) : "memory");
    if (!pre && !hold) { const uint32_t t0 = clock(); while ((uint32_t)clock() - t0 < ((threadIdx.x >> 5) - NEARLY + 1) * LATE) {} }
    epoch = __shfl_sync(~0u, epoch, 0);
    if (hold) { unsigned n = 0; while (ld_acquire_cta_shared(help + 24) < 2) { if (++n > (SPIN_LIMIT << 4)) __trap(); } }
    unsigned (*ctl)[32] = scratch(p)->ctl[epoch & 1];
    const unsigned tag = epoch + 1;
    unsigned nxt = once ? NU : 0;
    int u = -1;
    uint32_t phase = 0;
    unsigned kpend = 0;
    const unsigned zero = gridDim.x >> 24;
    uint32_t Q[16];
    float4 oret = make_float4(0.f, 0.f, 0.f, 0.f);
    while (true) {
        const char* nsrc = block_src(un < NUK ? p.kc : p.vc, bn);
        float4* odst = &scratch(p)->oacc[(bu / UPP) * 32 + lane];
        unsigned* vdst = &scratch(p)->vdone[(lane & (NR - 1)) * NH + bu / (4 * UPP)][0];
        float d[8][4];
        uint32_t act = un >= NU ? 0u : (u >= 0 || !pre ? 1u : 0u) | (!once && lane == 0 ? 2u : 0u);
        asm volatile("" : "+l"(odst), "+l"(nsrc), "+r"(act));
        if (u >= NUK) {
#pragma unroll
            for (int j = 0; j < 8; j++) { d[j][0] = d[j][1] = d[j][2] = d[j][3] = 0.f; }
            mbar_wait(bar, phase);
            uint32_t a[2][8][4];
#pragma unroll
            for (int c = 0; c < 8; c++) ldsm4t(a[0][c], vaddr[c]);
#pragma unroll
            for (int j = 0; j < 8; j++) {
                if (j < 7) {
#pragma unroll
                    for (int c = 0; c < 8; c++) ldsm4t(a[(j + 1) & 1][c], vaddr[c] + (j + 1) * 4096);
                }
#pragma unroll
                for (int c = 0; c < 8; c++) mma16816(d[c], a[j & 1][c], Q[2 * j], Q[2 * j + 1]);
            }
            float o[4];
#pragma unroll
            for (int r = 0; r < 2; r++) {
                o[2 * r] = d[0][2 * r] + d[7][2 * r + 1];
                o[2 * r + 1] = d[0][2 * r + 1] + d[1][2 * r];
#pragma unroll
                for (int k = 1; k < 4; k++) {
                    const int src = (lane & 28) | ((t - k) & 3);
                    o[2 * r] += __shfl_sync(~0u, d[2 * k][2 * r] + d[2 * k - 1][2 * r + 1], src);
                    o[2 * r + 1] += __shfl_sync(~0u, d[2 * k][2 * r + 1] + d[2 * k + 1][2 * r], src);
                }
            }
            oret = atom_add_f4(odst, o[0], o[1], o[2], o[3]);
        } else if (u >= 0) {
#pragma unroll
            for (int j = 0; j < 8; j++) { d[j][0] = d[j][1] = d[j][2] = d[j][3] = 0.f; }
            mbar_wait(bar, phase);
            uint32_t a[2][8][4];
#pragma unroll
            for (int j = 0; j < 8; j++) ldsm4(a[0][j], kaddr[0] + (4 * (j & 3) + 2 * (j >> 2)) * 256);
#pragma unroll
            for (int s = 0; s < 8; s++) {
                if (s < 7) {
#pragma unroll
                    for (int j = 0; j < 8; j++)
                        ldsm4(a[(s + 1) & 1][j], kaddr[(s + 1) & 3] + (4 * (j & 3) + 2 * (j >> 2)) * 256 + ((s + 1) >> 2) * 128);
                }
#pragma unroll
                for (int j = 0; j < 8; j++)
                    mma16816(d[j], a[s & 1][j], Q[(s & 4) * 2 + ((2 * s - 2 * j) & 7)], Q[(s & 4) * 2 + ((2 * s + 1 - 2 * j) & 7)]);
            }
        }
        if (u >= 0) phase ^= 1;
        asm volatile("{\n.reg .pred p, q;\n.reg .u32 a;\nelect.sync _|p, 0xffffffff;\nand.b32 a, %5, 1;\nsetp.ne.and.u32 q, a, 0, p;\n"
                     "@q mbarrier.arrive.expect_tx.shared::cta.b64 _, [%2], %4;\n"
                     "@q cp.async.bulk.shared::cluster.global.mbarrier::complete_tx::bytes.L2::cache_hint [%0], [%1], %4, [%2], %3;\n}"
                     ::"r"(slot), "l"(nsrc), "r"(bar), "l"(pol), "n"(TILE_BYTES), "r"(act) : "memory");
        if (act & 2) nxt = atom_inc(&ctl[C_QUEUE][0]);
        const uint32_t tk = clock();
        if ((unsigned)u < (unsigned)NUK) {
            const int j0 = (t - (g >> 1)) & 3;
            float v[4];
#pragma unroll
            for (int q = 0; q < 4; q++) {
                const int jq = (q >> 1) * 4, e = (q & 1) * 2;
                const float x0 = (g & 1) ? d[jq + 0][e + 1] : d[jq + 0][e];
                const float x1 = (g & 1) ? d[jq + 1][e + 1] : d[jq + 1][e];
                const float x2 = (g & 1) ? d[jq + 2][e + 1] : d[jq + 2][e];
                const float x3 = (g & 1) ? d[jq + 3][e + 1] : d[jq + 3][e];
                const float y0 = (j0 & 1) ? x1 : x0, y1 = (j0 & 1) ? x3 : x2;
                v[q] = (j0 & 2) ? y1 : y0;
            }
            const uint32_t r0 = pack_bf16(v[0], v[1]), r1 = pack_bf16(v[2], v[3]);
            const uint32_t s0 = pack_bf16(bf_lo(r0) * SCALE, bf_hi(r0) * SCALE);
            const uint32_t s1 = pack_bf16(bf_lo(r1) * SCALE, bf_hi(r1) * SCALE);
            scratch(p)->scores[bu * (KEYS / 4) + 4 * g + j0] = make_uint2(s0, s1);
            const float f0 = bf_lo(s0), f1 = bf_hi(s0), f2 = bf_lo(s1), f3 = bf_hi(s1);
            const float m = warp_max(fmaxf(fmaxf(f0, f1), fmaxf(f2, f3)));
            const float l = warp_sum((expsub(f0, m) + expsub(f1, m)) + (expsub(f2, m) + expsub(f3, m)));
            if (lane == 0) scratch(p)->stats[bu] = make_float2(m, l);
            kpend++;
            if (un / (NUK / 2) != u / (NUK / 2)) {
                __syncwarp();
                if (lane == 0) {
                    red_release_cta_shared(help + 4 * (u / (NUK / 2)), kpend);
                    if (un >= NUK) red_release_cta_shared(help + 8, 1u);
                }
                kpend = 0;
            }
        }
        int unn = NU;
        if (un < NU) {
            unsigned n = 0;
            while (true) {
                header(un, bn);
                if (un >= NUK || __all_sync(~0u, (uint32_t)(H0 >> 32) == tag && (uint32_t)(H1 >> 32) == tag)) break;
                if (++n > SPIN_LIMIT) __trap();
            }
            if (un >= NUK) {
                const uint32_t s0 = (uint32_t)H0, s1 = (uint32_t)(H0 >> 32);
                const float mu = __uint_as_float((uint32_t)H1);
                const float m = warp_max(mu);
                const float l = warp_sum(__uint_as_float((uint32_t)(H1 >> 32)) * expsub(mu, m));
                const float inv = 1.0f / l;
                const uint32_t w0 = pack_bf16(expsub(bf_lo(s0), m) * inv, expsub(bf_hi(s0), m) * inv);
                const uint32_t w1 = pack_bf16(expsub(bf_lo(s1), m) * inv, expsub(bf_hi(s1), m) * inv);
#pragma unroll
                for (int j = 0; j < 8; j++) {
                    Q[2 * j] = __shfl_sync(~0u, w0, 4 * j + t) & vmask;
                    Q[2 * j + 1] = __shfl_sync(~0u, w1, 4 * j + t) & vmask;
                }
            } else {
#pragma unroll
                for (int j = 0; j < 8; j++) {
                    const int src = (((j + g) & 7) << 2) + t;
                    Q[j] = __shfl_sync(~0u, (uint32_t)H0, src);
                    Q[8 + j] = __shfl_sync(~0u, (uint32_t)H1, src);
                }
            }
            unn = nstatic + (int)__shfl_sync(~0u, nxt, 0);
            if (CLU && ((NU - EARLY - unn) & ~(7 << ELOG)) == 0 && lane < MINCL)
                st_relaxed64(&scratch(p)->dry[lane][(NU - EARLY - unn) >> ELOG],
                             (time_ns() - (((uint32_t)clock() - tk) >> 1) + (NU - unn) * TPU / 16) | (unsigned long long)tag << 32);
        }
        if (u >= NUK && lane < NR)
            red_add_u32(vdst,
                        1u + ((__float_as_uint(oret.x) | __float_as_uint(oret.y) | __float_as_uint(oret.z) | __float_as_uint(oret.w)) & zero));
        if (un >= NU) break;
        bu = bn;
        bn = unit_block<CLU>(unn);
        u = un;
        un = unn;
    }
}

__device__ __forceinline__ void k_helper(const Params& p, uint32_t help, unsigned epoch) {
    if ((threadIdx.x & 31) != 0) return;
    unsigned (*ctl)[32] = scratch(p)->ctl[epoch & 1];
    unsigned sent0 = 0, sent1 = 0, n = 0;
    int seen = 0;
    bool fin = false;
    while (!fin || seen < 2) {
        if (!fin) {
            fin = ld_acquire_cta_shared(help + 8) == NW + XW;
            const unsigned c0 = ld_acquire_cta_shared(help), c1 = ld_acquire_cta_shared(help + 4);
            if (c0 != sent0 || c1 != sent1) {
                fence_gpu();
                if (c0 != sent0) red_add_u32(&ctl[C_KDONE][0], c0 - sent0);
                if (c1 != sent1) red_add_u32(&ctl[C_KDONE + 1][0], c1 - sent1);
                sent0 = c0; sent1 = c1;
            }
        }
        if (seen < 2 && ld_acquire(&ctl[C_KDONE + seen][0]) >= NUK / 2) {
            st_release_cta_shared(help + 12 + 4 * seen, 1u);
            seen++;
        } else {
            __nanosleep(300);
        }
        if (++n > SPIN_LIMIT) __trap();
    }
}

__device__ __forceinline__ void v_poller(const Params& p, uint32_t sbase, int f, int w) {
    constexpr int HL = NH;
    const int lane = threadIdx.x & 31;
    const unsigned (*cp)[32] = &scratch(p)->vdone[((f * NPOLL + w) % NREP) * NH];
    unsigned n = 0;
    while (ld_acquire_cta_shared(sbase + M_HELP + 12) == 0) { __nanosleep(1000); if (++n > SPIN_LIMIT) __trap(); }
    int h = 0;
    bool fast = false;
    while (h < HL) {
        const unsigned r = __ballot_sync(~0u, ld_acquire(&cp[min(h + (lane & 3), HL - 1)][0]) >= 4 * UPP) & 15u;
        if (r & 1) {
            h = min(HL, h + __ffs(~r) - 1);
            __syncwarp();
            if (lane == 0) asm volatile("red.release.cta.shared::cta.max.u32 [%0], %1;" ::"r"(sbase + M_HELP + 20), "r"(h) : "memory");
        }
        if (h < HL - 4) {
            __nanosleep(h ? 300 : 1000);
        } else if (!fast) {
            fast = true;
            const long long t0 = clock64();
            while (clock64() - t0 < w * PGAP) {}
        }
        if (++n > SPIN_LIMIT) __trap();
    }
}
__device__ __forceinline__ void finisher(const Params& p, uint32_t sbase, int f) {
    constexpr int HL = NH;
    const int lane = threadIdx.x & 31;
    {
        const char* wg = reinterpret_cast<const char*>(p.wo);
        const uint32_t dst = sbase + 4 * SLOT + (16 * (lane & 7) + (lane >> 3)) * 16;
#pragma unroll 1
        for (int h = -FPF - 4; h < HL; h++) {
            if (lane == 0 && (unsigned)(h + FPF) < (unsigned)HL) l2_prefetch(wg + (size_t)(h + FPF) * 147456 + f * 2048, 2048);
            if (h >= 0) {
#pragma unroll
                for (int r = 0; r < 4; r++)
                    asm volatile("cp.async.cg.shared.global [%0], [%1], 16;" ::"r"(dst + h * 2048 + ((r & 1) * 4 + (r >> 1) * 8) * 16),
                                 "l"(wg + (size_t)(h * 128 + r * 32 + lane) * (DM * 2) + f * 16) : "memory");
            }
            __nanosleep(FSLEEP);
        }
        asm volatile("cp.async.wait_all;" ::: "memory");
        __syncwarp();
    }
    const float4* vec = scratch(p)->oacc + ((lane >> 2) & 3) * 32 + (lane >> 4) * 16 + (lane & 3);
    float acc[2][2][4];
#pragma unroll
    for (int i = 0; i < 16; i++) acc[i >> 3][(i >> 2) & 1][i & 3] = 0.f;
    uint32_t* outp = reinterpret_cast<uint32_t*>(p.out + (lane >> 2) * (2 * DM) + f * 8 + (lane & 3) * 2);
    uint32_t wa = sbase + 4 * SLOT + lane * 16;
    auto project = [&](const float4 (&x)[4], const uint32_t (&w)[4][4]) {
#pragma unroll
        for (int s = 0; s < 4; s++) {
            const uint32_t a[4] = {pack_bf16(x[s].x, x[s].y), 0u, pack_bf16(x[s].z, x[s].w), 0u};
            mma16816(acc[0][s & 1], a, w[s >> 1][(s & 1) * 2], w[s >> 1][(s & 1) * 2 + 1]);
            mma16816(acc[1][s & 1], a, w[2 + (s >> 1)][(s & 1) * 2], w[2 + (s >> 1)][(s & 1) * 2 + 1]);
        }
    };
    int h = 0;
    unsigned n = 0;
    while (h < HL) {
        uint32_t w[4][4];
#pragma unroll
        for (int q = 0; q < 4; q++) ldsm4t(w[q], wa + q * 512);
        int ready;
        while ((ready = ld_acquire_cta_shared(sbase + M_HELP + 20)) <= h) {
            if (h < HL - 3) __nanosleep(100);
            if (++n > (SPIN_LIMIT << 4)) __trap();
        }
        float4 x[4], y[4];
#pragma unroll
        for (int s = 0; s < 4; s++) x[s] = ld_relaxed16(vec + s * 4);
        const bool two = ready > h + 1;
        if (two) {
#pragma unroll
            for (int s = 0; s < 4; s++) y[s] = ld_relaxed16(vec + 128 + s * 4);
        }
        project(x, w);
        if (two) {
#pragma unroll
            for (int q = 0; q < 4; q++) ldsm4t(w[q], wa + 2048 + q * 512);
            project(y, w);
        }
        const int nr = two ? 2 : 1;
        h += nr;
        vec += nr * 128;
        wa += nr * 2048;
        const float o0 = acc[0][0][0] + acc[0][1][0] + __shfl_down_sync(~0u, acc[1][0][0] + acc[1][1][0], 16);
        const float o1 = acc[0][0][1] + acc[0][1][1] + __shfl_down_sync(~0u, acc[1][0][1] + acc[1][1][1], 16);
        asm volatile("{\n.reg .pred p;\nsetp.ne.u32 p, %2, 0;\n@p st.global.u32 [%0], %1;\n}" ::"l"(outp), "r"(pack_bf16(o0, o1)),
                     "r"((uint32_t)(lane < 16 && h == NH)) : "memory");
    }
}

__device__ __noinline__ void f_collect(const unsigned (*flag)[32], unsigned full, const float4* src, unsigned todo, uint32_t sbase) {
    const int lane = threadIdx.x & 31, g = lane >> 2, t = lane & 3;
    const bool last = todo != 15;
    unsigned n = 0;
    while (todo) {
        const unsigned v = ld_acquire(&flag[t][0]);
        unsigned m = __ballot_sync(~0u, v == full) & todo;
        if (m == 0) {
            if (!last || __shfl_sync(~0u, v, 0) == 0) __nanosleep(200);
            if (++n > SPIN_LIMIT) __trap();
            continue;
        }
        __syncwarp();
        todo ^= m;
        do {
            const int h0 = __ffs(m) - 1, h1 = 31 - __clz(m);
            m &= ~((1u << h0) | (1u << h1));
            float4 x[8];
#pragma unroll
            for (int b = 0; b < 8; b++) x[b] = ld_relaxed16(src + ((b & 4) ? h1 : h0) * 128 + (b & 3) * 32 + lane);
#pragma unroll
            for (int b = 0; b < 8; b++) {
                const uint32_t lo = pack_bf16(x[b].x, x[b].y), hi = pack_bf16(x[b].z, x[b].w);
                const uint32_t o = __shfl_xor_sync(~0u, (g & 1) ? lo : hi, 4);
                const uint32_t e0 = (g & 1) ? o : lo, e1 = (g & 1) ? hi : o;
                asm volatile("st.shared.v2.u32 [%0], {%1,%2};"
                             ::"r"(sbase + F_BF + ((b & 4) ? h1 : h0) * 1024 + t * 256 + ((b ^ t) & 3) * 64 + g * 8),
                               "r"(__byte_perm(e0, e1, 0x5410)), "r"(__byte_perm(e0, e1, 0x7632)) : "memory");
            }
            __syncwarp();
            if (lane < (h0 == h1 ? 1 : 2))
                asm volatile("mbarrier.arrive.shared::cta.b64 _, [%0];" ::"r"(sbase + F_BAR + 32 + (lane ? h1 : h0) * 8) : "memory");
        } while (m);
    }
}

__device__ __forceinline__ void f_request(const Params& p, const CUtensorMap* tm, int panel, int rank, int nsl, int delay, int step, unsigned tag,
                                          uint32_t sbase, uint64_t pol) {
    const int lane = threadIdx.x & 31;
    if (lane == 0) asm volatile("prefetch.tensormap [%0];" ::"l"(tm) : "memory");
    unsigned long long v;
    unsigned n = 0;
    while (!__all_sync(~0u, (v = ld_relaxed64(&scratch(p)->dry[blockIdx.x >> 3][lane >> 2])) >> 32 == tag)) {
        __nanosleep(200);
        if (++n > SPIN_LIMIT) __trap();
    }
    const uint32_t t0 = __shfl_sync(~0u, (uint32_t)v, 0);
    uint32_t due = t0 + (__reduce_add_sync(~0u, (int)((uint32_t)v - t0)) >> 5);
    due += delay;
#pragma unroll 1
    for (int q = 0; q < 8 * nsl; q++, due += step) {
        if (q >= LAG * nsl) mbar_spin(sbase + F_BAR + 64 + (q - LAG * nsl) * 8);
        if (rank == 7 && q == 8 * nsl - 1) due += TOWN;
        while ((int)(time_ns() - due) < 0 && ++n < SPIN_LIMIT) {}
        tma3d_warp(sbase + F_W - (q >> 3) * 2 * SLOT + (q & 7) * 8192, tm, 0, (rank * 8 + (q & 7)) * 64, panel + (q >> 3), sbase + F_BAR + 64 + q * 8,
                   8192, pol);
    }
}

__device__ __forceinline__ void f_project(const Params& p, int rank, int j, int nsl, uint32_t sbase, __nv_bfloat16* out) {
    const int lane = threadIdx.x & 31, g = lane >> 2, t = lane & 3;
    const uint32_t wa = sbase + F_W + ((lane & 7) + (lane >> 4) * 8) * 128 + (((2 * j + ((lane >> 3) & 1)) ^ (lane & 7)) * 16);
    const uint32_t ba = sbase + F_BF + (g & 3) * 64 + t * 16;
    const bool up = t & 2;
#pragma unroll 1
    for (int sl = 0; sl < nsl; sl++) {
        const int owner = 8 - nsl + sl;
        const uint32_t rdst = mapa(sbase + F_RX + min(rank, 6) * 1024 + j * 256 + lane * 8, owner);
        const uint32_t rbar = mapa(sbase + F_BAR + j * 8, owner);
        __nv_bfloat16* dst = out + sl * 64 + (t & 1) * (4 * DM) + j * 16 + (t >> 1) * 8 + g;
        uint32_t src = sbase + F_RX + j * 256 + lane * 8;
        asm volatile("" : "+l"(dst), "+r"(src));
        float acc[2][4];
#pragma unroll
        for (int k = 0; k < 8; k++) acc[k >> 2][k & 3] = 0.f;
#pragma unroll 1
        for (int hp = 0; hp < 2; hp++) {
            uint32_t wp = wa + hp * 32768 - sl * 2 * SLOT, bar = sbase + F_BAR + 64 + sl * 64 + hp * 32, last = hp;
            uint32_t bf[2][4][4];
#pragma unroll
            for (int e = 0; e < 2; e++) {
                mbar_spin(sbase + F_BAR + 32 + hp * 16 + e * 8);
#pragma unroll
                for (int s = 0; s < 4; s++)
                    asm volatile("ld.shared.v4.u32 {%0,%1,%2,%3}, [%4];" : "=r"(bf[e][s][0]), "=r"(bf[e][s][1]), "=r"(bf[e][s][2]), "=r"(bf[e][s][3])
                                 : "r"(((ba + hp * 2048 + e * 1024) ^ (s * 64)) + s * 256) : "memory");
            }
            uint32_t send = hp && rank != owner, obar = hp ? sbase + F_BAR + j * 8 : bar;
            asm volatile("" : "+r"(wp), "+r"(bar), "+r"(last), "+r"(send), "+r"(obar));
#pragma unroll
            for (int e = 0; e < 2; e++) {
                uint32_t a[8][4];
#pragma unroll
                for (int q = 0; q < 2; q++) {
                    mbar_spin(bar + e * 16 + q * 8);
#pragma unroll
                    for (int s = 4 * q; s < 4 * q + 4; s++) ldsm4t(a[s], wp + e * 16384 + s * 2048);
                }
#pragma unroll
                for (int s = 0; s < 8; s++) mma16816(acc[s & 1], a[s], bf[e][s & 3][(s >> 2) * 2], bf[e][s & 3][(s >> 2) * 2 + 1]);
            }
            const float v0 = up ? acc[0][2] + acc[1][2] : acc[0][0] + acc[1][0], v1 = up ? acc[0][3] + acc[1][3] : acc[0][1] + acc[1][1];
            asm volatile("{\n.reg .pred p;\nsetp.ne.u32 p, %4, 0;\n"
                         "@p st.async.weak.shared::cluster.mbarrier::complete_tx::bytes.v2.b32 [%0], {%1,%2}, [%3];\n}"
                         ::"r"(rdst), "r"(__float_as_uint(v0)), "r"(__float_as_uint(v1)), "r"(rbar), "r"(send) : "memory");
            if (rank == owner) {
                mbar_spin_cluster(obar);
                float2 x[7];
#pragma unroll
                for (int r = 0; r < 7; r++) asm volatile("ld.shared.v2.f32 {%0,%1}, [%2];" : "=f"(x[r].x), "=f"(x[r].y) : "r"(src + r * 1024) : "memory");
                const uint32_t o = pack_bf16(((v0 + x[0].x) + (x[1].x + x[2].x)) + ((x[3].x + x[4].x) + (x[5].x + x[6].x)),
                                             ((v1 + x[0].y) + (x[1].y + x[2].y)) + ((x[3].y + x[4].y) + (x[5].y + x[6].y)));
                asm volatile("{\n.reg .pred p;\n.reg .b16 a, b;\nsetp.ne.u32 p, %2, 0;\nmov.b32 {a, b}, %1;\n@p st.global.u16 [%0], a;\n@p st.global.u16 [%0+2304], b;\n}"
                             ::"l"(dst), "r"(o), "r"(last) : "memory");
            }
        }
    }
}

constexpr int BS_WUK = 5, BS_Q = 9, BS_CKV = 11, BS_PART = 27, BS_WUV = 29, BS_END = 33;

__device__ __noinline__ void b_issue(const Params& p, int n, int bi, uint32_t sbase, uint64_t pol) {
    if (n >= BS_END || (n >= BS_Q && n < BS_CKV) || (n >= BS_PART && n < BS_WUV)) return;
    const uint32_t bar = sbase + M_BAR + (NSLOT + n % BRING) * 8;
    const CUtensorMap* tm;
    int row, panel = 2 * bi;
    if (n < BS_WUK) { tm = &p.tm_wq; row = n * 128; }
    else if (n < BS_Q) { tm = &p.tm_wuk; row = (n - BS_WUK) * 128; }
    else if (n < BS_PART) {
        tm = &p.tm_ckv; panel = 0;
        row = (bi >> 3) * SK + ((n - BS_CKV) * 8 + (bi & 7)) * 32;
    }
    else { tm = &p.tm_wuv; row = (n - BS_WUV) * 128; }
    mbar_expect_tx(bar, n == 0 ? 32768 + 4 * 1152 : 32768);
    tma3d(sbase + (n % BRING) * SLOT, tm, 0, row, panel, bar, pol);
}
__device__ __forceinline__ void b_issue_xchg(int n, const void* src, uint32_t sbase, uint64_t pol) {
    asm volatile("fence.proxy.async;" ::: "memory");
#pragma unroll
    for (int i = 0; i < 2; i++) {
        const uint32_t bar = sbase + M_BAR + (NSLOT + (n + i) % BRING) * 8;
        mbar_expect_tx(bar, 32768);
        bulk_load(sbase + ((n + i) % BRING) * SLOT, reinterpret_cast<const char*>(src) + i * 32768, 32768, bar, pol);
    }
}
__device__ __forceinline__ void b_wait(int n, uint32_t sbase) {
    mbar_wait(sbase + M_BAR + (NSLOT + n % BRING) * 8, (n / BRING) & 1);
}

__device__ __noinline__ void b_gemm(const Params& p, uint32_t sbase, int n0, int n1, int ktot, uint32_t xh, uint32_t xl, int pitch,
                                    int bi, uint64_t pol) {
    const int tid = threadIdx.x, warp = tid >> 5, lane = tid & 31, g = lane >> 2, t = lane & 3;
    const uint32_t woff = (warp >> 2) * 16384 + (lane & 15) * 128 + ((((warp & 3) * 2 + (lane >> 4)) ^ (lane & 7)) * 16);
    const uint32_t xoff = (g & 3) * pitch + t * 4;
    float acc[2][4];
#pragma unroll
    for (int i = 0; i < 8; i++) acc[i >> 2][i & 3] = 0.f;
#pragma unroll 1
    for (int n = n0; n < n1; n++) {
        b_wait(n, sbase);
        const uint32_t slot = sbase + (n % BRING) * SLOT + woff;
        const int k0 = (n - n0) * 128;
        const int ns = min(8, (ktot - k0) >> 4);
#pragma unroll 2
        for (int s = 0; s < ns; s++) {
            uint32_t a[4], w[4];
            const uint32_t xo = xoff + (k0 + 16 * s) * 2;
            a[0] = lds32(xh + xo); a[2] = lds32(xh + xo + 16);
            a[1] = xl ? lds32(xl + xo) : 0u; a[3] = xl ? lds32(xl + xo + 16) : 0u;
            ldsm4t(w, slot + s * 2048);
            mma16816(acc[0], a, w[0], w[1]);
            mma16816(acc[1], a, w[2], w[3]);
        }
        __syncthreads();
        if (tid == 0) b_issue(p, n + BD, bi, sbase, pol);
    }
    if (g < 4) {
#pragma unroll
        for (int j = 0; j < 2; j++)
            asm volatile("st.shared.u32 [%0], %1;" ::"r"(sbase + M_QB + g * QP + (warp * 16 + j * 8 + t * 2) * 2),
                         "r"(pack_bf16(acc[j][0] + acc[j][2], acc[j][1] + acc[j][3])) : "memory");
    }
    __syncthreads();
}

__device__ __forceinline__ void b_exchange(unsigned* c, int n, const void* src, uint32_t sbase, uint64_t pol) {
    __syncthreads();
    if (threadIdx.x == 0) {
        fence_gpu();
        red_add_u32(c, 1u);
        wait_count(c, NBCTA);
        b_issue_xchg(n, src, sbase, pol);
    }
}

template <bool CLU>
__device__ __noinline__ void b_chain(const Params& p, char* smem, uint32_t sbase, int bi, unsigned epoch, uint64_t pol) {
    const int tid = threadIdx.x, warp = tid >> 5, lane = tid & 31, g = lane >> 2, t = lane & 3;
    unsigned (*ctl)[32] = scratch(p)->ctl[epoch & 1];
    float* red = reinterpret_cast<float*>(smem + 5 * SLOT);
    __syncthreads();
    b_gemm(p, sbase, 0, BS_WUK, DM, sbase + M_XB, 0, XP, bi, pol);
    {
        uint32_t Q[16];
#pragma unroll
        for (int c = 0; c < 16; c++) Q[c] = lds32(sbase + M_QB + (g & 3) * QP + c * 16 + t * 4);
        float* qa = reinterpret_cast<float*>(smem + M_QA);
#pragma unroll 1
        for (int n = BS_WUK; n < BS_Q; n++) {
            b_wait(n, sbase);
            const uint32_t base = sbase + (n % BRING) * SLOT + (warp * 16 + (lane & 15)) * 128;
            float d[2][4];
#pragma unroll
            for (int i = 0; i < 8; i++) d[i >> 2][i & 3] = 0.f;
#pragma unroll
            for (int s = 0; s < 8; s++) {
                uint32_t a[4];
                ldsm4(a, base + (s >> 2) * 16384 + (((2 * (s & 3) + (lane >> 4)) ^ (lane & 7)) * 16));
                mma16816(d[s & 1], a, Q[2 * s], Q[2 * s + 1]);
            }
            const int c = (n - BS_WUK) * 128 + warp * 16 + g + 8 * (t >> 1);
            qa[(2 * (t & 1)) * 512 + c] = (t & 2) ? d[0][2] + d[1][2] : d[0][0] + d[1][0];
            qa[(2 * (t & 1) + 1) * 512 + c] = (t & 2) ? d[0][3] + d[1][3] : d[0][1] + d[1][1];
            __syncthreads();
            if (tid == 0) b_issue(p, n + BD, bi, sbase, pol);
        }
#pragma unroll 1
        for (int r = 0; r < 2; r++) {
            const int id = tid + r * 256;
            const int b = id >> 7, c0 = ((id >> 2) & 31) * 16 + (id & 3) * 2;
            const float2 u0 = *reinterpret_cast<const float2*>(qa + b * 512 + c0);
            const float2 u1 = *reinterpret_cast<const float2*>(qa + b * 512 + c0 + 8);
            const uint32_t h0 = pack_bf16(u0.x, u0.y), h1 = pack_bf16(u1.x, u1.y);
            const uint32_t l0 = pack_bf16(u0.x - bf_lo(h0), u0.y - bf_hi(h0)), l1 = pack_bf16(u1.x - bf_lo(h1), u1.y - bf_hi(h1));
            scratch(p)->qabs[((id >> 2) * 4 + (bi >> 3)) * 32 + (bi & 7) * 4 + (id & 3)] = make_uint4(h0, l0, h1, l1);
        }
    }
    b_exchange(&ctl[C_BBAR][0], BS_Q, &scratch(p)->qabs[(bi >> 3) * 4096], sbase, pol);
    {
        uint32_t qf[4][4][4];
        b_wait(BS_Q + (warp >> 2), sbase);
        {
            const uint4* qs = reinterpret_cast<const uint4*>(smem + ((BS_Q + (warp >> 2)) % BRING) * SLOT) + (warp & 3) * 512 + lane;
#pragma unroll
            for (int s = 0; s < 4; s++)
#pragma unroll
                for (int i = 0; i < 4; i++) {
                    const uint4 v = qs[(s * 4 + i) * 32];
                    qf[i][s][0] = v.x; qf[i][s][1] = v.y; qf[i][s][2] = v.z; qf[i][s][3] = v.w;
                }
        }
        __syncthreads();
        if (tid == 0) { b_issue(p, BS_Q + BD, bi, sbase, pol); b_issue(p, BS_Q + 1 + BD, bi, sbase, pol); }
        float acc[2][8][4];
#pragma unroll
        for (int i = 0; i < 2; i++)
#pragma unroll
            for (int j = 0; j < 8; j++) { acc[i][j][0] = acc[i][j][1] = acc[i][j][2] = acc[i][j][3] = 0.f; }
        float mrun = -INFINITY, lrun = 0.f;
        const int head = tid >> 3, kq = tid & 7;
        float* alpha = reinterpret_cast<float*>(smem + M_ALPHA);
        for (int n = BS_CKV; n < BS_PART; n++) {
            b_wait(n, sbase);
            const uint32_t slot = sbase + (n % BRING) * SLOT;
            float sc[4][4][4];
#pragma unroll
            for (int i = 0; i < 4; i++)
#pragma unroll
                for (int j = 0; j < 4; j++) { sc[i][j][0] = sc[i][j][1] = sc[i][j][2] = sc[i][j][3] = 0.f; }
#pragma unroll
            for (int j = 0; j < 4; j++)
#pragma unroll
                for (int sp = 0; sp < 2; sp++) {
                    uint32_t bf[4];
                    ldsm4(bf, slot + warp * 4096 + (8 * j + (lane & 7)) * 128 + (((4 * sp + (lane >> 3)) ^ (lane & 7)) * 16));
#pragma unroll
                    for (int i = 0; i < 4; i++) {
                        mma16816(sc[i][j], qf[i][2 * sp], bf[0], bf[1]);
                        mma16816(sc[i][j], qf[i][2 * sp + 1], bf[2], bf[3]);
                    }
                }
#pragma unroll
            for (int i = 0; i < 4; i++)
#pragma unroll
                for (int j = 0; j < 4; j++)
                    *reinterpret_cast<float2*>(red + warp * 1024 + (8 * i + g) * 32 + ((8 * j) ^ (8 * (g & 3))) + 2 * t) =
                        make_float2(sc[i][j][0] + sc[i][j][2], sc[i][j][1] + sc[i][j][3]);
            __syncthreads();
            if (tid == 0 && n > BS_CKV) b_issue(p, n - 1 + BD, bi, sbase, pol);
            {
                float4 s = make_float4(0.f, 0.f, 0.f, 0.f);
#pragma unroll
                for (int w = 0; w < 8; w++) {
                    const float4 v = *reinterpret_cast<const float4*>(red + w * 1024 + head * 32 + ((4 * kq) ^ (8 * (head & 3))));
                    s.x += v.x; s.y += v.y; s.z += v.z; s.w += v.w;
                }
                const uint32_t r0 = pack_bf16(s.x, s.y), r1 = pack_bf16(s.z, s.w);
                const uint32_t s0 = pack_bf16(bf_lo(r0) * SCALE, bf_hi(r0) * SCALE);
                const uint32_t s1 = pack_bf16(bf_lo(r1) * SCALE, bf_hi(r1) * SCALE);
                const float f0 = bf_lo(s0), f1 = bf_hi(s0), f2 = bf_lo(s1), f3 = bf_hi(s1);
                float mx = fmaxf(fmaxf(f0, f1), fmaxf(f2, f3));
                mx = fmaxf(mx, __shfl_xor_sync(~0u, mx, 1));
                mx = fmaxf(mx, __shfl_xor_sync(~0u, mx, 2));
                mx = fmaxf(mx, __shfl_xor_sync(~0u, mx, 4));
                const float mnew = fmaxf(mrun, mx);
                const float al = expsub(mrun, mnew);
                const float p0 = expsub(f0, mnew), p1 = expsub(f1, mnew), p2 = expsub(f2, mnew), p3 = expsub(f3, mnew);
                lrun = lrun * al + ((p0 + p1) + (p2 + p3));
                mrun = mnew;
                *reinterpret_cast<uint2*>(smem + M_P + head * 80 + kq * 8) = make_uint2(pack_bf16(p0, p1), pack_bf16(p2, p3));
                if (kq == 0) alpha[head] = al;
            }
            __syncthreads();
            {
                uint32_t pf[2][2][4];
#pragma unroll
                for (int i = 0; i < 2; i++)
#pragma unroll
                    for (int ks = 0; ks < 2; ks++)
                        ldsm4(pf[i][ks], sbase + M_P + (16 * i + (lane & 15)) * 80 + (16 * ks + 8 * (lane >> 4)) * 2);
#pragma unroll
                for (int i = 0; i < 2; i++) {
                    const float a0 = alpha[16 * i + g], a1 = alpha[16 * i + 8 + g];
#pragma unroll
                    for (int j = 0; j < 8; j++) { acc[i][j][0] *= a0; acc[i][j][1] *= a0; acc[i][j][2] *= a1; acc[i][j][3] *= a1; }
                }
#pragma unroll
                for (int j = 0; j < 8; j++) {
                    uint32_t bf[4];
                    ldsm4t(bf, slot + warp * 4096 + lane * 128 + ((j ^ (lane & 7)) * 16));
#pragma unroll
                    for (int i = 0; i < 2; i++) {
                        mma16816(acc[i][j], pf[i][0], bf[0], bf[1]);
                        mma16816(acc[i][j], pf[i][1], bf[2], bf[3]);
                    }
                }
            }
        }
        __syncthreads();
        if (tid == 0) b_issue(p, BS_PART - 1 + BD, bi, sbase, pol);
        lrun += __shfl_xor_sync(~0u, lrun, 1);
        lrun += __shfl_xor_sync(~0u, lrun, 2);
        lrun += __shfl_xor_sync(~0u, lrun, 4);
        if (kq == 0) scratch(p)->bml[head * NBCTA + bi] = make_float2(mrun, lrun);
#pragma unroll
        for (int i = 0; i < 2; i++)
#pragma unroll
            for (int j = 0; j < 8; j++) {
                scratch(p)->bpart[((16 * i + g) * NBCTA + bi) * 256 + warp * 32 + j * 4 + t] = make_float2(acc[i][j][0], acc[i][j][1]);
                scratch(p)->bpart[((16 * i + 8 + g) * NBCTA + bi) * 256 + warp * 32 + j * 4 + t] = make_float2(acc[i][j][2], acc[i][j][3]);
            }
    }
    b_exchange(&ctl[C_BBAR + 1][0], BS_PART, &scratch(p)->bpart[bi * NBCTA * 256], sbase, pol);
    {
        float* omega = reinterpret_cast<float*>(smem + M_OMEGA);
        if (warp == 0) {
            __syncwarp();
            const uint2 ml = ld_relaxed8(&scratch(p)->bml[bi * NBCTA + lane]);
            const float ms = __uint_as_float(ml.x);
            float m = ms;
            m = fmaxf(m, __shfl_xor_sync(~0u, m, 1));
            m = fmaxf(m, __shfl_xor_sync(~0u, m, 2));
            m = fmaxf(m, __shfl_xor_sync(~0u, m, 4));
            const float w = expsub(ms, m);
            float l = w * __uint_as_float(ml.y);
            l += __shfl_xor_sync(~0u, l, 1);
            l += __shfl_xor_sync(~0u, l, 2);
            l += __shfl_xor_sync(~0u, l, 4);
            omega[lane] = w / l;
        }
        __syncthreads();
        b_wait(BS_PART, sbase);
        b_wait(BS_PART + 1, sbase);
#pragma unroll 1
        for (int b = 0; b < 4; b++) {
            const float2* ps = reinterpret_cast<const float2*>(smem + ((BS_PART + (b >> 1)) % BRING) * SLOT) + (b & 1) * 2048 + tid;
            float c0 = 0.f, c1 = 0.f;
#pragma unroll
            for (int s = 0; s < 8; s++) {
                const float w = omega[b * 8 + s];
                const float2 v = ps[s * 256];
                c0 = fmaf(w, v.x, c0);
                c1 = fmaf(w, v.y, c1);
            }
            const uint32_t hi = pack_bf16(c0, c1);
            *reinterpret_cast<uint32_t*>(smem + M_CH + b * CP + tid * 4) = hi;
            *reinterpret_cast<uint32_t*>(smem + M_CL + b * CP + tid * 4) = pack_bf16(c0 - bf_lo(hi), c1 - bf_hi(hi));
        }
        __syncthreads();
        if (tid == 0) { b_issue(p, BS_PART + BD, bi, sbase, pol); b_issue(p, BS_PART + 1 + BD, bi, sbase, pol); }
    }
    b_gemm(p, sbase, BS_WUV, BS_END, 512, sbase + M_CH, sbase + M_CL, CP, bi, pol);
    if (CLU) {
        if (warp < 4) {
            const unsigned short* c = reinterpret_cast<const unsigned short*>(smem + M_QB + warp * QP) + 16 * t + g;
            scratch(p)->octx[(bi * 4 + warp) * 32 + lane] = make_float4(bf_lo(c[0]), bf_lo(c[8]), bf_lo(c[64]), bf_lo(c[72]));
        }
        __syncthreads();
        if (tid == 0) asm volatile("st.release.gpu.global.u32 [%0], %1;" ::"l"(&scratch(p)->cdone[bi][0]), "r"(epoch + 1) : "memory");
        return;
    }
    if (tid == 0) {
#pragma unroll 1
        for (int i = 0; i < 4; i++) {
            mbar_expect_tx(sbase + M_BAR + i * 8, 36864);
            tma3d(sbase + i * 36864, &p.tm_wo, 0, bi * 128 + i * 32, 0, sbase + M_BAR + i * 8, pol);
        }
    }
    {
        float acc[9][4];
#pragma unroll
        for (int j = 0; j < 9; j++) { acc[j][0] = acc[j][1] = acc[j][2] = acc[j][3] = 0.f; }
#pragma unroll 1
        for (int i = 0; i < 4; i++) {
            const uint32_t xo = sbase + M_QB + (g & 3) * QP + i * 64 + t * 4;
            const uint32_t a0[4] = {lds32(xo), 0u, lds32(xo + 16), 0u}, a1[4] = {lds32(xo + 32), 0u, lds32(xo + 48), 0u};
            mbar_wait(sbase + M_BAR + i * 8, 0);
#pragma unroll
            for (int j = 0; j < 9; j++) {
                const int nt = warp * 9 + j;
                uint32_t w[4];
                ldsm4t(w, sbase + i * 36864 + (nt >> 3) * 4096 + lane * 128 + (((nt & 7) ^ (lane & 7)) * 16));
                mma16816(acc[j], a0, w[0], w[1]);
                mma16816(acc[j], a1, w[2], w[3]);
            }
        }
        if (g < 4) {
#pragma unroll
            for (int j = 0; j < 9; j++) {
                const int c2 = (warp * 9 + j) * 4 + t;
                st_tagged2(&scratch(p)->outb[((c2 / 9) * NH + bi) * 36 + g * 9 + c2 % 9], acc[j][0], acc[j][1], epoch + 1);
            }
        }
    }
    {
        const uint4* src = scratch(p)->outb + (bi * NH + (tid >> 3)) * 36 + (tid & 7);
        float2* part = reinterpret_cast<float2*>(red);
        unsigned n = 0;
        while (true) {
            ulonglong2 v[5];
            bool ok = true;
#pragma unroll
            for (int i = 0; i < 5; i++)
                if (i < 4 || (tid & 7) < 4) v[i] = ld_tagged2(src + i * 8);
#pragma unroll
            for (int i = 0; i < 5; i++)
                if (i < 4 || (tid & 7) < 4) {
                    ok = ok && (unsigned)(v[i].x >> 32) == epoch + 1 && (unsigned)(v[i].y >> 32) == epoch + 1;
                    part[(tid >> 3) * 36 + (tid & 7) + i * 8] = make_float2(__uint_as_float((unsigned)v[i].x), __uint_as_float((unsigned)v[i].y));
                }
            if (ok) break;
            __nanosleep(400);
            if (++n > SPIN_LIMIT) __trap();
        }
        __syncthreads();
        if (tid < 36) {
            float s0 = 0.f, s1 = 0.f;
#pragma unroll 8
            for (int h = 0; h < NH; h++) { const float2 v = part[h * 36 + tid]; s0 += v.x; s1 += v.y; }
            *reinterpret_cast<uint32_t*>(p.out + (tid / 9) * 2 * DM + DM + bi * 18 + (tid % 9) * 2) = pack_bf16(s0, s1);
        }
    }
}

template <bool CLU>
__global__ void __launch_bounds__(256, 1) fused_decode_kernel(const __grid_constant__ Params p) {
    asm volatile("{\n.reg .pred p;\n.reg .u32 a;\n.reg .u64 b;\nsub.u32 a, %1, 128;\nsetp.lt.u32 p, a, %3;\nmad.lo.u32 a, %2, %3, %1;\n"
                 "mad.wide.u32 b, a, 128, %0;\n@p prefetch.global.L2 [b];\n}"
                 ::"l"(p.kc), "r"(threadIdx.x), "r"(blockIdx.x), "n"(PFN) : "memory");
    if (blockIdx.x >= 1024) return;
    extern __shared__ __align__(1024) char smem_raw[];
    const uint32_t sbase = (smem_u32(smem_raw) + 1023u) & ~1023u;
    char* smem = smem_raw + (sbase - smem_u32(smem_raw));
    const int tid = threadIdx.x, warp = __shfl_sync(~0u, tid >> 5, 0), lane = tid & 31;
    const int cl = blockIdx.x >> 3, rank = blockIdx.x & 7;
    const bool isB = CLU ? rank < (cl < MINCL - 2 ? 2 : 3) : (blockIdx.x & 3) == 0 && blockIdx.x < 4 * NBCTA;
    const int bi = CLU ? (rank < 2 ? 2 * cl + rank : cl + MINCL + 2) : blockIdx.x >> 2;
    const int nb = CLU ? 6 * cl + rank - 2 - max(0, cl - (MINCL - 3)) : blockIdx.x - min(NBCTA, (blockIdx.x + 3) >> 2);
    const int blk = CLU ? (isB ? bi : NBCTA + nb) : blockIdx.x;
    const int nblk = CLU ? 8 * MINCL : gridDim.x, nnb = nblk - NBCTA;
    const int nstatic = nnb * (NW + XW);
    uint64_t pol;
    asm volatile("createpolicy.fractional.L2::evict_first.b64 %0, 1.0;" : "=l"(pol));
    const uint32_t wbar = sbase + M_BAR + warp * 8, wslot = sbase + warp * SLOT;
    const int u0 = warp * nnb + nb;
    const bool hold = ((blk >> 2) >> KMIN << KMIN) * 4 * UPP < nstatic;
    const uint32_t jbar = sbase + M_BAR + (NSLOT + BRING) * 8;
    if (warp < 4) {
        const char* src = reinterpret_cast<const char*>(p.kc) + (size_t)(((unsigned)u0 >> 7) * 1024 + (u0 & 127)) * TILE_BYTES;
        asm volatile("" : "+l"(src));
        mbar_init_warp(wbar);
        if (warp < NEARLY && !isB && (CLU || !hold)) tile_load_warp(wslot, src, wbar, pol);
    }
    asm volatile("" ::: "memory");
    if (warp == 7) {
        if (blk < 128) {
            uint64_t poln;
            asm volatile("createpolicy.fractional.L2::evict_normal.b64 %0, 1.0;" : "=l"(poln));
            mbar_init_warp(jbar);
            tma3d_warp(sbase + J0W, &p.tm_j0, blk * 32, 0, 0, jbar, 36864, poln);
            mbar_init_warp(jbar + 8);
            if (lane == 0) {
                mbar_expect_tx(jbar + 8, 4608);
                bulk_load(sbase + M_XA, p.xa, 4608, jbar + 8, poln);
            }
        }
        if (lane < 8) reinterpret_cast<unsigned*>(smem + M_HELP)[lane] = 0;
        __syncwarp();
        asm volatile("bar.arrive 2, %0;" ::"r"(isB ? 64 : 32 * (NW + XW + 1)) : "memory");
    }
    unsigned epoch = 0;
    if (lane == 0) epoch = ld_relaxed4(scratch(p)->epoch);
    if (blk >= 128 ? warp >= 4 : isB && warp < 4) epoch = __shfl_sync(~0u, epoch, 0);
    if (isB && warp == 3) asm volatile("bar.sync 2, 64;" ::: "memory");
    if (isB && tid == 96) {
#pragma unroll 1
        for (int i = 0; i < BRING; i++) mbar_init(sbase + M_BAR + (NSLOT + i) * 8, 1);
        asm volatile("fence.mbarrier_init.release.cluster;" ::: "memory");
        if (hold) { unsigned n = 0; while (ld_acquire_cta_shared(sbase + M_HELP + 24) < 2) { if (++n > (SPIN_LIMIT << 4)) __trap(); } }
#pragma unroll 1
        for (int b = 0; b < 4; b++) bulk_load(sbase + M_XB + b * XP, p.xb + b * DM, 1152, sbase + M_BAR + NSLOT * 8, pol);
#pragma unroll 1
        for (int n = 0; n < BD; n++) b_issue(p, n, bi, sbase, pol);
    }
    if (warp >= 4 && blk < 128) {
        const int g = lane >> 2, t = lane & 3, j = tid - 128;
        asm volatile("bar.sync 1, 128;" ::: "memory");
#pragma unroll 1
        for (int ph = -1;; ph++) {
        const int sl = ph > 0 ? blk + 128 - nblk : blk;
        const uint32_t wa = sbase + J0W + ((warp - 4) * 144 + (lane & 7) + (lane >> 4) * 8) * 64 + ((((lane >> 3) & 1) ^ ((lane >> 1) & 3)) * 16);
        const uint32_t xa = sbase + M_XA + (g & 3) * 1152 + (warp - 4) * 288 + t * 4;
        if (ph >= 0) mbar_wait(jbar + 8, 0);
        uint32_t xb[18];
#pragma unroll
        for (int s = 0; s < 18; s++) xb[s] = lds32(xa + s * 16);
        epoch = __shfl_sync(~0u, epoch, 0);
        if (ph >= 0) mbar_wait(jbar, ph);
        float acc[4][4];
#pragma unroll
        for (int i = 0; i < 16; i++) acc[i >> 2][i & 3] = 0.f;
#pragma unroll
        for (int s = 0; s < 18; s++) {
            uint32_t w[4];
            ldsm4t(w, (wa ^ ((s & 1) * 32)) + (s >> 1) * 1024);
            mma16816(acc[s & 3], w, xb[s & ~1], xb[s | 1]);
        }
        float2* j0 = reinterpret_cast<float2*>(smem + M_J0);
        {
            float* jf = reinterpret_cast<float*>(j0) + (warp - 4) * 128 + (t & 1) * 64 + (t >> 1) * 8 + g;
#pragma unroll
            for (int i = 0; i < 4; i++)
                jf[(i & 1) * 32 + (i >> 1) * 16] = (t & 2) ? acc[i >> 1][2 + (i & 1)] + acc[2 + (i >> 1)][2 + (i & 1)] : acc[i >> 1][i & 1] + acc[2 + (i >> 1)][i & 1];
        }
        asm volatile("bar.sync 1, 128;" ::: "memory");
        const bool again = ph == 0 && blk + 128 - nblk >= nblk;
        if (again && tid == 224) {
            mbar_expect_tx(jbar, 36864);
            tma3d(sbase + J0W, &p.tm_j0, (blk + 128 - nblk) * 32, 0, 0, jbar, pol);
        }
        if (warp < 6) {
            const float2 v0 = j0[j], v1 = j0[64 + j], v2 = j0[128 + j], v3 = j0[192 + j];
            asm volatile("{\n.reg .pred p;\n.reg .b64 v;\nsetp.ge.s32 p, %3, 0;\nmov.b64 v, {%1, %2};\n@p st.relaxed.gpu.global.u64 [%0], v;\n}"
                         ::"l"(&scratch(p)->qll[(j >> 4) * 2048 + sl * 16 + (j & 15)]),
                           "r"(pack_bf16((v0.x + v1.x) + (v2.x + v3.x), (v0.y + v1.y) + (v2.y + v3.y))), "r"(epoch + 1), "r"(ph) : "memory");
            __syncwarp();
            if (lane == 0 && ph >= 0) asm volatile("red.relaxed.cta.shared::cta.add.u32 [%0], 1;" ::"r"(sbase + M_HELP + 24) : "memory");
        } else if (warp == 7) {
            if (blk < C_LINES && ph == 0) scratch(p)->ctl[(epoch & 1) ^ 1][blk][lane] = 0;
        }
        if (ph >= 0 && !again) break;
        asm volatile("bar.sync 1, 128;" ::: "memory");
        }
    }
    if (CLU) {
        if (warp == 6) {
            if (lane < 24) mbar_init(sbase + F_BAR + lane * 8, 1);
            if (lane < 4) mbar_expect_tx(sbase + F_BAR + lane * 8, 7 * 256);
            asm volatile("fence.mbarrier_init.release.cluster;" ::: "memory");
        }
        asm volatile("barrier.cluster.arrive.relaxed.aligned;" ::: "memory");
    }
    const int c5 = cl % 5;
    const bool partA = CLU && c5 < 3;
    const int nwork = partA && rank == 7 ? 1 : NW + ((CLU ? rank < 2 + X3C && c5 < 4 : (nb & 3) < X3) ? 1 : 0);
    if (isB) {
        b_chain<CLU>(p, smem, sbase, bi, epoch, pol);
        if (!CLU) return;
        if (warp == 2) {
            unsigned n = 0;
            while (ld_acquire(&scratch(p)->ctl[epoch & 1][C_KDONE][0]) < NUK / 2) { __nanosleep(1000); if (++n > SPIN_LIMIT) __trap(); }
        }
    } else if (warp < NW + XW) {
        a_worker<CLU>(p, u0, warp >= nwork, warp < NEARLY && !hold, hold, nstatic, wslot, wbar, sbase + M_HELP,
                      epoch, pol);
        if (!CLU || warp < nwork) return;
        epoch = __shfl_sync(~0u, epoch, 0);
        unsigned n = 0;
        while (ld_acquire_cta_shared(sbase + M_HELP + 12) == 0) { __nanosleep(1000); if (++n > SPIN_LIMIT) __trap(); }
    } else if (warp == 7) {
#pragma unroll 1
        for (int i = nb; i < 4 * NH; i += nnb) scratch(p)->oacc[i * 32 + lane] = make_float4(0.f, 0.f, 0.f, 0.f);
        if (nb < (CLU ? NREPC : NREP) * NH) scratch(p)->vdone[nb][lane] = 0;
        __syncwarp();
        k_helper(p, sbase + M_HELP, epoch);
        if (nb == 0 && lane == 0) scratch(p)->epoch[0] = epoch + 1;
        __syncwarp();
    } else if (!CLU && nb < NFIN) {
        if (warp == 6) {
            finisher(p, sbase, nb);
        } else if (warp >= 6 - NPOLL) {
            v_poller(p, sbase, nb, warp - (6 - NPOLL));
        }
    }
    if (!CLU) return;
    asm volatile("barrier.cluster.wait.acquire.aligned;" ::: "memory");
    const int nsl = c5 == 4 ? 2 : 1, panel = cl / 5 * 3 + (partA ? c5 : c5 - 3);
    if (warp >= 4) {
        f_project(p, rank, warp - 4, nsl, sbase, p.out + (partA ? 0 : DM) + panel * 64);
        return;
    }
    if (isB ? warp == 2 : warp < 3 || nwork == 3)
        f_collect((partA ? scratch(p)->vdone : scratch(p)->cdone) + 4 * rank, partA ? 4 * UPP : epoch + 1,
                  (partA ? scratch(p)->oacc : scratch(p)->octx) + 4 * rank * 128, nwork == 1 ? 5 * warp : 15, sbase);
    if (warp == 3)
        f_request(p, partA ? &p.tm_fa : &p.tm_fb, panel, rank, nsl, nsl == 2 ? T2A + rank * (T2D / 8) : T1A + rank * (T1D / 8),
                  nsl == 2 ? T2D : T1D, epoch + 1, sbase, pol);
}

}

typedef CUresult (*EncodeFn)(CUtensorMap*, CUtensorMapDataType, cuuint32_t, void*, const cuuint64_t*, const cuuint64_t*,
                             const cuuint32_t*, const cuuint32_t*, CUtensorMapInterleave, CUtensorMapSwizzle,
                             CUtensorMapL2promotion, CUtensorMapFloatOOBfill);

extern "C" void kernel_launch(void* const* d_in, const int* in_sizes, int n_in, void* d_out, int out_size) {
    (void)in_sizes; (void)n_in; (void)out_size;
    static int nsm = 0, ncl = 0;
    static EncodeFn encode = nullptr;
    static void* scr = nullptr;
    cudaLaunchConfig_t cfg = {};
    cudaLaunchAttribute at[1];
    at[0].id = cudaLaunchAttributeClusterDimension;
    at[0].val.clusterDim.x = 8; at[0].val.clusterDim.y = 1; at[0].val.clusterDim.z = 1;
    cfg.blockDim = dim3(256); cfg.dynamicSmemBytes = SMEM_BYTES; cfg.stream = cudaStreamPerThread; cfg.attrs = at; cfg.numAttrs = 1;
    if (nsm == 0) {
        int dev = 0;
        cudaGetDevice(&dev);
        cudaDeviceGetAttribute(&nsm, cudaDevAttrMultiProcessorCount, dev);
        cudaFuncSetAttribute(fused_decode_kernel<false>, cudaFuncAttributeMaxDynamicSharedMemorySize, SMEM_BYTES);
        cudaFuncSetAttribute(fused_decode_kernel<true>, cudaFuncAttributeMaxDynamicSharedMemorySize, SMEM_BYTES);
        cfg.gridDim = dim3(128);
        if (cudaOccupancyMaxActiveClusters(&ncl, fused_decode_kernel<true>, &cfg) != cudaSuccess) { ncl = 0; (void)cudaGetLastError(); }
        if (ncl > MINCL) ncl = MINCL;
        void* fn = nullptr;
        cudaDriverEntryPointQueryResult qr;
        cudaGetDriverEntryPoint("cuTensorMapEncodeTiled", &fn, cudaEnableDefault, &qr);
        encode = (EncodeFn)fn;
        cudaGetSymbolAddress(&scr, g_scratch);
    }
    Params p;
    auto panels = [&](CUtensorMap* tm, void* ptr, int rows, int cols, int box_rows, int box_panels,
                      CUtensorMapL2promotion promo = CU_TENSOR_MAP_L2_PROMOTION_L2_256B) {
        const cuuint64_t gd[3] = {64, (cuuint64_t)rows, (cuuint64_t)(cols / 64)}, gs[2] = {(cuuint64_t)cols * 2, 128};
        const cuuint32_t box[3] = {64, (cuuint32_t)box_rows, (cuuint32_t)box_panels}, es[3] = {1, 1, 1};
        encode(tm, CU_TENSOR_MAP_DATA_TYPE_BFLOAT16, 3, ptr, gd, gs, box, es, CU_TENSOR_MAP_INTERLEAVE_NONE,
               CU_TENSOR_MAP_SWIZZLE_128B, promo, CU_TENSOR_MAP_FLOAT_OOB_FILL_NONE);
    };
    panels(&p.tm_wq, d_in[7], DM, 4096, 128, 2);
    panels(&p.tm_wuk, d_in[8], 512, 4096, 128, 2);
    panels(&p.tm_wuv, d_in[9], 512, 4096, 128, 2);
    panels(&p.tm_wo, d_in[10], 4096, DM, 32, 9);
    panels(&p.tm_ckv, d_in[6], 4 * SK, 512, 32, 8);
    panels(&p.tm_fa, d_in[4], 4096, DM, 64, 1, CU_TENSOR_MAP_L2_PROMOTION_L2_128B);
    panels(&p.tm_fb, d_in[10], 4096, DM, 64, 1, CU_TENSOR_MAP_L2_PROMOTION_L2_128B);
    {
        const cuuint64_t gd[3] = {4096, 192, 3}, gs[2] = {8192, 192 * 8192};
        const cuuint32_t box[3] = {32, 192, 3}, es[3] = {1, 1, 1};
        encode(&p.tm_j0, CU_TENSOR_MAP_DATA_TYPE_BFLOAT16, 3, d_in[3], gd, gs, box, es, CU_TENSOR_MAP_INTERLEAVE_NONE,
               CU_TENSOR_MAP_SWIZZLE_64B, CU_TENSOR_MAP_L2_PROMOTION_L2_128B, CU_TENSOR_MAP_FLOAT_OOB_FILL_NONE);
    }
    p.xa = (const __nv_bfloat16*)d_in[0];
    p.kc = (const __nv_bfloat16*)d_in[1];
    p.vc = (const __nv_bfloat16*)d_in[2];
    p.wo = (const __nv_bfloat16*)d_in[4];
    p.xb = (const __nv_bfloat16*)d_in[5];
    p.out = (__nv_bfloat16*)d_out;
    p.s = (Scratch*)scr;
    if (ncl >= MINCL) {
        cfg.gridDim = dim3(8 * ncl);
        cudaLaunchKernelEx(&cfg, fused_decode_kernel<true>, p);
    } else {
        fused_decode_kernel<false><<<nsm, 256, SMEM_BYTES, cudaStreamPerThread>>>(p);
    }
}
```

```cpp
#include <cuda_runtime.h>
#include <cuda.h>
#include <cuda_bf16.h>
#include <stdint.h>

namespace {

constexpr int NH = 32, SK = 4096, DM = 576;
constexpr int KEYS = 128;
constexpr int UPP = SK / KEYS;
constexpr int NUK = 4 * NH * UPP;
constexpr int TILE_BYTES = KEYS * 256;
#define NWORK 2
constexpr int NW = NWORK;
constexpr int NBCTA = 32;
constexpr int MINCL = 15;
constexpr int NFIN = 72;
constexpr int SLOT = 32768;
constexpr int NSLOT = 6;
constexpr int BRING = 5;
constexpr int J0W = 5 * SLOT;
constexpr int MISC = NSLOT * SLOT + 4096;
constexpr int XP = 1168, CP = 1040, QP = 272;
constexpr int M_XA = MISC;
constexpr int M_XB = M_XA + 4 * XP;
constexpr int M_CH = M_XB + 4 * XP;
constexpr int M_CL = M_CH + 4 * CP;
constexpr int M_QB = M_CL + 4 * CP;
constexpr int M_QA = M_CH;
constexpr int M_J0 = M_QB + 4 * QP;
constexpr int M_P = M_J0 + 2048;
constexpr int M_ALPHA = M_P + 2560;
constexpr int M_OMEGA = M_ALPHA + 128;
constexpr int M_BAR = M_OMEGA + 128;
constexpr int M_HELP = M_BAR + 128;
constexpr int F_W = 4 * SLOT;
constexpr int F_BF = (M_HELP + 383) / 256 * 256;
constexpr int F_RX = NSLOT * SLOT;
constexpr int F_BAR = F_BF + 4096;
constexpr int SMEM_BYTES = F_BAR + 200 + 1024;
static_assert(SMEM_BYTES <= 232448 && F_RX + 7168 <= M_XB && M_BAR % 8 == 0 && M_QA % 16 == 0 && M_P % 16 == 0, "smem layout");
#define XW 2
#define X3 1
#define X3C 3
#define NEARLY 2
#define LATE 2000
#define BD 5
#define FPF 3
#define FSLEEP 800
#define PFN 96
#define EARLY 100
#define ELOG 5
#define TPU 159
#define T1A (1590 + 200 * X3C)
#define T1D 390
#define T2A (T1A - 340)
#define T2D 195
#define TOWN 90
#define LAG 5
#define NPOLL 2
#define PGAP 200
static_assert(X3C <= 4 && NW == 2 && XW == 2 && MINCL == 15, "roles of the cluster launch");
static_assert(NW + XW <= 4 && NEARLY <= NW + XW && BD <= BRING, "slots 4 and 5 hold the finisher weights");
constexpr float SCALE = 0.08838834764831845f;
constexpr float LOG2E = 1.4426950408889634f;
constexpr unsigned SPIN_LIMIT = 1u << 24;

#define NREP 2
#define NREPC 1
constexpr int C_QUEUE = 0, C_KDONE = 1, C_BBAR = 3, C_LINES = 5;

struct Scratch {
    unsigned epoch[32];
    unsigned ctl[2][C_LINES][32];
    uint2 qll[4 * 2048];
    uint2 scores[128 * SK / 4];
    float2 stats[128 * UPP];
    float4 oacc[128 * 32];
    unsigned vdone[NREP * NH][32];
    float4 octx[128 * 32];
    unsigned cdone[NH][32];
    unsigned long long dry[16][16];
    uint4 qabs[4 * 8 * 4 * 4 * 32];
    float2 bpart[NBCTA * NH * 256];
    float2 bml[NBCTA * NH];
    uint4 outb[NBCTA * NH * 36];
};
__device__ __align__(256) Scratch g_scratch;

struct Params {
    const __nv_bfloat16 *kc, *xa, *vc, *wo, *xb;
    __nv_bfloat16* out;
    Scratch* s;
    CUtensorMap tm_j0;
    CUtensorMap tm_wq, tm_wuk, tm_ckv, tm_wuv, tm_wo;
    CUtensorMap tm_fa, tm_fb;
};

__device__ __forceinline__ Scratch* scratch(const Params& p) {
    Scratch* s = p.s;
    __builtin_assume(__isGlobal(s));
    return s;
}

__device__ __forceinline__ uint32_t smem_u32(const void* p) { return (uint32_t)__cvta_generic_to_shared(p); }
__device__ __forceinline__ void mbar_init(uint32_t bar, uint32_t cnt) {
    asm volatile("mbarrier.init.shared::cta.b64 [%0], %1;" ::"r"(bar), "r"(cnt) : "memory");
}
__device__ __forceinline__ void mbar_expect_tx(uint32_t bar, uint32_t bytes) {
    asm volatile("mbarrier.arrive.expect_tx.shared::cta.b64 _, [%0], %1;" ::"r"(bar), "r"(bytes) : "memory");
}
__device__ __forceinline__ bool mbar_try(uint32_t bar, uint32_t parity) {
    uint32_t ok;
    asm volatile("{\n.reg .pred p;\nmbarrier.try_wait.parity.shared::cta.b64 p, [%1], %2;\nselp.u32 %0, 1, 0, p;\n}\n"
                 : "=r"(ok) : "r"(bar), "r"(parity) : "memory");
    return ok;
}
__device__ __forceinline__ void mbar_wait(uint32_t bar, uint32_t parity) {
    unsigned n = 0;
    while (!mbar_try(bar, parity)) { if (++n > SPIN_LIMIT) __trap(); }
}
__device__ __forceinline__ void mbar_spin(uint32_t bar) {
    asm volatile("{\n.reg .pred p;\n.reg .u32 n;\nmov.u32 n, 0;\nSPIN:\nmbarrier.try_wait.parity.shared::cta.b64 p, [%0], 0;\n@p bra.uni DONE;\n"
                 "add.u32 n, n, 1;\nsetp.lt.u32 p, n, 0x1000000;\n@p bra.uni SPIN;\ntrap;\nDONE:\n}" ::"r"(bar) : "memory");
}
__device__ __forceinline__ void mbar_spin_cluster(uint32_t bar) {
    asm volatile("{\n.reg .pred p;\n.reg .u32 n;\nmov.u32 n, 0;\nSPIN:\nmbarrier.try_wait.parity.relaxed.cluster.shared::cta.b64 p, [%0], 0;\n"
                 "@p bra.uni DONE;\nadd.u32 n, n, 1;\nsetp.lt.u32 p, n, 0x1000000;\n@p bra.uni SPIN;\ntrap;\nDONE:\n"
                 "fence.acquire.sync_restrict::shared::cluster.cluster;\n}" ::"r"(bar) : "memory");
}
__device__ __forceinline__ void bulk_load(uint32_t dst, const void* src, uint32_t bytes, uint32_t bar, uint64_t pol) {
    asm volatile("cp.async.bulk.shared::cluster.global.mbarrier::complete_tx::bytes.L2::cache_hint [%0], [%1], %2, [%3], %4;"
                 ::"r"(dst), "l"(src), "r"(bytes), "r"(bar), "l"(pol) : "memory");
}
__device__ __forceinline__ void mbar_init_warp(uint32_t bar) {
    asm volatile("{\n.reg .pred p;\nelect.sync _|p, 0xffffffff;\n@p mbarrier.init.shared::cta.b64 [%0], 1;\n@p fence.mbarrier_init.release.cluster;\n}"
                 ::"r"(bar) : "memory");
}
__device__ __forceinline__ void tile_load_warp(uint32_t dst, const void* src, uint32_t bar, uint64_t pol) {
    asm volatile("{\n.reg .pred p;\nelect.sync _|p, 0xffffffff;\n@p mbarrier.arrive.expect_tx.shared::cta.b64 _, [%2], %4;\n"
                 "@p cp.async.bulk.shared::cluster.global.mbarrier::complete_tx::bytes.L2::cache_hint [%0], [%1], %4, [%2], %3;\n}"
                 ::"r"(dst), "l"(src), "r"(bar), "l"(pol), "n"(TILE_BYTES) : "memory");
}
__device__ __forceinline__ void tma3d_warp(uint32_t dst, const CUtensorMap* tm, int c0, int c1, int c2, uint32_t bar, uint32_t bytes, uint64_t pol) {
    asm volatile("{\n.reg .pred p;\nelect.sync _|p, 0xffffffff;\n@p mbarrier.arrive.expect_tx.shared::cta.b64 _, [%2], %7;\n"
                 "@p cp.async.bulk.tensor.3d.shared::cluster.global.mbarrier::complete_tx::bytes.L2::cache_hint [%0], [%1, {%3,%4,%5}], [%2], %6;\n}"
                 ::"r"(dst), "l"(tm), "r"(bar), "r"(c0), "r"(c1), "r"(c2), "l"(pol), "r"(bytes) : "memory");
}
__device__ __forceinline__ void tma3d(uint32_t dst, const CUtensorMap* tm, int c0, int c1, int c2, uint32_t bar, uint64_t pol) {
    asm volatile("cp.async.bulk.tensor.3d.shared::cluster.global.mbarrier::complete_tx::bytes.L2::cache_hint [%0], [%1, {%3,%4,%5}], [%2], %6;"
                 ::"r"(dst), "l"(tm), "r"(bar), "r"(c0), "r"(c1), "r"(c2), "l"(pol) : "memory");
}
__device__ __forceinline__ void l2_prefetch(const void* src, uint32_t bytes) {
    asm volatile("cp.async.bulk.prefetch.L2.global [%0], %1;" ::"l"(src), "r"(bytes) : "memory");
}
__device__ __forceinline__ void ldsm4(uint32_t (&r)[4], uint32_t addr) {
    asm volatile("ldmatrix.sync.aligned.m8n8.x4.shared.b16 {%0,%1,%2,%3}, [%4];"
                 : "=r"(r[0]), "=r"(r[1]), "=r"(r[2]), "=r"(r[3]) : "r"(addr));
}
__device__ __forceinline__ void ldsm4t(uint32_t (&r)[4], uint32_t addr) {
    asm volatile("ldmatrix.sync.aligned.m8n8.x4.trans.shared.b16 {%0,%1,%2,%3}, [%4];"
                 : "=r"(r[0]), "=r"(r[1]), "=r"(r[2]), "=r"(r[3]) : "r"(addr));
}
__device__ __forceinline__ void mma16816(float (&d)[4], const uint32_t (&a)[4], uint32_t b0, uint32_t b1) {
    asm("mma.sync.aligned.m16n8k16.row.col.f32.bf16.bf16.f32 {%0,%1,%2,%3}, {%4,%5,%6,%7}, {%8,%9}, {%0,%1,%2,%3};"
        : "+f"(d[0]), "+f"(d[1]), "+f"(d[2]), "+f"(d[3])
        : "r"(a[0]), "r"(a[1]), "r"(a[2]), "r"(a[3]), "r"(b0), "r"(b1));
}
__device__ __forceinline__ uint32_t lds32(uint32_t a) {
    uint32_t v;
    asm volatile("ld.shared.u32 %0, [%1];" : "=r"(v) : "r"(a));
    return v;
}
__device__ __forceinline__ unsigned ld_acquire(const unsigned* p) {
    unsigned v;
    asm volatile("ld.acquire.gpu.global.u32 %0, [%1];" : "=r"(v) : "l"(p) : "memory");
    return v;
}
__device__ __forceinline__ uint2 ld_relaxed8(const void* p) {
    uint2 v;
    asm volatile("ld.relaxed.gpu.global.v2.u32 {%0,%1}, [%2];" : "=r"(v.x), "=r"(v.y) : "l"(p) : "memory");
    return v;
}
__device__ __forceinline__ unsigned ld_relaxed4(const void* p) {
    unsigned v;
    asm volatile("ld.relaxed.gpu.global.u32 %0, [%1];" : "=r"(v) : "l"(p) : "memory");
    return v;
}
__device__ __forceinline__ unsigned atom_inc(unsigned* p) {
    unsigned v;
    asm volatile("atom.relaxed.gpu.global.inc.u32 %0, [%1], 0x7fffffff;" : "=r"(v) : "l"(p) : "memory");
    return v;
}
__device__ __forceinline__ unsigned long long ld_relaxed64(const void* p) {
    unsigned long long v;
    asm volatile("ld.relaxed.gpu.global.u64 %0, [%1];" : "=l"(v) : "l"(p) : "memory");
    return v;
}
__device__ __forceinline__ void st_relaxed64(void* p, unsigned long long v) {
    asm volatile("st.relaxed.gpu.global.u64 [%0], %1;" ::"l"(p), "l"(v) : "memory");
}
__device__ __forceinline__ float4 ld_relaxed16(const void* p) {
    float4 v;
    asm volatile("ld.relaxed.gpu.global.v4.f32 {%0,%1,%2,%3}, [%4];" : "=f"(v.x), "=f"(v.y), "=f"(v.z), "=f"(v.w) : "l"(p) : "memory");
    return v;
}
__device__ __forceinline__ uint32_t mapa(uint32_t a, uint32_t rank) {
    uint32_t r;
    asm("mapa.shared::cluster.u32 %0, %1, %2;" : "=r"(r) : "r"(a), "r"(rank));
    return r;
}
__device__ __forceinline__ uint32_t time_ns() { uint32_t t; asm volatile("mov.u32 %0, %globaltimer_lo;" : "=r"(t)); return t; }
__device__ __forceinline__ void fence_gpu() { asm volatile("fence.acq_rel.gpu;" ::: "memory"); }
__device__ __forceinline__ void red_add_u32(unsigned* p, unsigned v) {
    asm volatile("red.relaxed.gpu.global.add.u32 [%0], %1;" ::"l"(p), "r"(v) : "memory");
}
__device__ __forceinline__ void st_tagged2(void* p, float a, float b, unsigned tag) {
    const unsigned long long hi = (unsigned long long)tag << 32;
    asm volatile("st.relaxed.gpu.global.v2.b64 [%0], {%1,%2};" ::"l"(p), "l"(hi | __float_as_uint(a)), "l"(hi | __float_as_uint(b)) : "memory");
}
__device__ __forceinline__ ulonglong2 ld_tagged2(const void* p) {
    ulonglong2 v;
    asm volatile("ld.relaxed.gpu.global.v2.b64 {%0,%1}, [%2];" : "=l"(v.x), "=l"(v.y) : "l"(p) : "memory");
    return v;
}
__device__ __forceinline__ float4 atom_add_f4(void* p, float a, float b, float c, float d) {
    float4 r;
    asm volatile("atom.relaxed.gpu.global.add.v4.f32 {%0,%1,%2,%3}, [%4], {%5,%6,%7,%8};"
                 : "=f"(r.x), "=f"(r.y), "=f"(r.z), "=f"(r.w) : "l"(p), "f"(a), "f"(b), "f"(c), "f"(d) : "memory");
    return r;
}
__device__ __forceinline__ void red_release_cta_shared(uint32_t a, unsigned v) {
    asm volatile("red.release.cta.shared::cta.add.u32 [%0], %1;" ::"r"(a), "r"(v) : "memory");
}
__device__ __forceinline__ unsigned ld_acquire_cta_shared(uint32_t a) {
    unsigned v;
    asm volatile("ld.acquire.cta.shared::cta.u32 %0, [%1];" : "=r"(v) : "r"(a) : "memory");
    return v;
}
__device__ __forceinline__ void st_release_cta_shared(uint32_t a, unsigned v) {
    asm volatile("st.release.cta.shared::cta.u32 [%0], %1;" ::"r"(a), "r"(v) : "memory");
}
__device__ __forceinline__ void wait_count(const unsigned* p, unsigned target) {
    unsigned n = 0;
    while (ld_acquire(p) < target) { if (++n > SPIN_LIMIT) __trap(); }
}
__device__ __forceinline__ uint32_t pack_bf16(float lo, float hi) {
    uint32_t r;
    asm("cvt.rn.bf16x2.f32 %0, %1, %2;" : "=r"(r) : "f"(hi), "f"(lo));
    return r;
}
__device__ __forceinline__ float bf_lo(uint32_t v) { return __uint_as_float(v << 16); }
__device__ __forceinline__ float bf_hi(uint32_t v) { return __uint_as_float(v & 0xffff0000u); }
__device__ __forceinline__ float ex2(float x) { float y; asm("ex2.approx.ftz.f32 %0, %1;" : "=f"(y) : "f"(x)); return y; }
__device__ __forceinline__ float expsub(float a, float b) { return ex2((a - b) * LOG2E); }
__device__ __forceinline__ float warp_max(float v) {
#pragma unroll
    for (int m = 16; m; m >>= 1) v = fmaxf(v, __shfl_xor_sync(~0u, v, m));
    return v;
}
__device__ __forceinline__ float warp_sum(float v) {
#pragma unroll
    for (int m = 16; m; m >>= 1) v += __shfl_xor_sync(~0u, v, m);
    return v;
}
__device__ __forceinline__ unsigned unit_block(int u) {
    const unsigned x = (unsigned)u & (NUK - 1);
    if (u < 512) return ((x & 96) << 2) | ((x >> 2) & 96) | (x & 31);
    if (u < NUK) return (x & ~127u) | ((x & 3) << 5) | ((x >> 2) & 31);
    return (x & ~255u) | ((x & 64) << 1) | ((x >> 1) & 64) | ((x & 1) << 5) | ((x >> 1) & 31);
}
__device__ __forceinline__ const char* block_src(const void* base, unsigned blk) {
    const unsigned po = blk / UPP;
    return reinterpret_cast<const char*>(base) + (size_t)(((po & 3) * NH + (po >> 2)) * UPP + blk % UPP) * TILE_BYTES;
}

template <bool CLU>
__device__ __forceinline__ void a_worker(const Params& p, int un, bool once, bool pre, bool hold, int nstatic, uint32_t slot, uint32_t bar,
                                         uint32_t help, unsigned epoch, uint64_t pol) {
    constexpr int NU = 2 * NUK, NR = CLU ? NREPC : NREP;
    const int lane = threadIdx.x & 31, g = lane >> 2, t = lane & 3;
    const int li = lane & 7;
    uint32_t kaddr[4], vaddr[8];
    {
        const int e = (lane >> 3) & 1, kk = lane >> 4;
#pragma unroll
        for (int s = 0; s < 4; s++) kaddr[s] = slot + (16 * li + e) * 256 + ((2 * s + kk + li) & 7) * 16;
        const int vrow = 4 * (li >> 1) + (li & 1) + 2 * kk;
#pragma unroll
        for (int c = 0; c < 8; c++) vaddr[c] = slot + vrow * 256 + e * 128 + ((c + li) & 7) * 16;
#pragma unroll
        for (int c = 0; c < 8; c++) asm volatile("" : "+r"(vaddr[c]));
    }
    const uint32_t vmask = (g >> 1) != t ? 0u : ((g & 1) ? 0xffff0000u : 0xffffu);
    int kseen = -1;
    unsigned long long H0 = 0, H1 = 0;
    auto header = [&](int v, unsigned vb) {
        const void *a0, *a1;
        if (v < NUK) {
            const unsigned po = vb / UPP;
            a0 = scratch(p)->qll + (po & 3) * 2048 + (po >> 2) * 64 + lane;
            a1 = reinterpret_cast<const uint2*>(a0) + 32;
        } else {
            const int half = vb / (NUK / 2);
            if (half > kseen) {
                unsigned n = 0;
                while (ld_acquire_cta_shared(help + 12 + 4 * half) == 0) { if (++n > (SPIN_LIMIT << 4)) __trap(); }
                kseen = half;
            }
            a0 = &scratch(p)->scores[vb * (KEYS / 4) + lane];
            a1 = &scratch(p)->stats[(vb / UPP) * UPP + lane];
        }
        H0 = ld_relaxed64(a0);
        H1 = ld_relaxed64(a1);
    };
    unsigned bu = 0, bn = unit_block(un);
    asm volatile("bar.sync 2, %0;" ::"n"(32 * (NW + XW + 1)) : "memory");
    if (!pre && !hold) { const uint32_t t0 = clock(); while ((uint32_t)clock() - t0 < ((threadIdx.x >> 5) - NEARLY + 1) * LATE) {} }
    epoch = __shfl_sync(~0u, epoch, 0);
    if (hold) { unsigned n = 0; while (ld_acquire_cta_shared(help + 24) < 2) { if (++n > (SPIN_LIMIT << 4)) __trap(); } }
    unsigned (*ctl)[32] = scratch(p)->ctl[epoch & 1];
    const unsigned tag = epoch + 1;
    unsigned nxt = once ? NU : 0;
    int u = -1;
    uint32_t phase = 0;
    unsigned kpend = 0;
    const unsigned zero = gridDim.x >> 24;
    uint32_t Q[16];
    float4 oret = make_float4(0.f, 0.f, 0.f, 0.f);
    while (true) {
        const char* nsrc = block_src(un < NUK ? p.kc : p.vc, bn);
        float4* odst = &scratch(p)->oacc[(bu / UPP) * 32 + lane];
        unsigned* vdst = &scratch(p)->vdone[(lane & (NR - 1)) * NH + bu / (4 * UPP)][0];
        float d[8][4];
        uint32_t act = un >= NU ? 0u : (u >= 0 || !pre ? 1u : 0u) | (!once && lane == 0 ? 2u : 0u);
        asm volatile("" : "+l"(odst), "+l"(nsrc), "+r"(act));
        if (u >= NUK) {
#pragma unroll
            for (int j = 0; j < 8; j++) { d[j][0] = d[j][1] = d[j][2] = d[j][3] = 0.f; }
            mbar_wait(bar, phase);
            uint32_t a[2][8][4];
#pragma unroll
            for (int c = 0; c < 8; c++) ldsm4t(a[0][c], vaddr[c]);
#pragma unroll
            for (int j = 0; j < 8; j++) {
                if (j < 7) {
#pragma unroll
                    for (int c = 0; c < 8; c++) ldsm4t(a[(j + 1) & 1][c], vaddr[c] + (j + 1) * 4096);
                }
#pragma unroll
                for (int c = 0; c < 8; c++) mma16816(d[c], a[j & 1][c], Q[2 * j], Q[2 * j + 1]);
            }
            float o[4];
#pragma unroll
            for (int r = 0; r < 2; r++) {
                o[2 * r] = d[0][2 * r] + d[7][2 * r + 1];
                o[2 * r + 1] = d[0][2 * r + 1] + d[1][2 * r];
#pragma unroll
                for (int k = 1; k < 4; k++) {
                    const int src = (lane & 28) | ((t - k) & 3);
                    o[2 * r] += __shfl_sync(~0u, d[2 * k][2 * r] + d[2 * k - 1][2 * r + 1], src);
                    o[2 * r + 1] += __shfl_sync(~0u, d[2 * k][2 * r + 1] + d[2 * k + 1][2 * r], src);
                }
            }
            oret = atom_add_f4(odst, o[0], o[1], o[2], o[3]);
        } else if (u >= 0) {
#pragma unroll
            for (int j = 0; j < 8; j++) { d[j][0] = d[j][1] = d[j][2] = d[j][3] = 0.f; }
            mbar_wait(bar, phase);
            uint32_t a[2][8][4];
#pragma unroll
            for (int j = 0; j < 8; j++) ldsm4(a[0][j], kaddr[0] + (4 * (j & 3) + 2 * (j >> 2)) * 256);
#pragma unroll
            for (int s = 0; s < 8; s++) {
                if (s < 7) {
#pragma unroll
                    for (int j = 0; j < 8; j++)
                        ldsm4(a[(s + 1) & 1][j], kaddr[(s + 1) & 3] + (4 * (j & 3) + 2 * (j >> 2)) * 256 + ((s + 1) >> 2) * 128);
                }
#pragma unroll
                for (int j = 0; j < 8; j++)
                    mma16816(d[j], a[s & 1][j], Q[(s & 4) * 2 + ((2 * s - 2 * j) & 7)], Q[(s & 4) * 2 + ((2 * s + 1 - 2 * j) & 7)]);
            }
        }
        if (u >= 0) phase ^= 1;
        asm volatile("{\n.reg .pred p, q;\n.reg .u32 a;\nelect.sync _|p, 0xffffffff;\nand.b32 a, %5, 1;\nsetp.ne.and.u32 q, a, 0, p;\n"
                     "@q mbarrier.arrive.expect_tx.shared::cta.b64 _, [%2], %4;\n"
                     "@q cp.async.bulk.shared::cluster.global.mbarrier::complete_tx::bytes.L2::cache_hint [%0], [%1], %4, [%2], %3;\n}"
                     ::"r"(slot), "l"(nsrc), "r"(bar), "l"(pol), "n"(TILE_BYTES), "r"(act) : "memory");
        if (act & 2) nxt = atom_inc(&ctl[C_QUEUE][0]);
        const uint32_t tk = clock();
        if ((unsigned)u < (unsigned)NUK) {
            const int j0 = (t - (g >> 1)) & 3;
            float v[4];
#pragma unroll
            for (int q = 0; q < 4; q++) {
                const int jq = (q >> 1) * 4, e = (q & 1) * 2;
                const float x0 = (g & 1) ? d[jq + 0][e + 1] : d[jq + 0][e];
                const float x1 = (g & 1) ? d[jq + 1][e + 1] : d[jq + 1][e];
                const float x2 = (g & 1) ? d[jq + 2][e + 1] : d[jq + 2][e];
                const float x3 = (g & 1) ? d[jq + 3][e + 1] : d[jq + 3][e];
                const float y0 = (j0 & 1) ? x1 : x0, y1 = (j0 & 1) ? x3 : x2;
                v[q] = (j0 & 2) ? y1 : y0;
            }
            const uint32_t r0 = pack_bf16(v[0], v[1]), r1 = pack_bf16(v[2], v[3]);
            const uint32_t s0 = pack_bf16(bf_lo(r0) * SCALE, bf_hi(r0) * SCALE);
            const uint32_t s1 = pack_bf16(bf_lo(r1) * SCALE, bf_hi(r1) * SCALE);
            scratch(p)->scores[bu * (KEYS / 4) + 4 * g + j0] = make_uint2(s0, s1);
            const float f0 = bf_lo(s0), f1 = bf_hi(s0), f2 = bf_lo(s1), f3 = bf_hi(s1);
            const float m = warp_max(fmaxf(fmaxf(f0, f1), fmaxf(f2, f3)));
            const float l = warp_sum((expsub(f0, m) + expsub(f1, m)) + (expsub(f2, m) + expsub(f3, m)));
            if (lane == 0) scratch(p)->stats[bu] = make_float2(m, l);
            kpend++;
            if (un / (NUK / 2) != u / (NUK / 2)) {
                __syncwarp();
                if (lane == 0) {
                    red_release_cta_shared(help + 4 * (u / (NUK / 2)), kpend);
                    if (un >= NUK) red_release_cta_shared(help + 8, 1u);
                }
                kpend = 0;
            }
        }
        int unn = NU;
        if (un < NU) {
            unsigned n = 0;
            while (true) {
                header(un, bn);
                if (un >= NUK || __all_sync(~0u, (uint32_t)(H0 >> 32) == tag && (uint32_t)(H1 >> 32) == tag)) break;
                if (++n > SPIN_LIMIT) __trap();
            }
            if (un >= NUK) {
                const uint32_t s0 = (uint32_t)H0, s1 = (uint32_t)(H0 >> 32);
                const float mu = __uint_as_float((uint32_t)H1);
                const float m = warp_max(mu);
                const float l = warp_sum(__uint_as_float((uint32_t)(H1 >> 32)) * expsub(mu, m));
                const float inv = 1.0f / l;
                const uint32_t w0 = pack_bf16(expsub(bf_lo(s0), m) * inv, expsub(bf_hi(s0), m) * inv);
                const uint32_t w1 = pack_bf16(expsub(bf_lo(s1), m) * inv, expsub(bf_hi(s1), m) * inv);
#pragma unroll
                for (int j = 0; j < 8; j++) {
                    Q[2 * j] = __shfl_sync(~0u, w0, 4 * j + t) & vmask;
                    Q[2 * j + 1] = __shfl_sync(~0u, w1, 4 * j + t) & vmask;
                }
            } else {
#pragma unroll
                for (int j = 0; j < 8; j++) {
                    const int src = (((j + g) & 7) << 2) + t;
                    Q[j] = __shfl_sync(~0u, (uint32_t)H0, src);
                    Q[8 + j] = __shfl_sync(~0u, (uint32_t)H1, src);
                }
            }
            unn = nstatic + (int)__shfl_sync(~0u, nxt, 0);
            if (CLU && ((NU - EARLY - unn) & ~(7 << ELOG)) == 0 && lane < MINCL)
                st_relaxed64(&scratch(p)->dry[lane][(NU - EARLY - unn) >> ELOG],
                             (time_ns() - (((uint32_t)clock() - tk) >> 1) + (NU - unn) * TPU / 16) | (unsigned long long)tag << 32);
        }
        if (u >= NUK && lane < NR)
            red_add_u32(vdst,
                        1u + ((__float_as_uint(oret.x) | __float_as_uint(oret.y) | __float_as_uint(oret.z) | __float_as_uint(oret.w)) & zero));
        if (un >= NU) break;
        bu = bn;
        bn = unit_block(unn);
        u = un;
        un = unn;
    }
}

__device__ __forceinline__ void k_helper(const Params& p, uint32_t help, unsigned epoch) {
    if ((threadIdx.x & 31) != 0) return;
    unsigned (*ctl)[32] = scratch(p)->ctl[epoch & 1];
    unsigned sent0 = 0, sent1 = 0, n = 0;
    int seen = 0;
    bool fin = false;
    while (!fin || seen < 2) {
        if (!fin) {
            fin = ld_acquire_cta_shared(help + 8) == NW + XW;
            const unsigned c0 = ld_acquire_cta_shared(help), c1 = ld_acquire_cta_shared(help + 4);
            if (c0 != sent0 || c1 != sent1) {
                fence_gpu();
                if (c0 != sent0) red_add_u32(&ctl[C_KDONE][0], c0 - sent0);
                if (c1 != sent1) red_add_u32(&ctl[C_KDONE + 1][0], c1 - sent1);
                sent0 = c0; sent1 = c1;
            }
        }
        if (seen < 2 && ld_acquire(&ctl[C_KDONE + seen][0]) >= NUK / 2) {
            st_release_cta_shared(help + 12 + 4 * seen, 1u);
            seen++;
        } else {
            __nanosleep(300);
        }
        if (++n > SPIN_LIMIT) __trap();
    }
}

__device__ __forceinline__ void v_poller(const Params& p, uint32_t sbase, int f, int w) {
    constexpr int HL = NH;
    const int lane = threadIdx.x & 31;
    const unsigned (*cp)[32] = &scratch(p)->vdone[((f * NPOLL + w) % NREP) * NH];
    unsigned n = 0;
    while (ld_acquire_cta_shared(sbase + M_HELP + 12) == 0) { __nanosleep(1000); if (++n > SPIN_LIMIT) __trap(); }
    int h = 0;
    bool fast = false;
    while (h < HL) {
        const unsigned r = __ballot_sync(~0u, ld_acquire(&cp[min(h + (lane & 3), HL - 1)][0]) >= 4 * UPP) & 15u;
        if (r & 1) {
            h = min(HL, h + __ffs(~r) - 1);
            __syncwarp();
            if (lane == 0) asm volatile("red.release.cta.shared::cta.max.u32 [%0], %1;" ::"r"(sbase + M_HELP + 20), "r"(h) : "memory");
        }
        if (h < HL - 4) {
            __nanosleep(h ? 300 : 1000);
        } else if (!fast) {
            fast = true;
            const long long t0 = clock64();
            while (clock64() - t0 < w * PGAP) {}
        }
        if (++n > SPIN_LIMIT) __trap();
    }
}
__device__ __forceinline__ void finisher(const Params& p, uint32_t sbase, int f) {
    constexpr int HL = NH;
    const int lane = threadIdx.x & 31;
    {
        const char* wg = reinterpret_cast<const char*>(p.wo);
        const uint32_t dst = sbase + 4 * SLOT + (16 * (lane & 7) + (lane >> 3)) * 16;
#pragma unroll 1
        for (int h = -FPF - 4; h < HL; h++) {
            if (lane == 0 && (unsigned)(h + FPF) < (unsigned)HL) l2_prefetch(wg + (size_t)(h + FPF) * 147456 + f * 2048, 2048);
            if (h >= 0) {
#pragma unroll
                for (int r = 0; r < 4; r++)
                    asm volatile("cp.async.cg.shared.global [%0], [%1], 16;" ::"r"(dst + h * 2048 + ((r & 1) * 4 + (r >> 1) * 8) * 16),
                                 "l"(wg + (size_t)(h * 128 + r * 32 + lane) * (DM * 2) + f * 16) : "memory");
            }
            __nanosleep(FSLEEP);
        }
        asm volatile("cp.async.wait_all;" ::: "memory");
        __syncwarp();
    }
    const float4* vec = scratch(p)->oacc + ((lane >> 2) & 3) * 32 + (lane >> 4) * 16 + (lane & 3);
    float acc[2][2][4];
#pragma unroll
    for (int i = 0; i < 16; i++) acc[i >> 3][(i >> 2) & 1][i & 3] = 0.f;
    uint32_t* outp = reinterpret_cast<uint32_t*>(p.out + (lane >> 2) * (2 * DM) + f * 8 + (lane & 3) * 2);
    uint32_t wa = sbase + 4 * SLOT + lane * 16;
    auto project = [&](const float4 (&x)[4], const uint32_t (&w)[4][4]) {
#pragma unroll
        for (int s = 0; s < 4; s++) {
            const uint32_t a[4] = {pack_bf16(x[s].x, x[s].y), 0u, pack_bf16(x[s].z, x[s].w), 0u};
            mma16816(acc[0][s & 1], a, w[s >> 1][(s & 1) * 2], w[s >> 1][(s & 1) * 2 + 1]);
            mma16816(acc[1][s & 1], a, w[2 + (s >> 1)][(s & 1) * 2], w[2 + (s >> 1)][(s & 1) * 2 + 1]);
        }
    };
    int h = 0;
    unsigned n = 0;
    while (h < HL) {
        uint32_t w[4][4];
#pragma unroll
        for (int q = 0; q < 4; q++) ldsm4t(w[q], wa + q * 512);
        int ready;
        while ((ready = ld_acquire_cta_shared(sbase + M_HELP + 20)) <= h) {
            if (h < HL - 3) __nanosleep(100);
            if (++n > (SPIN_LIMIT << 4)) __trap();
        }
        float4 x[4], y[4];
#pragma unroll
        for (int s = 0; s < 4; s++) x[s] = ld_relaxed16(vec + s * 4);
        const bool two = ready > h + 1;
        if (two) {
#pragma unroll
            for (int s = 0; s < 4; s++) y[s] = ld_relaxed16(vec + 128 + s * 4);
        }
        project(x, w);
        if (two) {
#pragma unroll
            for (int q = 0; q < 4; q++) ldsm4t(w[q], wa + 2048 + q * 512);
            project(y, w);
        }
        const int nr = two ? 2 : 1;
        h += nr;
        vec += nr * 128;
        wa += nr * 2048;
        const float o0 = acc[0][0][0] + acc[0][1][0] + __shfl_down_sync(~0u, acc[1][0][0] + acc[1][1][0], 16);
        const float o1 = acc[0][0][1] + acc[0][1][1] + __shfl_down_sync(~0u, acc[1][0][1] + acc[1][1][1], 16);
        asm volatile("{\n.reg .pred p;\nsetp.ne.u32 p, %2, 0;\n@p st.global.u32 [%0], %1;\n}" ::"l"(outp), "r"(pack_bf16(o0, o1)),
                     "r"((uint32_t)(lane < 16 && h == NH)) : "memory");
    }
}

__device__ __noinline__ void f_collect(const unsigned (*flag)[32], unsigned full, const float4* src, unsigned todo, uint32_t sbase) {
    const int lane = threadIdx.x & 31, g = lane >> 2, t = lane & 3;
    const bool last = todo != 15;
    unsigned n = 0;
    while (todo) {
        const unsigned v = ld_acquire(&flag[t][0]);
        unsigned m = __ballot_sync(~0u, v == full) & todo;
        if (m == 0) {
            if (!last || __shfl_sync(~0u, v, 0) == 0) __nanosleep(200);
            if (++n > SPIN_LIMIT) __trap();
            continue;
        }
        __syncwarp();
        todo ^= m;
        do {
            const int h0 = __ffs(m) - 1, h1 = 31 - __clz(m);
            m &= ~((1u << h0) | (1u << h1));
            float4 x[8];
#pragma unroll
            for (int b = 0; b < 8; b++) x[b] = ld_relaxed16(src + ((b & 4) ? h1 : h0) * 128 + (b & 3) * 32 + lane);
#pragma unroll
            for (int b = 0; b < 8; b++) {
                const uint32_t lo = pack_bf16(x[b].x, x[b].y), hi = pack_bf16(x[b].z, x[b].w);
                const uint32_t o = __shfl_xor_sync(~0u, (g & 1) ? lo : hi, 4);
                const uint32_t e0 = (g & 1) ? o : lo, e1 = (g & 1) ? hi : o;
                asm volatile("st.shared.v2.u32 [%0], {%1,%2};"
                             ::"r"(sbase + F_BF + ((b & 4) ? h1 : h0) * 1024 + t * 256 + ((b ^ t) & 3) * 64 + g * 8),
                               "r"(__byte_perm(e0, e1, 0x5410)), "r"(__byte_perm(e0, e1, 0x7632)) : "memory");
            }
            __syncwarp();
            if (lane < (h0 == h1 ? 1 : 2))
                asm volatile("mbarrier.arrive.shared::cta.b64 _, [%0];" ::"r"(sbase + F_BAR + 32 + (lane ? h1 : h0) * 8) : "memory");
        } while (m);
    }
}

__device__ __forceinline__ void f_request(const Params& p, const CUtensorMap* tm, int panel, int rank, int nsl, int delay, int step, unsigned tag,
                                          uint32_t sbase, uint64_t pol) {
    const int lane = threadIdx.x & 31;
    if (lane == 0) asm volatile("prefetch.tensormap [%0];" ::"l"(tm) : "memory");
    unsigned long long v;
    unsigned n = 0;
    while (!__all_sync(~0u, (v = ld_relaxed64(&scratch(p)->dry[blockIdx.x >> 3][lane >> 2])) >> 32 == tag)) {
        __nanosleep(200);
        if (++n > SPIN_LIMIT) __trap();
    }
    const uint32_t t0 = __shfl_sync(~0u, (uint32_t)v, 0);
    uint32_t due = t0 + (__reduce_add_sync(~0u, (int)((uint32_t)v - t0)) >> 5);
    due += delay;
#pragma unroll 1
    for (int q = 0; q < 8 * nsl; q++, due += step) {
        if (q >= LAG * nsl) mbar_spin(sbase + F_BAR + 64 + (q - LAG * nsl) * 8);
        if (rank == 7 && q == 8 * nsl - 1) due += TOWN;
        while ((int)(time_ns() - due) < 0 && ++n < SPIN_LIMIT) {}
        tma3d_warp(sbase + F_W - (q >> 3) * 2 * SLOT + (q & 7) * 8192, tm, 0, (rank * 8 + (q & 7)) * 64, panel + (q >> 3), sbase + F_BAR + 64 + q * 8,
                   8192, pol);
    }
}

__device__ __forceinline__ void f_project(const Params& p, int rank, int j, int nsl, uint32_t sbase, __nv_bfloat16* out) {
    const int lane = threadIdx.x & 31, g = lane >> 2, t = lane & 3;
    const uint32_t wa = sbase + F_W + ((lane & 7) + (lane >> 4) * 8) * 128 + (((2 * j + ((lane >> 3) & 1)) ^ (lane & 7)) * 16);
    const uint32_t ba = sbase + F_BF + (g & 3) * 64 + t * 16;
    const bool up = t & 2;
#pragma unroll 1
    for (int sl = 0; sl < nsl; sl++) {
        const int owner = 8 - nsl + sl;
        const uint32_t rdst = mapa(sbase + F_RX + min(rank, 6) * 1024 + j * 256 + lane * 8, owner);
        const uint32_t rbar = mapa(sbase + F_BAR + j * 8, owner);
        __nv_bfloat16* dst = out + sl * 64 + (t & 1) * (4 * DM) + j * 16 + (t >> 1) * 8 + g;
        uint32_t src = sbase + F_RX + j * 256 + lane * 8;
        asm volatile("" : "+l"(dst), "+r"(src));
        float acc[2][4];
#pragma unroll
        for (int k = 0; k < 8; k++) acc[k >> 2][k & 3] = 0.f;
#pragma unroll 1
        for (int hp = 0; hp < 2; hp++) {
            uint32_t wp = wa + hp * 32768 - sl * 2 * SLOT, bar = sbase + F_BAR + 64 + sl * 64 + hp * 32, last = hp;
            uint32_t bf[2][4][4];
#pragma unroll
            for (int e = 0; e < 2; e++) {
                mbar_spin(sbase + F_BAR + 32 + hp * 16 + e * 8);
#pragma unroll
                for (int s = 0; s < 4; s++)
                    asm volatile("ld.shared.v4.u32 {%0,%1,%2,%3}, [%4];" : "=r"(bf[e][s][0]), "=r"(bf[e][s][1]), "=r"(bf[e][s][2]), "=r"(bf[e][s][3])
                                 : "r"(((ba + hp * 2048 + e * 1024) ^ (s * 64)) + s * 256) : "memory");
            }
            uint32_t send = hp && rank != owner, obar = hp ? sbase + F_BAR + j * 8 : bar;
            asm volatile("" : "+r"(wp), "+r"(bar), "+r"(last), "+r"(send), "+r"(obar));
#pragma unroll
            for (int e = 0; e < 2; e++) {
                uint32_t a[8][4];
#pragma unroll
                for (int q = 0; q < 2; q++) {
                    mbar_spin(bar + e * 16 + q * 8);
#pragma unroll
                    for (int s = 4 * q; s < 4 * q + 4; s++) ldsm4t(a[s], wp + e * 16384 + s * 2048);
                }
#pragma unroll
                for (int s = 0; s < 8; s++) mma16816(acc[s & 1], a[s], bf[e][s & 3][(s >> 2) * 2], bf[e][s & 3][(s >> 2) * 2 + 1]);
            }
            const float v0 = up ? acc[0][2] + acc[1][2] : acc[0][0] + acc[1][0], v1 = up ? acc[0][3] + acc[1][3] : acc[0][1] + acc[1][1];
            asm volatile("{\n.reg .pred p;\nsetp.ne.u32 p, %4, 0;\n"
                         "@p st.async.weak.shared::cluster.mbarrier::complete_tx::bytes.v2.b32 [%0], {%1,%2}, [%3];\n}"
                         ::"r"(rdst), "r"(__float_as_uint(v0)), "r"(__float_as_uint(v1)), "r"(rbar), "r"(send) : "memory");
            if (rank == owner) {
                mbar_spin_cluster(obar);
                float2 x[7];
#pragma unroll
                for (int r = 0; r < 7; r++) asm volatile("ld.shared.v2.f32 {%0,%1}, [%2];" : "=f"(x[r].x), "=f"(x[r].y) : "r"(src + r * 1024) : "memory");
                const uint32_t o = pack_bf16(((v0 + x[0].x) + (x[1].x + x[2].x)) + ((x[3].x + x[4].x) + (x[5].x + x[6].x)),
                                             ((v1 + x[0].y) + (x[1].y + x[2].y)) + ((x[3].y + x[4].y) + (x[5].y + x[6].y)));
                asm volatile("{\n.reg .pred p;\n.reg .b16 a, b;\nsetp.ne.u32 p, %2, 0;\nmov.b32 {a, b}, %1;\n@p st.global.u16 [%0], a;\n@p st.global.u16 [%0+2304], b;\n}"
                             ::"l"(dst), "r"(o), "r"(last) : "memory");
            }
        }
    }
}

constexpr int BS_WUK = 5, BS_Q = 9, BS_CKV = 11, BS_PART = 27, BS_WUV = 29, BS_END = 33;

__device__ __noinline__ void b_issue(const Params& p, int n, int bi, uint32_t sbase, uint64_t pol) {
    if (n >= BS_END || (n >= BS_Q && n < BS_CKV) || (n >= BS_PART && n < BS_WUV)) return;
    const uint32_t bar = sbase + M_BAR + (NSLOT + n % BRING) * 8;
    const CUtensorMap* tm;
    int row, panel = 2 * bi;
    if (n < BS_WUK) { tm = &p.tm_wq; row = n * 128; }
    else if (n < BS_Q) { tm = &p.tm_wuk; row = (n - BS_WUK) * 128; }
    else if (n < BS_PART) {
        tm = &p.tm_ckv; panel = 0;
        row = (bi >> 3) * SK + ((n - BS_CKV) * 8 + (bi & 7)) * 32;
    }
    else { tm = &p.tm_wuv; row = (n - BS_WUV) * 128; }
    mbar_expect_tx(bar, n == 0 ? 32768 + 4 * 1152 : 32768);
    tma3d(sbase + (n % BRING) * SLOT, tm, 0, row, panel, bar, pol);
}
__device__ __forceinline__ void b_issue_xchg(int n, const void* src, uint32_t sbase, uint64_t pol) {
    asm volatile("fence.proxy.async;" ::: "memory");
#pragma unroll
    for (int i = 0; i < 2; i++) {
        const uint32_t bar = sbase + M_BAR + (NSLOT + (n + i) % BRING) * 8;
        mbar_expect_tx(bar, 32768);
        bulk_load(sbase + ((n + i) % BRING) * SLOT, reinterpret_cast<const char*>(src) + i * 32768, 32768, bar, pol);
    }
}
__device__ __forceinline__ void b_wait(int n, uint32_t sbase) {
    mbar_wait(sbase + M_BAR + (NSLOT + n % BRING) * 8, (n / BRING) & 1);
}

__device__ __noinline__ void b_gemm(const Params& p, uint32_t sbase, int n0, int n1, int ktot, uint32_t xh, uint32_t xl, int pitch,
                                    int bi, uint64_t pol) {
    const int tid = threadIdx.x, warp = tid >> 5, lane = tid & 31, g = lane >> 2, t = lane & 3;
    const uint32_t woff = (warp >> 2) * 16384 + (lane & 15) * 128 + ((((warp & 3) * 2 + (lane >> 4)) ^ (lane & 7)) * 16);
    const uint32_t xoff = (g & 3) * pitch + t * 4;
    float acc[2][4];
#pragma unroll
    for (int i = 0; i < 8; i++) acc[i >> 2][i & 3] = 0.f;
#pragma unroll 1
    for (int n = n0; n < n1; n++) {
        b_wait(n, sbase);
        const uint32_t slot = sbase + (n % BRING) * SLOT + woff;
        const int k0 = (n - n0) * 128;
        const int ns = min(8, (ktot - k0) >> 4);
#pragma unroll 2
        for (int s = 0; s < ns; s++) {
            uint32_t a[4], w[4];
            const uint32_t xo = xoff + (k0 + 16 * s) * 2;
            a[0] = lds32(xh + xo); a[2] = lds32(xh + xo + 16);
            a[1] = xl ? lds32(xl + xo) : 0u; a[3] = xl ? lds32(xl + xo + 16) : 0u;
            ldsm4t(w, slot + s * 2048);
            mma16816(acc[0], a, w[0], w[1]);
            mma16816(acc[1], a, w[2], w[3]);
        }
        __syncthreads();
        if (tid == 0) b_issue(p, n + BD, bi, sbase, pol);
    }
    if (g < 4) {
#pragma unroll
        for (int j = 0; j < 2; j++)
            asm volatile("st.shared.u32 [%0], %1;" ::"r"(sbase + M_QB + g * QP + (warp * 16 + j * 8 + t * 2) * 2),
                         "r"(pack_bf16(acc[j][0] + acc[j][2], acc[j][1] + acc[j][3])) : "memory");
    }
    __syncthreads();
}

__device__ __forceinline__ void b_exchange(unsigned* c, int n, const void* src, uint32_t sbase, uint64_t pol) {
    __syncthreads();
    if (threadIdx.x == 0) {
        fence_gpu();
        red_add_u32(c, 1u);
        wait_count(c, NBCTA);
        b_issue_xchg(n, src, sbase, pol);
    }
}

template <bool CLU>
__device__ __noinline__ void b_chain(const Params& p, char* smem, uint32_t sbase, int bi, unsigned epoch, uint64_t pol) {
    const int tid = threadIdx.x, warp = tid >> 5, lane = tid & 31, g = lane >> 2, t = lane & 3;
    unsigned (*ctl)[32] = scratch(p)->ctl[epoch & 1];
    float* red = reinterpret_cast<float*>(smem + 5 * SLOT);
    __syncthreads();
    b_gemm(p, sbase, 0, BS_WUK, DM, sbase + M_XB, 0, XP, bi, pol);
    {
        uint32_t Q[16];
#pragma unroll
        for (int c = 0; c < 16; c++) Q[c] = lds32(sbase + M_QB + (g & 3) * QP + c * 16 + t * 4);
        float* qa = reinterpret_cast<float*>(smem + M_QA);
#pragma unroll 1
        for (int n = BS_WUK; n < BS_Q; n++) {
            b_wait(n, sbase);
            const uint32_t base = sbase + (n % BRING) * SLOT + (warp * 16 + (lane & 15)) * 128;
            float d[2][4];
#pragma unroll
            for (int i = 0; i < 8; i++) d[i >> 2][i & 3] = 0.f;
#pragma unroll
            for (int s = 0; s < 8; s++) {
                uint32_t a[4];
                ldsm4(a, base + (s >> 2) * 16384 + (((2 * (s & 3) + (lane >> 4)) ^ (lane & 7)) * 16));
                mma16816(d[s & 1], a, Q[2 * s], Q[2 * s + 1]);
            }
            const int c = (n - BS_WUK) * 128 + warp * 16 + g + 8 * (t >> 1);
            qa[(2 * (t & 1)) * 512 + c] = (t & 2) ? d[0][2] + d[1][2] : d[0][0] + d[1][0];
            qa[(2 * (t & 1) + 1) * 512 + c] = (t & 2) ? d[0][3] + d[1][3] : d[0][1] + d[1][1];
            __syncthreads();
            if (tid == 0) b_issue(p, n + BD, bi, sbase, pol);
        }
#pragma unroll 1
        for (int r = 0; r < 2; r++) {
            const int id = tid + r * 256;
            const int b = id >> 7, c0 = ((id >> 2) & 31) * 16 + (id & 3) * 2;
            const float2 u0 = *reinterpret_cast<const float2*>(qa + b * 512 + c0);
            const float2 u1 = *reinterpret_cast<const float2*>(qa + b * 512 + c0 + 8);
            const uint32_t h0 = pack_bf16(u0.x, u0.y), h1 = pack_bf16(u1.x, u1.y);
            const uint32_t l0 = pack_bf16(u0.x - bf_lo(h0), u0.y - bf_hi(h0)), l1 = pack_bf16(u1.x - bf_lo(h1), u1.y - bf_hi(h1));
            scratch(p)->qabs[((id >> 2) * 4 + (bi >> 3)) * 32 + (bi & 7) * 4 + (id & 3)] = make_uint4(h0, l0, h1, l1);
        }
    }
    b_exchange(&ctl[C_BBAR][0], BS_Q, &scratch(p)->qabs[(bi >> 3) * 4096], sbase, pol);
    {
        uint32_t qf[4][4][4];
        b_wait(BS_Q + (warp >> 2), sbase);
        {
            const uint4* qs = reinterpret_cast<const uint4*>(smem + ((BS_Q + (warp >> 2)) % BRING) * SLOT) + (warp & 3) * 512 + lane;
#pragma unroll
            for (int s = 0; s < 4; s++)
#pragma unroll
                for (int i = 0; i < 4; i++) {
                    const uint4 v = qs[(s * 4 + i) * 32];
                    qf[i][s][0] = v.x; qf[i][s][1] = v.y; qf[i][s][2] = v.z; qf[i][s][3] = v.w;
                }
        }
        __syncthreads();
        if (tid == 0) { b_issue(p, BS_Q + BD, bi, sbase, pol); b_issue(p, BS_Q + 1 + BD, bi, sbase, pol); }
        float acc[2][8][4];
#pragma unroll
        for (int i = 0; i < 2; i++)
#pragma unroll
            for (int j = 0; j < 8; j++) { acc[i][j][0] = acc[i][j][1] = acc[i][j][2] = acc[i][j][3] = 0.f; }
        float mrun = -INFINITY, lrun = 0.f;
        const int head = tid >> 3, kq = tid & 7;
        float* alpha = reinterpret_cast<float*>(smem + M_ALPHA);
        for (int n = BS_CKV; n < BS_PART; n++) {
            b_wait(n, sbase);
            const uint32_t slot = sbase + (n % BRING) * SLOT;
            float sc[4][4][4];
#pragma unroll
            for (int i = 0; i < 4; i++)
#pragma unroll
                for (int j = 0; j < 4; j++) { sc[i][j][0] = sc[i][j][1] = sc[i][j][2] = sc[i][j][3] = 0.f; }
#pragma unroll
            for (int j = 0; j < 4; j++)
#pragma unroll
                for (int sp = 0; sp < 2; sp++) {
                    uint32_t bf[4];
                    ldsm4(bf, slot + warp * 4096 + (8 * j + (lane & 7)) * 128 + (((4 * sp + (lane >> 3)) ^ (lane & 7)) * 16));
#pragma unroll
                    for (int i = 0; i < 4; i++) {
                        mma16816(sc[i][j], qf[i][2 * sp], bf[0], bf[1]);
                        mma16816(sc[i][j], qf[i][2 * sp + 1], bf[2], bf[3]);
                    }
                }
#pragma unroll
            for (int i = 0; i < 4; i++)
#pragma unroll
                for (int j = 0; j < 4; j++)
                    *reinterpret_cast<float2*>(red + warp * 1024 + (8 * i + g) * 32 + ((8 * j) ^ (8 * (g & 3))) + 2 * t) =
                        make_float2(sc[i][j][0] + sc[i][j][2], sc[i][j][1] + sc[i][j][3]);
            __syncthreads();
            if (tid == 0 && n > BS_CKV) b_issue(p, n - 1 + BD, bi, sbase, pol);
            {
                float4 s = make_float4(0.f, 0.f, 0.f, 0.f);
#pragma unroll
                for (int w = 0; w < 8; w++) {
                    const float4 v = *reinterpret_cast<const float4*>(red + w * 1024 + head * 32 + ((4 * kq) ^ (8 * (head & 3))));
                    s.x += v.x; s.y += v.y; s.z += v.z; s.w += v.w;
                }
                const uint32_t r0 = pack_bf16(s.x, s.y), r1 = pack_bf16(s.z, s.w);
                const uint32_t s0 = pack_bf16(bf_lo(r0) * SCALE, bf_hi(r0) * SCALE);
                const uint32_t s1 = pack_bf16(bf_lo(r1) * SCALE, bf_hi(r1) * SCALE);
                const float f0 = bf_lo(s0), f1 = bf_hi(s0), f2 = bf_lo(s1), f3 = bf_hi(s1);
                float mx = fmaxf(fmaxf(f0, f1), fmaxf(f2, f3));
                mx = fmaxf(mx, __shfl_xor_sync(~0u, mx, 1));
                mx = fmaxf(mx, __shfl_xor_sync(~0u, mx, 2));
                mx = fmaxf(mx, __shfl_xor_sync(~0u, mx, 4));
                const float mnew = fmaxf(mrun, mx);
                const float al = expsub(mrun, mnew);
                const float p0 = expsub(f0, mnew), p1 = expsub(f1, mnew), p2 = expsub(f2, mnew), p3 = expsub(f3, mnew);
                lrun = lrun * al + ((p0 + p1) + (p2 + p3));
                mrun = mnew;
                *reinterpret_cast<uint2*>(smem + M_P + head * 80 + kq * 8) = make_uint2(pack_bf16(p0, p1), pack_bf16(p2, p3));
                if (kq == 0) alpha[head] = al;
            }
            __syncthreads();
            {
                uint32_t pf[2][2][4];
#pragma unroll
                for (int i = 0; i < 2; i++)
#pragma unroll
                    for (int ks = 0; ks < 2; ks++)
                        ldsm4(pf[i][ks], sbase + M_P + (16 * i + (lane & 15)) * 80 + (16 * ks + 8 * (lane >> 4)) * 2);
#pragma unroll
                for (int i = 0; i < 2; i++) {
                    const float a0 = alpha[16 * i + g], a1 = alpha[16 * i + 8 + g];
#pragma unroll
                    for (int j = 0; j < 8; j++) { acc[i][j][0] *= a0; acc[i][j][1] *= a0; acc[i][j][2] *= a1; acc[i][j][3] *= a1; }
                }
#pragma unroll
                for (int j = 0; j < 8; j++) {
                    uint32_t bf[4];
                    ldsm4t(bf, slot + warp * 4096 + lane * 128 + ((j ^ (lane & 7)) * 16));
#pragma unroll
                    for (int i = 0; i < 2; i++) {
                        mma16816(acc[i][j], pf[i][0], bf[0], bf[1]);
                        mma16816(acc[i][j], pf[i][1], bf[2], bf[3]);
                    }
                }
            }
        }
        __syncthreads();
        if (tid == 0) b_issue(p, BS_PART - 1 + BD, bi, sbase, pol);
        lrun += __shfl_xor_sync(~0u, lrun, 1);
        lrun += __shfl_xor_sync(~0u, lrun, 2);
        lrun += __shfl_xor_sync(~0u, lrun, 4);
        if (kq == 0) scratch(p)->bml[head * NBCTA + bi] = make_float2(mrun, lrun);
#pragma unroll
        for (int i = 0; i < 2; i++)
#pragma unroll
            for (int j = 0; j < 8; j++) {
                scratch(p)->bpart[((16 * i + g) * NBCTA + bi) * 256 + warp * 32 + j * 4 + t] = make_float2(acc[i][j][0], acc[i][j][1]);
                scratch(p)->bpart[((16 * i + 8 + g) * NBCTA + bi) * 256 + warp * 32 + j * 4 + t] = make_float2(acc[i][j][2], acc[i][j][3]);
            }
    }
    b_exchange(&ctl[C_BBAR + 1][0], BS_PART, &scratch(p)->bpart[bi * NBCTA * 256], sbase, pol);
    {
        float* omega = reinterpret_cast<float*>(smem + M_OMEGA);
        if (warp == 0) {
            __syncwarp();
            const uint2 ml = ld_relaxed8(&scratch(p)->bml[bi * NBCTA + lane]);
            const float ms = __uint_as_float(ml.x);
            float m = ms;
            m = fmaxf(m, __shfl_xor_sync(~0u, m, 1));
            m = fmaxf(m, __shfl_xor_sync(~0u, m, 2));
            m = fmaxf(m, __shfl_xor_sync(~0u, m, 4));
            const float w = expsub(ms, m);
            float l = w * __uint_as_float(ml.y);
            l += __shfl_xor_sync(~0u, l, 1);
            l += __shfl_xor_sync(~0u, l, 2);
            l += __shfl_xor_sync(~0u, l, 4);
            omega[lane] = w / l;
        }
        __syncthreads();
        b_wait(BS_PART, sbase);
        b_wait(BS_PART + 1, sbase);
#pragma unroll 1
        for (int b = 0; b < 4; b++) {
            const float2* ps = reinterpret_cast<const float2*>(smem + ((BS_PART + (b >> 1)) % BRING) * SLOT) + (b & 1) * 2048 + tid;
            float c0 = 0.f, c1 = 0.f;
#pragma unroll
            for (int s = 0; s < 8; s++) {
                const float w = omega[b * 8 + s];
                const float2 v = ps[s * 256];
                c0 = fmaf(w, v.x, c0);
                c1 = fmaf(w, v.y, c1);
            }
            const uint32_t hi = pack_bf16(c0, c1);
            *reinterpret_cast<uint32_t*>(smem + M_CH + b * CP + tid * 4) = hi;
            *reinterpret_cast<uint32_t*>(smem + M_CL + b * CP + tid * 4) = pack_bf16(c0 - bf_lo(hi), c1 - bf_hi(hi));
        }
        __syncthreads();
        if (tid == 0) { b_issue(p, BS_PART + BD, bi, sbase, pol); b_issue(p, BS_PART + 1 + BD, bi, sbase, pol); }
    }
    b_gemm(p, sbase, BS_WUV, BS_END, 512, sbase + M_CH, sbase + M_CL, CP, bi, pol);
    if (CLU) {
        if (warp < 4) {
            const unsigned short* c = reinterpret_cast<const unsigned short*>(smem + M_QB + warp * QP) + 16 * t + g;
            scratch(p)->octx[(bi * 4 + warp) * 32 + lane] = make_float4(bf_lo(c[0]), bf_lo(c[8]), bf_lo(c[64]), bf_lo(c[72]));
        }
        __syncthreads();
        if (tid == 0) asm volatile("st.release.gpu.global.u32 [%0], %1;" ::"l"(&scratch(p)->cdone[bi][0]), "r"(epoch + 1) : "memory");
        return;
    }
    if (tid == 0) {
#pragma unroll 1
        for (int i = 0; i < 4; i++) {
            mbar_expect_tx(sbase + M_BAR + i * 8, 36864);
            tma3d(sbase + i * 36864, &p.tm_wo, 0, bi * 128 + i * 32, 0, sbase + M_BAR + i * 8, pol);
        }
    }
    {
        float acc[9][4];
#pragma unroll
        for (int j = 0; j < 9; j++) { acc[j][0] = acc[j][1] = acc[j][2] = acc[j][3] = 0.f; }
#pragma unroll 1
        for (int i = 0; i < 4; i++) {
            const uint32_t xo = sbase + M_QB + (g & 3) * QP + i * 64 + t * 4;
            const uint32_t a0[4] = {lds32(xo), 0u, lds32(xo + 16), 0u}, a1[4] = {lds32(xo + 32), 0u, lds32(xo + 48), 0u};
            mbar_wait(sbase + M_BAR + i * 8, 0);
#pragma unroll
            for (int j = 0; j < 9; j++) {
                const int nt = warp * 9 + j;
                uint32_t w[4];
                ldsm4t(w, sbase + i * 36864 + (nt >> 3) * 4096 + lane * 128 + (((nt & 7) ^ (lane & 7)) * 16));
                mma16816(acc[j], a0, w[0], w[1]);
                mma16816(acc[j], a1, w[2], w[3]);
            }
        }
        if (g < 4) {
#pragma unroll
            for (int j = 0; j < 9; j++) {
                const int c2 = (warp * 9 + j) * 4 + t;
                st_tagged2(&scratch(p)->outb[((c2 / 9) * NH + bi) * 36 + g * 9 + c2 % 9], acc[j][0], acc[j][1], epoch + 1);
            }
        }
    }
    {
        const uint4* src = scratch(p)->outb + (bi * NH + (tid >> 3)) * 36 + (tid & 7);
        float2* part = reinterpret_cast<float2*>(red);
        unsigned n = 0;
        while (true) {
            ulonglong2 v[5];
            bool ok = true;
#pragma unroll
            for (int i = 0; i < 5; i++)
                if (i < 4 || (tid & 7) < 4) v[i] = ld_tagged2(src + i * 8);
#pragma unroll
            for (int i = 0; i < 5; i++)
                if (i < 4 || (tid & 7) < 4) {
                    ok = ok && (unsigned)(v[i].x >> 32) == epoch + 1 && (unsigned)(v[i].y >> 32) == epoch + 1;
                    part[(tid >> 3) * 36 + (tid & 7) + i * 8] = make_float2(__uint_as_float((unsigned)v[i].x), __uint_as_float((unsigned)v[i].y));
                }
            if (ok) break;
            __nanosleep(400);
            if (++n > SPIN_LIMIT) __trap();
        }
        __syncthreads();
        if (tid < 36) {
            float s0 = 0.f, s1 = 0.f;
#pragma unroll 8
            for (int h = 0; h < NH; h++) { const float2 v = part[h * 36 + tid]; s0 += v.x; s1 += v.y; }
            *reinterpret_cast<uint32_t*>(p.out + (tid / 9) * 2 * DM + DM + bi * 18 + (tid % 9) * 2) = pack_bf16(s0, s1);
        }
    }
}

template <bool CLU>
__global__ void __launch_bounds__(256, 1) fused_decode_kernel(const __grid_constant__ Params p) {
    asm volatile("{\n.reg .pred p;\n.reg .u32 a;\n.reg .u64 b;\nsub.u32 a, %1, 128;\nsetp.lt.u32 p, a, %3;\nmad.lo.u32 a, %2, %3, %1;\n"
                 "mad.wide.u32 b, a, 128, %0;\n@p prefetch.global.L2 [b];\n}"
                 ::"l"(p.kc), "r"(threadIdx.x), "r"(blockIdx.x), "n"(PFN) : "memory");
    if (blockIdx.x >= 1024) return;
    extern __shared__ __align__(1024) char smem_raw[];
    const uint32_t sbase = (smem_u32(smem_raw) + 1023u) & ~1023u;
    char* smem = smem_raw + (sbase - smem_u32(smem_raw));
    const int tid = threadIdx.x, warp = __shfl_sync(~0u, tid >> 5, 0), lane = tid & 31;
    const int cl = blockIdx.x >> 3, rank = blockIdx.x & 7;
    const bool isB = CLU ? rank < (cl < MINCL - 2 ? 2 : 3) : (blockIdx.x & 3) == 0 && blockIdx.x < 4 * NBCTA;
    const int bi = CLU ? (rank < 2 ? 2 * cl + rank : cl + MINCL + 2) : blockIdx.x >> 2;
    const int nb = CLU ? 6 * cl + rank - 2 - max(0, cl - (MINCL - 3)) : blockIdx.x - min(NBCTA, (blockIdx.x + 3) >> 2);
    const int blk = CLU ? (isB ? bi : NBCTA + nb) : blockIdx.x;
    const int nblk = CLU ? 8 * MINCL : gridDim.x, nnb = nblk - NBCTA;
    const int nstatic = nnb * (NW + XW);
    uint64_t pol;
    asm volatile("createpolicy.fractional.L2::evict_first.b64 %0, 1.0;" : "=l"(pol));
    const uint32_t wbar = sbase + M_BAR + warp * 8, wslot = sbase + warp * SLOT;
    const int u0 = warp * nnb + nb;
    const bool hold = blk < 16;
    const uint32_t jbar = sbase + M_BAR + (NSLOT + BRING) * 8;
    if (warp < 4) {
        const char* src = reinterpret_cast<const char*>(p.kc) + (size_t)(((unsigned)u0 >> 7) * 1024 + (u0 & 127)) * TILE_BYTES;
        asm volatile("" : "+l"(src));
        mbar_init_warp(wbar);
        if (warp < NEARLY && !isB && (CLU || !hold)) tile_load_warp(wslot, src, wbar, pol);
    }
    asm volatile("" ::: "memory");
    if (warp == 7) {
        if (blk < 128) {
            uint64_t poln;
            asm volatile("createpolicy.fractional.L2::evict_normal.b64 %0, 1.0;" : "=l"(poln));
            mbar_init_warp(jbar);
            tma3d_warp(sbase + J0W, &p.tm_j0, blk * 32, 0, 0, jbar, 36864, poln);
            mbar_init_warp(jbar + 8);
            if (lane == 0) {
                mbar_expect_tx(jbar + 8, 4608);
                bulk_load(sbase + M_XA, p.xa, 4608, jbar + 8, poln);
            }
        }
        if (lane < 8) reinterpret_cast<unsigned*>(smem + M_HELP)[lane] = 0;
        __syncwarp();
        asm volatile("bar.arrive 2, %0;" ::"r"(isB ? 64 : 32 * (NW + XW + 1)) : "memory");
    }
    unsigned epoch = 0;
    if (lane == 0) epoch = ld_relaxed4(scratch(p)->epoch);
    if (blk >= 128 ? warp >= 4 : isB && warp < 4) epoch = __shfl_sync(~0u, epoch, 0);
    if (isB && warp == 3) asm volatile("bar.sync 2, 64;" ::: "memory");
    if (isB && tid == 96) {
#pragma unroll 1
        for (int i = 0; i < BRING; i++) mbar_init(sbase + M_BAR + (NSLOT + i) * 8, 1);
        asm volatile("fence.mbarrier_init.release.cluster;" ::: "memory");
        if (hold) { unsigned n = 0; while (ld_acquire_cta_shared(sbase + M_HELP + 24) < 2) { if (++n > (SPIN_LIMIT << 4)) __trap(); } }
#pragma unroll 1
        for (int b = 0; b < 4; b++) bulk_load(sbase + M_XB + b * XP, p.xb + b * DM, 1152, sbase + M_BAR + NSLOT * 8, pol);
#pragma unroll 1
        for (int n = 0; n < BD; n++) b_issue(p, n, bi, sbase, pol);
    }
    if (warp >= 4 && blk < 128) {
        const int g = lane >> 2, t = lane & 3, j = tid - 128;
        asm volatile("bar.sync 1, 128;" ::: "memory");
#pragma unroll 1
        for (int ph = -1;; ph++) {
        const int sl = ph > 0 ? blk + 128 - nblk : blk;
        const uint32_t wa = sbase + J0W + ((warp - 4) * 144 + (lane & 7) + (lane >> 4) * 8) * 64 + ((((lane >> 3) & 1) ^ ((lane >> 1) & 3)) * 16);
        const uint32_t xa = sbase + M_XA + (g & 3) * 1152 + (warp - 4) * 288 + t * 4;
        if (ph >= 0) mbar_wait(jbar + 8, 0);
        uint32_t xb[18];
#pragma unroll
        for (int s = 0; s < 18; s++) xb[s] = lds32(xa + s * 16);
        epoch = __shfl_sync(~0u, epoch, 0);
        if (ph >= 0) mbar_wait(jbar, ph);
        float acc[4][4];
#pragma unroll
        for (int i = 0; i < 16; i++) acc[i >> 2][i & 3] = 0.f;
#pragma unroll
        for (int s = 0; s < 18; s++) {
            uint32_t w[4];
            ldsm4t(w, (wa ^ ((s & 1) * 32)) + (s >> 1) * 1024);
            mma16816(acc[s & 3], w, xb[s & ~1], xb[s | 1]);
        }
        float2* j0 = reinterpret_cast<float2*>(smem + M_J0);
        {
            float* jf = reinterpret_cast<float*>(j0) + (warp - 4) * 128 + (t & 1) * 64 + (t >> 1) * 8 + g;
#pragma unroll
            for (int i = 0; i < 4; i++)
                jf[(i & 1) * 32 + (i >> 1) * 16] = (t & 2) ? acc[i >> 1][2 + (i & 1)] + acc[2 + (i >> 1)][2 + (i & 1)] : acc[i >> 1][i & 1] + acc[2 + (i >> 1)][i & 1];
        }
        asm volatile("bar.sync 1, 128;" ::: "memory");
        const bool again = ph == 0 && blk + 128 - nblk >= nblk;
        if (again && tid == 224) {
            mbar_expect_tx(jbar, 36864);
            tma3d(sbase + J0W, &p.tm_j0, (blk + 128 - nblk) * 32, 0, 0, jbar, pol);
        }
        if (warp < 6) {
            const float2 v0 = j0[j], v1 = j0[64 + j], v2 = j0[128 + j], v3 = j0[192 + j];
            asm volatile("{\n.reg .pred p;\n.reg .b64 v;\nsetp.ge.s32 p, %3, 0;\nmov.b64 v, {%1, %2};\n@p st.relaxed.gpu.global.u64 [%0], v;\n}"
                         ::"l"(&scratch(p)->qll[(j >> 4) * 2048 + sl * 16 + (j & 15)]),
                           "r"(pack_bf16((v0.x + v1.x) + (v2.x + v3.x), (v0.y + v1.y) + (v2.y + v3.y))), "r"(epoch + 1), "r"(ph) : "memory");
            __syncwarp();
            if (lane == 0 && ph >= 0) asm volatile("red.relaxed.cta.shared::cta.add.u32 [%0], 1;" ::"r"(sbase + M_HELP + 24) : "memory");
        } else if (warp == 7) {
            if (blk < C_LINES && ph == 0) scratch(p)->ctl[(epoch & 1) ^ 1][blk][lane] = 0;
        }
        if (ph >= 0 && !again) break;
        asm volatile("bar.sync 1, 128;" ::: "memory");
        }
    }
    if (CLU) {
        if (warp == 6) {
            if (lane < 24) mbar_init(sbase + F_BAR + lane * 8, 1);
            if (lane < 4) mbar_expect_tx(sbase + F_BAR + lane * 8, 7 * 256);
            asm volatile("fence.mbarrier_init.release.cluster;" ::: "memory");
        }
        asm volatile("barrier.cluster.arrive.relaxed.aligned;" ::: "memory");
    }
    const int c5 = cl % 5;
    const bool partA = CLU && c5 < 3;
    const int nwork = partA && rank == 7 ? 1 : NW + ((CLU ? rank < 2 + X3C && c5 < 4 : (nb & 3) < X3) ? 1 : 0);
    if (isB) {
        b_chain<CLU>(p, smem, sbase, bi, epoch, pol);
        if (!CLU) return;
        if (warp == 2) {
            unsigned n = 0;
            while (ld_acquire(&scratch(p)->ctl[epoch & 1][C_KDONE][0]) < NUK / 2) { __nanosleep(1000); if (++n > SPIN_LIMIT) __trap(); }
        }
    } else if (warp < NW + XW) {
        a_worker<CLU>(p, u0, warp >= nwork, warp < NEARLY && !hold, hold, nstatic, wslot, wbar, sbase + M_HELP,
                      epoch, pol);
        if (!CLU || warp < nwork) return;
        epoch = __shfl_sync(~0u, epoch, 0);
        unsigned n = 0;
        while (ld_acquire_cta_shared(sbase + M_HELP + 12) == 0) { __nanosleep(1000); if (++n > SPIN_LIMIT) __trap(); }
    } else if (warp == 7) {
#pragma unroll 1
        for (int i = nb; i < 4 * NH; i += nnb) scratch(p)->oacc[i * 32 + lane] = make_float4(0.f, 0.f, 0.f, 0.f);
        if (nb < (CLU ? NREPC : NREP) * NH) scratch(p)->vdone[nb][lane] = 0;
        __syncwarp();
        k_helper(p, sbase + M_HELP, epoch);
        if (nb == 0 && lane == 0) scratch(p)->epoch[0] = epoch + 1;
        __syncwarp();
    } else if (!CLU && nb < NFIN) {
        if (warp == 6) {
            finisher(p, sbase, nb);
        } else if (warp >= 6 - NPOLL) {
            v_poller(p, sbase, nb, warp - (6 - NPOLL));
        }
    }
    if (!CLU) return;
    asm volatile("barrier.cluster.wait.acquire.aligned;" ::: "memory");
    const int nsl = c5 == 4 ? 2 : 1, panel = cl / 5 * 3 + (partA ? c5 : c5 - 3);
    if (warp >= 4) {
        f_project(p, rank, warp - 4, nsl, sbase, p.out + (partA ? 0 : DM) + panel * 64);
        return;
    }
    if (isB ? warp == 2 : warp < 3 || nwork == 3)
        f_collect((partA ? scratch(p)->vdone : scratch(p)->cdone) + 4 * rank, partA ? 4 * UPP : epoch + 1,
                  (partA ? scratch(p)->oacc : scratch(p)->octx) + 4 * rank * 128, nwork == 1 ? 5 * warp : 15, sbase);
    if (warp == 3)
        f_request(p, partA ? &p.tm_fa : &p.tm_fb, panel, rank, nsl, nsl == 2 ? T2A + rank * (T2D / 8) : T1A + rank * (T1D / 8),
                  nsl == 2 ? T2D : T1D, epoch + 1, sbase, pol);
}

}

typedef CUresult (*EncodeFn)(CUtensorMap*, CUtensorMapDataType, cuuint32_t, void*, const cuuint64_t*, const cuuint64_t*,
                             const cuuint32_t*, const cuuint32_t*, CUtensorMapInterleave, CUtensorMapSwizzle,
                             CUtensorMapL2promotion, CUtensorMapFloatOOBfill);

extern "C" void kernel_launch(void* const* d_in, const int* in_sizes, int n_in, void* d_out, int out_size) {
    (void)in_sizes; (void)n_in; (void)out_size;
    static int nsm = 0, ncl = 0;
    static EncodeFn encode = nullptr;
    static void* scr = nullptr;
    cudaLaunchConfig_t cfg = {};
    cudaLaunchAttribute at[1];
    at[0].id = cudaLaunchAttributeClusterDimension;
    at[0].val.clusterDim.x = 8; at[0].val.clusterDim.y = 1; at[0].val.clusterDim.z = 1;
    cfg.blockDim = dim3(256); cfg.dynamicSmemBytes = SMEM_BYTES; cfg.stream = cudaStreamPerThread; cfg.attrs = at; cfg.numAttrs = 1;
    if (nsm == 0) {
        int dev = 0;
        cudaGetDevice(&dev);
        cudaDeviceGetAttribute(&nsm, cudaDevAttrMultiProcessorCount, dev);
        cudaFuncSetAttribute(fused_decode_kernel<false>, cudaFuncAttributeMaxDynamicSharedMemorySize, SMEM_BYTES);
        cudaFuncSetAttribute(fused_decode_kernel<true>, cudaFuncAttributeMaxDynamicSharedMemorySize, SMEM_BYTES);
        cfg.gridDim = dim3(128);
        if (cudaOccupancyMaxActiveClusters(&ncl, fused_decode_kernel<true>, &cfg) != cudaSuccess) { ncl = 0; (void)cudaGetLastError(); }
        if (ncl > MINCL) ncl = MINCL;
        void* fn = nullptr;
        cudaDriverEntryPointQueryResult qr;
        cudaGetDriverEntryPoint("cuTensorMapEncodeTiled", &fn, cudaEnableDefault, &qr);
        encode = (EncodeFn)fn;
        cudaGetSymbolAddress(&scr, g_scratch);
    }
    Params p;
    auto panels = [&](CUtensorMap* tm, void* ptr, int rows, int cols, int box_rows, int box_panels,
                      CUtensorMapL2promotion promo = CU_TENSOR_MAP_L2_PROMOTION_L2_256B) {
        const cuuint64_t gd[3] = {64, (cuuint64_t)rows, (cuuint64_t)(cols / 64)}, gs[2] = {(cuuint64_t)cols * 2, 128};
        const cuuint32_t box[3] = {64, (cuuint32_t)box_rows, (cuuint32_t)box_panels}, es[3] = {1, 1, 1};
        encode(tm, CU_TENSOR_MAP_DATA_TYPE_BFLOAT16, 3, ptr, gd, gs, box, es, CU_TENSOR_MAP_INTERLEAVE_NONE,
               CU_TENSOR_MAP_SWIZZLE_128B, promo, CU_TENSOR_MAP_FLOAT_OOB_FILL_NONE);
    };
    panels(&p.tm_wq, d_in[7], DM, 4096, 128, 2);
    panels(&p.tm_wuk, d_in[8], 512, 4096, 128, 2);
    panels(&p.tm_wuv, d_in[9], 512, 4096, 128, 2);
    panels(&p.tm_wo, d_in[10], 4096, DM, 32, 9);
    panels(&p.tm_ckv, d_in[6], 4 * SK, 512, 32, 8);
    panels(&p.tm_fa, d_in[4], 4096, DM, 64, 1, CU_TENSOR_MAP_L2_PROMOTION_L2_128B);
    panels(&p.tm_fb, d_in[10], 4096, DM, 64, 1, CU_TENSOR_MAP_L2_PROMOTION_L2_128B);
    {
        const cuuint64_t gd[3] = {4096, 192, 3}, gs[2] = {8192, 192 * 8192};
        const cuuint32_t box[3] = {32, 192, 3}, es[3] = {1, 1, 1};
        encode(&p.tm_j0, CU_TENSOR_MAP_DATA_TYPE_BFLOAT16, 3, d_in[3], gd, gs, box, es, CU_TENSOR_MAP_INTERLEAVE_NONE,
               CU_TENSOR_MAP_SWIZZLE_64B, CU_TENSOR_MAP_L2_PROMOTION_L2_128B, CU_TENSOR_MAP_FLOAT_OOB_FILL_NONE);
    }
    p.xa = (const __nv_bfloat16*)d_in[0];
    p.kc = (const __nv_bfloat16*)d_in[1];
    p.vc = (const __nv_bfloat16*)d_in[2];
    p.wo = (const __nv_bfloat16*)d_in[4];
    p.xb = (const __nv_bfloat16*)d_in[5];
    p.out = (__nv_bfloat16*)d_out;
    p.s = (Scratch*)scr;
    if (ncl >= MINCL) {
        cfg.gridDim = dim3(8 * ncl);
        cudaLaunchKernelEx(&cfg, fused_decode_kernel<true>, p);
    } else {
        fused_decode_kernel<false><<<nsm, 256, SMEM_BYTES, cudaStreamPerThread>>>(p);
    }
}
```
